```python
import torch

def _softmax(x, axis=-1):
    return torch.softmax(x, dim=axis)
def _gelu(x):
    return torch.nn.functional.gelu(x, approximate="tanh")
def _silu(x):
    return torch.nn.functional.silu(x)
def _sigmoid(x):
    return torch.sigmoid(x)
def _layernorm(x, axis=-1, eps=1e-5):
    m = x.mean(dim=axis, keepdim=True)
    v = x.var(dim=axis, keepdim=True, unbiased=False)
    return (x - m) / torch.sqrt(v + eps)
def _scatter_add(tgt, idx, src, axis=0):
    return tgt.clone().index_add_(axis, idx, src)
def _segment_sum(src, seg, n):
    out = torch.zeros((n,) + src.shape[1:], dtype=src.dtype)
    return out.index_add_(0, seg, src)
def _pad(x, pw):
    flat = tuple(v for pair in reversed(pw) for v in pair)
    return torch.nn.functional.pad(x, flat)

kernel_name = 'interleave_layers__ssm_conv_s4__sliding_local_dilated__prompt'

def setup_inputs():

    _w = (lambda a: (lambda t: t.to(torch.bfloat16) if t.is_floating_point() else t)(torch.as_tensor(a)))
    def _A_setup():
        B, L, D, N = 1, 2048, 512, 128
        A_re = -(lambda _x: torch.exp(torch.as_tensor(_x)))((lambda *s: torch.randn(*s, dtype=torch.bfloat16) * 1.6)(D, N))
        A_im = torch.pi * (lambda *s: torch.randn(*s, dtype=torch.bfloat16) * 0.1)(D, N)
        B_re = (lambda *s: torch.randn(*s, dtype=torch.bfloat16) * 0.1)(D, N)
        B_im = (lambda *s: torch.randn(*s, dtype=torch.bfloat16) * 0.1)(D, N)
        C_re = (lambda *s: torch.randn(*s, dtype=torch.bfloat16) * 0.1)(D, N)
        C_im = (lambda *s: torch.randn(*s, dtype=torch.bfloat16) * 0.1)(D, N)
        log_dt = (lambda *s: torch.randn(*s, dtype=torch.bfloat16) * 0.1)(D) * 0.5 - 4.0
        Dskip = (lambda *s: torch.randn(*s, dtype=torch.bfloat16) * 0.1)(D)
        return {
            "u": _w((lambda *s: torch.randn(*s, dtype=torch.bfloat16) * 0.05)(B, L, D)),
            "A_re": _w(A_re),
            "A_im": _w(A_im),
            "B_re": _w(B_re),
            "B_im": _w(B_im),
            "C_re": _w(C_re),
            "C_im": _w(C_im),
            "log_dt": _w(log_dt),
            "Dskip": _w(Dskip),
        }
    _A_in = _A_setup()

    def _B_setup():
        B, S, D = 1, 2048, 512
        return {
            "x": _w((lambda *s: torch.randn(*s, dtype=torch.bfloat16) * 0.05)(B, S, D)),
            "wqkv": _w((lambda *s: torch.randn(*s, dtype=torch.bfloat16) * 0.05)(D, 3 * D)),
            "wo": _w((lambda *s: torch.randn(*s, dtype=torch.bfloat16) * 0.05)(D, D)),
        }
    _B_in = _B_setup()

    return {
        "A_u": _A_in["u"],
        "A_A_re": _A_in["A_re"],
        "A_A_im": _A_in["A_im"],
        "A_B_re": _A_in["B_re"],
        "A_B_im": _A_in["B_im"],
        "A_C_re": _A_in["C_re"],
        "A_C_im": _A_in["C_im"],
        "A_log_dt": _A_in["log_dt"],
        "A_Dskip": _A_in["Dskip"],
        "B_x": _B_in["x"],
        "B_wqkv": _B_in["wqkv"],
        "B_wo": _B_in["wo"],
    }

def reference(A_u, A_A_re, A_A_im, A_B_re, A_B_im, A_C_re, A_C_im, A_log_dt, A_Dskip, B_x, B_wqkv, B_wo):
    def _A_ref(u, A_re, A_im, B_re, B_im, C_re, C_im, log_dt, Dskip):
        Bsz, L, D = u.shape
        dt = torch.exp(log_dt)[:, None]
        A = A_re + 1j * A_im
        Bc = B_re + 1j * B_im
        Cc = C_re + 1j * C_im
        logdA = dt * A
        dB = dt * Bc
        l = (lambda x, dt: x.to(dt))(torch.arange(L), A_re.dtype)
        P = torch.exp(logdA[:, :, None] * l[None, None, :])
        K = torch.einsum("dn,dnl,dn->dl", Cc, P, dB).real
        L2 = 2 * L
        Kp = _pad(K, ((0, 0), (0, L)))
        up = (lambda x, *d: x.permute(*d))(u, 0, 2, 1)
        up = _pad(up, ((0, 0), (0, 0), (0, L)))
        Kf = (lambda x, axes=(-2,-1): torch.fft.rfft2(x.float(), dim=axes))(Kp[:, None, :], axes=(-2, -1))
        Uf = (lambda x, axes=(-2,-1): torch.fft.rfft2(x.float(), dim=axes))(up[:, :, None, :], axes=(-2, -1))
        Yf = Uf * Kf[None, :, :, :]
        y = (lambda x, s, axes=(-2,-1): torch.fft.irfft2(x, s=s, dim=axes).to(torch.bfloat16))(Yf, (1, L2), axes=(-2, -1))[:, :, 0, :L]
        y = (lambda x, *d: x.permute(*d))(y, 0, 2, 1) + u * Dskip[None, None, :]
        return y

    def _B_ref(x, wqkv, wo):
        B, S, D = x.shape
        H = 32; Dh = D // H
        W, dil = 8, 2
        qkv = (lambda x, *d: x.permute(*d))((x @ wqkv).reshape(B, S, 3, H, Dh), 2, 0, 3, 1, 4)
        q, k, v = qkv[0], qkv[1], qkv[2]
        scale = Dh ** -0.5
        pos = torch.arange(S)
        off = torch.arange(W) * dil
        idx = pos[:, None] - off[None, :]
        mask = idx >= 0
        idx_c = torch.where(mask, idx, 0).reshape(-1)
        kg = k[:, :, idx_c, :].reshape(B, H, S, W, Dh)
        vg = v[:, :, idx_c, :].reshape(B, H, S, W, Dh)
        logits = torch.einsum("bhsd,bhswd->bhsw", q, kg) * scale
        logits = torch.where(mask[None, None, :, :], logits, -1e9)
        attn = _softmax(logits, axis=-1)
        o = torch.einsum("bhsw,bhswd->bhsd", attn, vg)
        return (lambda x, *d: x.permute(*d))(o, 0, 2, 1, 3).reshape(B, S, D) @ wo

    x = A_u
    x = x + _A_ref(_layernorm(x, axis=-1), A_A_re, A_A_im, A_B_re, A_B_im, A_C_re, A_C_im, A_log_dt, A_Dskip)
    x = x + _B_ref(_layernorm(x, axis=-1), B_wqkv, B_wo)
    x = x + _A_ref(_layernorm(x, axis=-1), A_A_re, A_A_im, A_B_re, A_B_im, A_C_re, A_C_im, A_log_dt, A_Dskip)
    x = x + _B_ref(_layernorm(x, axis=-1), B_wqkv, B_wo)
    return x
```

```cpp
#include <cuda_runtime.h>
#include <cuda_bf16.h>
#include <cuda.h>
#include <stdint.h>

#define DEV __device__ __forceinline__

#define NCOPY 4
#define NSUB 1
#define EA 0x2121
constexpr int NTHR = 512;
constexpr int SPIN_LIMIT = 1 << 22;

constexpr uint32_t SB = 1024;
constexpr uint32_t SM_XA   = SB;
constexpr uint32_t SM_S0   = SM_XA + 16384;
constexpr uint32_t SM_S1   = SM_S0 + 49152;
constexpr uint32_t SM_XB   = SM_S1 + 49152;
constexpr uint32_t SM_R    = SM_XB + 16384;
constexpr uint32_t SM_RES  = SM_R + 65536;
constexpr uint32_t SM_TAP  = SM_RES + 16384;
constexpr int TAP_SZ = 3584;
constexpr uint32_t SM_CS   = SM_TAP + 4 * TAP_SZ;
constexpr uint32_t SM_STAT = SM_CS + 768;
constexpr uint32_t SM_MISC = SM_STAT + 1280;
constexpr uint32_t SM_BAR  = SM_MISC + 512;
constexpr int SM_TOTAL = SM_BAR + 448 - SB;
constexpr int R_U = 512, R_A5 = 5120, R_A3 = 8704, R_B = 11776;
constexpr int T_E = 1536, T_O = T_E + 1602, T_C = 3714;
constexpr uint32_t B_W = SM_BAR, B_X = SM_BAR + 64, B_O = SM_BAR + 128, B_WO = SM_BAR + 256, B_RES = SM_BAR + 264;
constexpr uint32_t B_ST = SM_BAR + 272, B_R = SM_BAR + 288, B_E = SM_BAR + 304;
constexpr uint32_t B_F = SM_BAR + 320, B_G = SM_BAR + 352, B_K = SM_BAR + 376, B_ED = SM_BAR + 384, B_CS = SM_BAR + 400, B_H = SM_BAR + 416;
constexpr uint32_t CNT = 0x183444CC;
constexpr int NB_WG = 1, NB_T = 5, NB_Q = 10, NB_H = 11, NB_P = 14, NB_RL = 15;

struct Scratch {
  uint4    XG[2][512 * 256];
  uint4    XF[32 * 4096];
  uint4    O[32 * 8 * 512];
  uint32_t F[32 * 32];
  uint4    H[17 * 8 * 256];
  uint4    SR[2][8][512];
  uint4    ST[32 * 16];
  uint4    PS[128 * 64];
  float4   CS[16 * 1536 / 4];
  uint32_t C[10 * 32 * 32];
};
__device__ __align__(1024) Scratch g_S;

struct Params {
  int by_sm;
  uint32_t zero;
  Scratch* S;
  const uint16_t *x0, *Are, *Aim, *Bre, *Bim, *Cre, *Cim, *logdt, *dskip, *wqkv, *wo;
  uint16_t* out;
  uint8_t role[144];
};
#define EVENT(n) do {} while (0)
#define PROFD(slot, name, v) do {} while (0)
#define PROF(slot, name) do {} while (0)
#define PW(x)

DEV uint32_t s2u(const void* p) { return (uint32_t)__cvta_generic_to_shared(p); }
template <class T> DEV T opq(T x) { asm volatile("" : "+r"(x)); return x; }
DEV uint32_t pack2(float lo, float hi) { uint32_t d; asm("cvt.rn.bf16x2.f32 %0,%1,%2;" : "=r"(d) : "f"(hi), "f"(lo)); return d; }
DEV float bflo(uint32_t v) { return __uint_as_float(v << 16); }
DEV float bfhi(uint32_t v) { return __uint_as_float(v & 0xFFFF0000u); }
DEV float bfr(float x) { return bflo(pack2(x, 0.f)); }
DEV uint32_t hadd2(uint32_t a, uint32_t b) { uint32_t d; asm("add.rn.bf16x2 %0,%1,%2;" : "=r"(d) : "r"(a), "r"(b)); return d; }
DEV uint32_t hsub2(uint32_t a, uint32_t b) { uint32_t d; asm("sub.rn.bf16x2 %0,%1,%2;" : "=r"(d) : "r"(a), "r"(b)); return d; }
DEV uint32_t hmul2(uint32_t a, uint32_t b) { uint32_t d; asm("mul.rn.bf16x2 %0,%1,%2;" : "=r"(d) : "r"(a), "r"(b)); return d; }
DEV uint32_t hfma2(uint32_t a, uint32_t b, uint32_t c) { uint32_t d; asm("fma.rn.bf16x2 %0,%1,%2,%3;" : "=r"(d) : "r"(a), "r"(b), "r"(c)); return d; }
DEV uint32_t hmax2(uint32_t a, uint32_t b) { uint32_t d; asm("max.bf16x2 %0,%1,%2;" : "=r"(d) : "r"(a), "r"(b)); return d; }
DEV uint32_t prmt(uint32_t a, uint32_t b, uint32_t s) { uint32_t d; asm("prmt.b32 %0,%1,%2,%3;" : "=r"(d) : "r"(a), "r"(b), "r"(s)); return d; }
DEV uint32_t nz(uint32_t v) { return max(v, 1u); }
DEV uint32_t tagged(uint32_t v, uint32_t m, uint32_t tag) { return (v & ~m) | (tag & m); }
DEV uint4 hadd8(const uint4& a, const uint4& b) { return make_uint4(hadd2(a.x, b.x), hadd2(a.y, b.y), hadd2(a.z, b.z), hadd2(a.w, b.w)); }
DEV uint32_t min4(const uint4& v) { return min(min(v.x, v.y), min(v.z, v.w)); }
DEV float rcp(float x) { float y; asm("rcp.approx.ftz.f32 %0,%1;" : "=f"(y) : "f"(x)); return y; }
DEV float sqrt_(float x) { float y; asm("sqrt.approx.ftz.f32 %0,%1;" : "=f"(y) : "f"(x)); return y; }
DEV float ex2(float x) { float y; asm("ex2.approx.ftz.f32 %0,%1;" : "=f"(y) : "f"(x)); return y; }

DEV uint4 ldr4(const void* p) { uint4 v; asm volatile("ld.relaxed.gpu.global.v4.u32 {%0,%1,%2,%3},[%4];" : "=r"(v.x), "=r"(v.y), "=r"(v.z), "=r"(v.w) : "l"(p) : "memory"); return v; }
DEV void ldr4_if(uint4& v, const void* p, bool c) {
  asm volatile("{.reg .pred q; setp.ne.u32 q,%5,0; @q ld.relaxed.gpu.global.v4.u32 {%0,%1,%2,%3},[%4];}"
    : "+r"(v.x), "+r"(v.y), "+r"(v.z), "+r"(v.w) : "l"(p), "r"((uint32_t)c) : "memory");
}
DEV uint2 ldr2(const void* p) { uint2 v; asm volatile("ld.relaxed.gpu.global.v2.u32 {%0,%1},[%2];" : "=r"(v.x), "=r"(v.y) : "l"(p) : "memory"); return v; }
DEV uint32_t ldr1(const void* p) { uint32_t v; asm volatile("ld.relaxed.gpu.global.u32 %0,[%1];" : "=r"(v) : "l"(p) : "memory"); return v; }
DEV void str4(void* p, uint32_t a, uint32_t b, uint32_t c, uint32_t d) { asm volatile("st.relaxed.gpu.global.v4.u32 [%0],{%1,%2,%3,%4};" :: "l"(p), "r"(a), "r"(b), "r"(c), "r"(d) : "memory"); }
DEV void str2(void* p, uint32_t a, uint32_t b) { asm volatile("st.relaxed.gpu.global.v2.u32 [%0],{%1,%2};" :: "l"(p), "r"(a), "r"(b) : "memory"); }
DEV void str1(void* p, uint32_t a) { asm volatile("st.relaxed.gpu.global.u32 [%0],%1;" :: "l"(p), "r"(a) : "memory"); }
DEV void stw4(void* p, uint32_t a, uint32_t b, uint32_t c, uint32_t d) { asm volatile("st.global.v4.u32 [%0],{%1,%2,%3,%4};" :: "l"(p), "r"(a), "r"(b), "r"(c), "r"(d) : "memory"); }
DEV uint4 ldnc4(const void* p) { uint4 v; asm volatile("ld.global.nc.v4.u32 {%0,%1,%2,%3},[%4];" : "=r"(v.x), "=r"(v.y), "=r"(v.z), "=r"(v.w) : "l"(p)); return v; }
DEV uint4 ldw4(const void* p) { uint4 v; asm volatile("ld.global.v4.u32 {%0,%1,%2,%3},[%4];" : "=r"(v.x), "=r"(v.y), "=r"(v.z), "=r"(v.w) : "l"(p) : "memory"); return v; }
DEV void cp16(uint32_t d, const void* p) { asm volatile("cp.async.cg.shared.global [%0],[%1],16;" :: "r"(d), "l"(p) : "memory"); }
DEV uint32_t ldnc16(const void* p) { uint32_t v; asm volatile("ld.global.u16 %0,[%1];" : "=r"(v) : "l"(p) : "memory"); return v; }

DEV uint32_t lds1v(uint32_t a) { uint32_t v; asm volatile("ld.volatile.shared.u32 %0,[%1];" : "=r"(v) : "r"(a) : "memory"); return v; }
DEV uint4 lds4v(uint32_t a) { uint4 v; asm volatile("ld.volatile.shared.v4.u32 {%0,%1,%2,%3},[%4];" : "=r"(v.x), "=r"(v.y), "=r"(v.z), "=r"(v.w) : "r"(a) : "memory"); return v; }
DEV uint32_t lds1(uint32_t a) { uint32_t v; asm volatile("ld.shared.u32 %0,[%1];" : "=r"(v) : "r"(a)); return v; }
DEV uint2 lds2(uint32_t a) { uint2 v; asm volatile("ld.shared.v2.u32 {%0,%1},[%2];" : "=r"(v.x), "=r"(v.y) : "r"(a)); return v; }
DEV uint4 lds4(uint32_t a) { uint4 v; asm volatile("ld.shared.v4.u32 {%0,%1,%2,%3},[%4];" : "=r"(v.x), "=r"(v.y), "=r"(v.z), "=r"(v.w) : "r"(a)); return v; }
DEV uint32_t lds16(uint32_t a) { uint32_t v; asm volatile("ld.shared.u16 %0,[%1];" : "=r"(v) : "r"(a)); return v; }
DEV float lds1f(uint32_t a) { float v; asm volatile("ld.shared.f32 %0,[%1];" : "=f"(v) : "r"(a)); return v; }
DEV float2 lds2f(uint32_t a) { float2 v; asm volatile("ld.shared.v2.f32 {%0,%1},[%2];" : "=f"(v.x), "=f"(v.y) : "r"(a)); return v; }
DEV float4 lds4f(uint32_t a) { float4 v; asm volatile("ld.shared.v4.f32 {%0,%1,%2,%3},[%4];" : "=f"(v.x), "=f"(v.y), "=f"(v.z), "=f"(v.w) : "r"(a)); return v; }
DEV void sts1(uint32_t a, uint32_t v) { asm volatile("st.shared.u32 [%0],%1;" :: "r"(a), "r"(v) : "memory"); }
DEV void sts16(uint32_t a, uint32_t v) { asm volatile("{.reg .b16 h; cvt.u16.u32 h,%1; st.shared.u16 [%0],h;}" :: "r"(a), "r"(v) : "memory"); }
DEV void sts2f(uint32_t a, float x, float y) { asm volatile("st.shared.v2.f32 [%0],{%1,%2};" :: "r"(a), "f"(x), "f"(y) : "memory"); }
DEV void sts4f(uint32_t a, float x, float y, float z, float w) { asm volatile("st.shared.v4.f32 [%0],{%1,%2,%3,%4};" :: "r"(a), "f"(x), "f"(y), "f"(z), "f"(w) : "memory"); }
DEV void sts4(uint32_t a, uint32_t x, uint32_t y, uint32_t z, uint32_t w) { asm volatile("st.shared.v4.u32 [%0],{%1,%2,%3,%4};" :: "r"(a), "r"(x), "r"(y), "r"(z), "r"(w) : "memory"); }
DEV void sts4z_if(uint32_t a, bool c) { asm volatile("{.reg .pred q; setp.ne.u32 q,%1,0; @q st.shared.v4.u32 [%0],{%2,%2,%2,%2};}" :: "r"(a), "r"((uint32_t)c), "r"(0) : "memory"); }

DEV void ldsm4t(uint32_t& r0, uint32_t& r1, uint32_t& r2, uint32_t& r3, uint32_t a) { asm volatile("ldmatrix.sync.aligned.m8n8.x4.trans.shared.b16 {%0,%1,%2,%3},[%4];" : "=r"(r0), "=r"(r1), "=r"(r2), "=r"(r3) : "r"(a) : "memory"); }
DEV void stsm4(uint32_t a, uint32_t r0, uint32_t r1, uint32_t r2, uint32_t r3) { asm volatile("stmatrix.sync.aligned.m8n8.x4.shared.b16 [%0],{%1,%2,%3,%4};" :: "r"(a), "r"(r0), "r"(r1), "r"(r2), "r"(r3) : "memory"); }
DEV void stsm2(uint32_t a, uint32_t r0, uint32_t r1) { asm volatile("stmatrix.sync.aligned.m8n8.x2.shared.b16 [%0],{%1,%2};" :: "r"(a), "r"(r0), "r"(r1) : "memory"); }
DEV void stsm4t(uint32_t a, uint32_t r0, uint32_t r1, uint32_t r2, uint32_t r3) { asm volatile("stmatrix.sync.aligned.m8n8.x4.trans.shared.b16 [%0],{%1,%2,%3,%4};" :: "r"(a), "r"(r0), "r"(r1), "r"(r2), "r"(r3) : "memory"); }
DEV uint32_t movm(uint32_t a) { uint32_t d; asm volatile("movmatrix.sync.aligned.m8n8.trans.b16 %0,%1;" : "=r"(d) : "r"(a)); return d; }
DEV void mma16(float (&d)[4], uint32_t a0, uint32_t a1, uint32_t a2, uint32_t a3, uint32_t b0, uint32_t b1) {
  asm volatile("mma.sync.aligned.m16n8k16.row.col.f32.bf16.bf16.f32 {%0,%1,%2,%3},{%4,%5,%6,%7},{%8,%9},{%0,%1,%2,%3};"
    : "+f"(d[0]), "+f"(d[1]), "+f"(d[2]), "+f"(d[3]) : "r"(a0), "r"(a1), "r"(a2), "r"(a3), "r"(b0), "r"(b1));
}
DEV void mma16z(float (&d)[4], uint32_t a0, uint32_t a1, uint32_t a2, uint32_t a3, uint32_t b0, uint32_t b1) {
  asm volatile("mma.sync.aligned.m16n8k16.row.col.f32.bf16.bf16.f32 {%0,%1,%2,%3},{%4,%5,%6,%7},{%8,%9},{%10,%10,%10,%10};"
    : "=f"(d[0]), "=f"(d[1]), "=f"(d[2]), "=f"(d[3]) : "r"(a0), "r"(a1), "r"(a2), "r"(a3), "r"(b0), "r"(b1), "f"(0.f));
}
DEV void mma8z(float (&d)[4], uint32_t a0, uint32_t a1, uint32_t b0) {
  asm volatile("mma.sync.aligned.m16n8k8.row.col.f32.bf16.bf16.f32 {%0,%1,%2,%3},{%4,%5},{%6},{%7,%7,%7,%7};"
    : "=f"(d[0]), "=f"(d[1]), "=f"(d[2]), "=f"(d[3]) : "r"(a0), "r"(a1), "r"(b0), "f"(0.f));
}
DEV void mma8(float (&d)[4], uint32_t a0, uint32_t a1, uint32_t b0) {
  asm volatile("mma.sync.aligned.m16n8k8.row.col.f32.bf16.bf16.f32 {%0,%1,%2,%3},{%4,%5},{%6},{%0,%1,%2,%3};"
    : "+f"(d[0]), "+f"(d[1]), "+f"(d[2]), "+f"(d[3]) : "r"(a0), "r"(a1), "r"(b0));
}

DEV void bar_sync(int id, int n) { asm volatile("bar.sync %0,%1;" :: "r"(id), "r"(n) : "memory"); }
DEV void bar_arrive(int id, int n) { asm volatile("bar.arrive %0,%1;" :: "r"(id), "r"(n) : "memory"); }
DEV void bar_sync_if(int id, int n, int c) { asm volatile("{.reg .pred q; setp.ne.s32 q,%2,0; @q bar.sync %0,%1;}" :: "r"(id), "r"(n), "r"(c) : "memory"); }
DEV void bar_arrive_if(int id, int n, int c) { asm volatile("{.reg .pred q; setp.ne.s32 q,%2,0; @q bar.arrive %0,%1;}" :: "r"(id), "r"(n), "r"(c) : "memory"); }
DEV bool bar_any(int id, int n, bool c) {
  uint32_t r; asm volatile("{.reg .pred p,q; setp.ne.u32 q,%3,0; bar.red.or.pred p,%1,%2,q; selp.u32 %0,1,0,p;}" : "=r"(r) : "r"(id), "r"(n), "r"((uint32_t)c) : "memory");
  return __any_sync(0xffffffffu, r);
}
DEV void fence_async_glob() { asm volatile("fence.proxy.async.global;" ::: "memory"); }
DEV void fence_async_smem() { asm volatile("fence.proxy.async.shared::cta;" ::: "memory"); }
DEV void fence_gpu() { asm volatile("fence.acq_rel.gpu;" ::: "memory"); }
DEV void mbar_wait(uint32_t b, uint32_t ph) {
  asm volatile("{\n.reg .pred p;\nW: mbarrier.try_wait.parity.shared::cta.b64 p,[%0],%1;\n@!p bra W;\n}" :: "r"(b), "r"(ph) : "memory");
}
DEV bool mbar_test(uint32_t b, uint32_t ph) {
  uint32_t r; asm volatile("{.reg .pred p; mbarrier.test_wait.parity.shared::cta.b64 p,[%1],%2; selp.u32 %0,1,0,p;}" : "=r"(r) : "r"(b), "r"(ph) : "memory");
  return __all_sync(0xffffffffu, r);
}
DEV void spin_guard(int it) { asm volatile("{.reg .pred p; setp.gt.s32 p,%0,%1; @p trap;}" :: "r"(it), "n"(SPIN_LIMIT)); }
DEV uint32_t here(uint32_t zero) {
  uint32_t d; asm volatile("mov.u32 %0,%%clock;" : "=r"(d) :: "memory"); return d & zero;
}
DEV int lane_here(uint32_t zero) {
  uint32_t d; asm volatile("mov.u32 %0,%%laneid;" : "=r"(d)); return d | here(zero);
}
DEV void delay(uint32_t n) { const uint32_t t0 = clock(); while ((uint32_t)clock() - t0 < n); __syncwarp(); }
DEV void poll(const uint32_t* p, uint32_t n) {
  for (int it = 0; !__all_sync(0xffffffffu, ldr1(p) >= n); ++it) spin_guard(it);
}
DEV void cnt_add(const Params& P, int n, int c, int lane) { asm volatile("{.reg .pred p; setp.lt.s32 p,%1,%2; @p red.relaxed.gpu.global.add.u32 [%0],1;}" :: "l"(P.S->C + (32 * (NSUB * lane + c % NSUB) + n * 1024)), "r"(lane), "n"(NCOPY) : "memory"); }
DEV void cnt_wait(const Params& P, int n, int c, int lane) { poll(P.S->C + (32 * (NSUB * (c / (128 / NCOPY)) + lane % NSUB) + n * 1024), 128 / NSUB); }
DEV void mbar_init1(uint32_t b, int n) { asm volatile("{.reg .pred p; elect.sync _|p,0xffffffff; @p mbarrier.init.shared::cta.b64 [%0],%1;}" :: "r"(b), "r"(n) : "memory"); }
DEV void mbar_arrive1(uint32_t b) { asm volatile("{.reg .pred p; elect.sync _|p,0xffffffff; @p mbarrier.arrive.shared::cta.b64 _,[%0];}" :: "r"(b) : "memory"); }
DEV void mbar_arrive1_if(uint32_t b, int c) {
  asm volatile("{.reg .pred p,q; setp.ne.s32 q,%1,0; elect.sync _|p,0xffffffff; and.pred p,p,q; @p mbarrier.arrive.shared::cta.b64 _,[%0];}" :: "r"(b), "r"(c) : "memory");
}
DEV void mbar_expect1(uint32_t b, int bytes) { asm volatile("{.reg .pred p; elect.sync _|p,0xffffffff; @p mbarrier.arrive.expect_tx.shared::cta.b64 _,[%0],%1;}" :: "r"(b), "r"(bytes) : "memory"); }
DEV void flag_set1(uint32_t* q) { asm volatile("{.reg .pred p; elect.sync _|p,0xffffffff; @p st.relaxed.gpu.global.u32 [%0],1;}" :: "l"(q) : "memory"); }
DEV void tma3(uint32_t dst, const CUtensorMap* m, int c0, int c1, uint32_t bar) {
  asm volatile("{.reg .pred p; elect.sync _|p,0xffffffff;\n"
    "@p cp.async.bulk.tensor.3d.shared::cluster.global.mbarrier::complete_tx::bytes [%0],[%1,{%2,%3,%5}],[%4];}"
    :: "r"(dst), "l"(m), "r"(c0), "r"(c1), "r"(bar), "r"(0) : "memory");
}
DEV void tma5(uint32_t dst, const CUtensorMap* m, int c0, int c4, uint32_t bar) {
  asm volatile("{.reg .pred p; elect.sync _|p,0xffffffff;\n"
    "@p cp.async.bulk.tensor.5d.shared::cluster.global.mbarrier::complete_tx::bytes [%0],[%1,{%2,%5,%5,%5,%3}],[%4];}"
    :: "r"(dst), "l"(m), "r"(c0), "r"(c4), "r"(bar), "r"(0) : "memory");
}
DEV void bulk(uint32_t dst, const void* src, int bytes, uint32_t bar) {
  asm volatile("{.reg .pred p; elect.sync _|p,0xffffffff;\n@p cp.async.bulk.shared::cluster.global.mbarrier::complete_tx::bytes [%0],[%1],%2,[%3];}" :: "r"(dst), "l"(src), "r"(bytes), "r"(bar) : "memory");
}
DEV void bulk_store(void* dst, uint32_t src, int bytes) {
  asm volatile("{.reg .pred p; elect.sync _|p,0xffffffff;\n@p cp.async.bulk.global.shared::cta.bulk_group [%0],[%1],%2;}" :: "l"(dst), "r"(src), "r"(bytes) : "memory");
}
DEV void bulk_done() { asm volatile("cp.async.bulk.commit_group;\ncp.async.bulk.wait_group 0;" ::: "memory"); }
DEV void l2_prefetch(const void* src, int bytes) {
  asm volatile("{.reg .pred p; elect.sync _|p,0xffffffff;\n@p cp.async.bulk.prefetch.L2.global [%0],%1;}" :: "l"(src), "r"(bytes) : "memory");
}

DEV uint64_t mkdesc(uint32_t addr, uint32_t lbo, uint32_t sbo, uint32_t swz) {
  return (uint64_t)((addr >> 4) | ((lbo >> 4) << 16)) | ((uint64_t)((sbo >> 4) | (swz << 30)) << 32);
}
DEV void wg_fence() { asm volatile("wgmma.fence.sync.aligned;" ::: "memory"); }
DEV void wg_commit() { asm volatile("wgmma.commit_group.sync.aligned;" ::: "memory"); }
template <int N> DEV void wg_wait() { asm volatile("wgmma.wait_group.sync.aligned %0;" :: "n"(N) : "memory"); }
template <int N> DEV void zerov(float (&d)[N]) {
#pragma unroll
  for (int i = 0; i < N; ++i) asm volatile("mov.b32 %0,0;" : "=f"(d[i]));
}
template <int N> DEV void undef(float (&d)[N]) {
#pragma unroll
  for (int i = 0; i < N; ++i) asm volatile("" : "=f"(d[i]));
}
#define R4(d, o) "+f"(d[o]), "+f"(d[o + 1]), "+f"(d[o + 2]), "+f"(d[o + 3])
#define R8(d, o) R4(d, o), R4(d, o + 4)
#define R16(d, o) R8(d, o), R8(d, o + 8)
#define R32(d, o) R16(d, o), R16(d, o + 16)
#define L0 "%0,%1,%2,%3,%4,%5,%6,%7,%8,%9,"
#define L10(a) "%" #a "0,%" #a "1,%" #a "2,%" #a "3,%" #a "4,%" #a "5,%" #a "6,%" #a "7,%" #a "8,%" #a "9,"
#define WG_HEAD(pr, n) "{.reg .pred p; setp.ne.s32 p,%" #pr ",0;\nwgmma.mma_async.sync.aligned.m64n" #n "k16.f32.bf16.bf16 {"
DEV void wg_rs64k(float (&d)[32], const uint32_t (&a)[4], uint64_t db, int acc) {
  asm volatile(WG_HEAD(37, 64) L0 L10(1) L10(2) "%30,%31},{%32,%33,%34,%35},%36,p,1,1,0;}"
    : R32(d, 0) : "r"(a[0]), "r"(a[1]), "r"(a[2]), "r"(a[3]), "l"(db), "r"(acc));
}
DEV void wg_rs48t(float (&d)[24], const uint32_t (&a)[4], uint64_t db, int acc) {
  asm volatile(WG_HEAD(29, 48) L0 L10(1) "%20,%21,%22,%23},{%24,%25,%26,%27},%28,p,1,1,1;}"
    : R16(d, 0), R8(d, 16) : "r"(a[0]), "r"(a[1]), "r"(a[2]), "r"(a[3]), "l"(db), "r"(acc));
}
DEV void wg_rs32t(float (&d)[16], const uint32_t (&a)[4], uint64_t db, int acc) {
  asm volatile(WG_HEAD(21, 32) L0 "%10,%11,%12,%13,%14,%15},{%16,%17,%18,%19},%20,p,1,1,1;}"
    : R16(d, 0) : "r"(a[0]), "r"(a[1]), "r"(a[2]), "r"(a[3]), "l"(db), "r"(acc));
}
DEV void wg_ss48(float (&d)[24], uint64_t da, uint64_t db, int acc) {
  asm volatile(WG_HEAD(26, 48) L0 L10(1) "%20,%21,%22,%23},%24,%25,p,1,1,1,1;}" : R16(d, 0), R8(d, 16) : "l"(da), "l"(db), "r"(acc));
}
DEV void wg_ss64(float (&d)[32], uint64_t da, uint64_t db, int acc) {
  asm volatile(WG_HEAD(34, 64) L0 L10(1) L10(2) "%30,%31},%32,%33,p,1,1,0,1;}" : R32(d, 0) : "l"(da), "l"(db), "r"(acc));
}
DEV void wg_ss192(float (&d)[96], uint64_t da, uint64_t db, int acc) {
  asm volatile(WG_HEAD(98, 192) L0 L10(1) L10(2) L10(3) L10(4) L10(5) L10(6) L10(7) L10(8) "%90,%91,%92,%93,%94,%95},%96,%97,p,1,1,1,1;}"
    : R32(d, 0), R32(d, 32), R32(d, 64) : "l"(da), "l"(db), "r"(acc));
}

DEV void wg_rs192t(float (&d)[96], const uint32_t (&a)[4], uint64_t db) {
  asm volatile("wgmma.mma_async.sync.aligned.m64n192k16.f32.bf16.bf16 {" L0 L10(1) L10(2) L10(3) L10(4) L10(5) L10(6) L10(7) L10(8) "%90,%91,%92,%93,%94,%95},{%96,%97,%98,%99},%100,1,1,1,1;"
    : R32(d, 0), R32(d, 32), R32(d, 64) : "r"(a[0]), "r"(a[1]), "r"(a[2]), "r"(a[3]), "l"(db));
}

DEV float ln_sd(float s, float q, float& m) {
  m = s * (1.f / 512.f);
  return bfr(sqrt_(bfr(bfr(fmaxf(q * (1.f / 512.f) - m * m, 0.f)) + 1e-5f)));
}
template <int N> DEV float4 gram(const uint32_t (&w)[N][2], int g) {
  float s0[4], s1[4];
  const uint32_t one = 0x3F803F80u;
  mma16z(s0, w[0][0], one, w[1][0], one, w[0][0], w[1][0]); mma16z(s1, w[0][1], one, w[1][1], one, w[0][1], w[1][1]);
#pragma unroll
  for (int j = 2; j < N; j += 2) {
    mma16(s0, w[j][0], one, w[j + 1][0], one, w[j][0], w[j + 1][0]); mma16(s1, w[j][1], one, w[j + 1][1], one, w[j][1], w[j + 1][1]);
  }
  const bool od = g & 1;
  return make_float4(od ? s0[3] : s0[2], od ? s0[1] : s0[0], od ? s1[3] : s1[2], od ? s1[1] : s1[0]);
}
template <bool FRAG> DEV void xg_store(uint4* dst, const uint32_t (&w)[8][2], uint32_t stg, int nb, int wp, int lane) {
  const int t = lane & 3;
  const uint32_t a = stg + t * (FRAG ? 256 : 1024) + ((wp ^ t) * 32) + (lane >> 2) * 4;
#pragma unroll
  for (int n = 0; n < 8; ++n) {
    const uint32_t b = (a ^ ((n & 3) * 32)) + (FRAG ? n * 1024 : (n >> 2) * 4096 + (n & 3) * 256);
    sts1(b, prmt(w[n][0], w[n][1], 0x5410)); sts1(b + 128, prmt(w[n][0], w[n][1], 0x7632));
  }
  bar_sync(nb, 128);
  const int r = 4 * wp + (lane >> 3);
  const uint32_t b = stg + r * 128 + (((lane & 7) ^ (2 * (((r >> 1) ^ (r >> 3)) & 3))) * 16);
#pragma unroll
  for (int k = 0; k < 4; ++k) {
    const uint4 v = lds4((b ^ ((k & 1) * 64)) + k * 2048);
    str4(dst + (r * 256 + (lane & 7)) + k * 4096, nz(v.x), v.y, v.z, v.w);
  }
}
template <int N, int M> DEV void fold(float (&v)[M], int lane, int bit) {
  const bool b = lane & bit;
#pragma unroll
  for (int k = 0; k < N; ++k) { const float sn = b ? v[k] : v[k + N], kp = b ? v[k + N] : v[k]; v[k] = kp + __shfl_xor_sync(0xffffffffu, sn, bit); }
}
DEV void refetch(uint32_t dst, const uint4* src, int half, int e, int w) {
#pragma unroll 1
  for (int r = 0; r < 2; ++r) {
    if (w == 0) { mbar_expect1(B_R + 8 * e, half); bulk(dst + r * half, src + r * (half >> 4), half, B_R + 8 * e); }
    mbar_wait(B_R + 8 * e, r);
    bar_sync(NB_WG + e, 128);
  }
}
DEV uint32_t kvslot(int cg, int n) { return SM_XA + (cg < 4 ? 5 : 2) * 8192 + n * 2048; }
DEV uint32_t xstage(int q, int e) { return ((q + 1) & 2) ? SM_R + ((q & 2) + e) * 16384 : e ? SM_XB : SM_XA; }
DEV void cmul(float& orr, float& oi, float ar, float ai, float br, float bi) {
  float r = ar * br - ai * bi, i = ar * bi + ai * br; orr = r; oi = i;
}
DEV void cexp_(float al, float bt, float s, float& er, float& ei) {
  float mag = ex2(al * s), ph = bt * s;
  ph -= rintf(ph);
  float ang = ph * 6.283185307179586f;
  er = mag * __cosf(ang); ei = mag * __sinf(ang);
}

#define KS 2048
#define LATEF 0
DEV void put8(uint32_t a, const float (&r)[8], const float (&i)[8]) {
  sts4(a, pack2(r[0], r[1]), pack2(r[2], r[3]), pack2(r[4], r[5]), pack2(r[6], r[7]));
  sts4(a + 1024, pack2(i[0], i[1]), pack2(i[2], i[3]), pack2(i[4], i[5]), pack2(i[6], i[7]));
}
DEV void tables(const uint32_t (&pv)[8], int k4, int w, int lane) {
  PW(4 * k4 + w)
  [[maybe_unused]] const int layer = 0;
  const float dt = bfr(__expf(bflo(pv[6])));
  const float al = dt * bflo(pv[0]) * 1.4426950408889634f, bt = dt * bflo(pv[1]) * 0.15915494309189535f;
  float qr[8], qi[8], yr[8], yi[8];
  cmul(qr[0], qi[0], bflo(pv[4]), bflo(pv[5]), dt * bflo(pv[2]), dt * bflo(pv[3]));
  PROFD(2, a_par, __float_as_uint(qr[0] + al + bt));
  float e1r, e1i, eMr, eMi, eLr, eLi;
  cexp_(al, bt, 1.f, e1r, e1i); cexp_(al, -bt, 8.f, yr[1], yi[1]); cexp_(al, -bt, 64.f, eMr, eMi); cexp_(al, bt, 256.f, eLr, eLi);
  const uint32_t ad = SB + k4 * 32768 + (w & 1) * 512 + lane * 16, am = ad + (w >> 1) * KS, an = ad + (8 + 3 * (w >> 1)) * KS;
  yr[0] = 1.f; yi[0] = 0.f;
#pragma unroll
  for (int k = 1; k < 8; ++k) {
    cmul(qr[k], qi[k], qr[k - 1], qi[k - 1], e1r, e1i);
    if (k > 1) cmul(yr[k], yi[k], yr[k - 1], yi[k - 1], yr[1], yi[1]);
  }
  put8(an, qr, qi);
#pragma unroll
  for (int j = 0; j < 4; ++j) {
    put8(am + j * 2 * KS, yr, yi);
#pragma unroll
    for (int k = 0; k < 8; ++k) {
      if (j == 0 && k == 0) { yr[0] = eMr; yi[0] = eMi; } else if (j < 3) cmul(yr[k], yi[k], yr[k], yi[k], eMr, eMi);
    }
    if (j == 0) {
#pragma unroll
      for (int k = 0; k < 8; ++k) { const int o = k < 4 ? 2 * k : k < 6 ? 2 * k - 8 : k - 2; cmul(qr[k], qi[k], qr[o], qi[o], eLr, eLi); }
      put8(an + KS, qr, qi);
    } else if (j == 1) {
#pragma unroll
      for (int k = 0; k < 5; ++k) cmul(qr[k], qi[k], qr[k ? k - 1 : 6], qi[k ? k - 1 : 6], eLr, eLi);
      put8(an + 2 * KS, qr, qi);
    }
  }
  PROF(3, a_tab);
}

DEV void sts16_if(uint32_t a, uint32_t v, bool c) { asm volatile("{.reg .pred q; .reg .b16 h; setp.ne.u32 q,%2,0; cvt.u16.u32 h,%1; @q st.shared.u16 [%0],h;}" :: "r"(a), "r"(v), "r"((uint32_t)c) : "memory"); }
DEV void sts1_if(uint32_t a, uint32_t v, bool c) { asm volatile("{.reg .pred q; setp.ne.u32 q,%2,0; @q st.shared.u32 [%0],%1;}" :: "r"(a), "r"(v), "r"((uint32_t)c) : "memory"); }
DEV void taps(uint32_t dskip, int k4, int w, int lane) {
  PW(4 * k4 + w)
  [[maybe_unused]] const int layer = 0;
  fence_async_smem();
  bar_sync(k4 > LATEF ? NB_WG + k4 : NB_Q, k4 > LATEF ? 128 : 448 + 64 * LATEF);
  float d[24];
  undef(d);
  const uint64_t da = mkdesc(SB + k4 * 32768, 1024, KS, 0);
  wg_fence();
#pragma unroll
  for (int j = 0; j < 8; ++j) wg_ss48(d, da + j * 8, da + KS / 2 + j * 8, j);
  wg_commit();
  const int b = 8 * w + (lane >> 2), t = lane & 3, id = 32 * w + lane;
  constexpr int DO = T_O - T_E;
  const uint32_t te = SM_TAP + k4 * TAP_SZ + T_E, a0 = te - 16 * b - 4 * t;
  const uint32_t a1 = a0 - 512 - 4 * t, a2 = te - 2 * (511 + b) - 64 * t, a3 = te + (T_C - T_E) - 2 * (127 + b) - 128 * t;
  wg_wait<0>();
  PROF(4, a_mma);
  {
    const uint32_t v = pack2(d[1] + d[15], d[0] + d[14] + (id ? 0.f : bflo(dskip)));
    sts1(a0 + DO - 2, v); sts16(a0 - 2, v); sts16(a0, v >> 16);
  }
  {
    const uint32_t v = pack2(d[5] + d[19], d[4] + d[18]), u = prmt(v, v, 0x3232);
    const bool lo = t < 2, k512 = id == 2;
    sts1_if(k512 ? te - 2 * 512 : a1, u, (lo && id) || k512);
    sts1_if(k512 ? te - 2 * 514 : a1 - 4, k512 ? u : v, lo || k512);
    sts1_if(k512 ? te + DO - 2 * 513 : a1 + DO - 2, u, lo || k512);
    sts16(lo ? a1 + DO - 4 : a2 + DO - 194, v);
    sts16(lo ? (id ? a1 + DO + 2 : a1) : k512 ? te + DO - 2 * 511 : a2 + DO, u);
    sts16_if(a2 - 194, v, !lo);
    sts16_if(k512 ? te + DO - 2 * 514 : a2, u, !lo);
  }
  {
    const uint32_t v = pack2(d[8] + d[22], d[9] + d[23]);
    sts16_if(id ? a3 : te - 2 * 639, v, t < 2 || id == 2);
    sts16_if(a3 - 64, v >> 16, t < 2);
    sts16_if(te + DO - 2 * 639, v, id == 0);
  }
  bar_sync(NB_WG + k4, 128);
  mbar_arrive1_if(B_K, w == 0);
}

DEV uint32_t cpy(uint32_t v, uint32_t id) {
  uint32_t d; asm volatile("prmt.b32 %0,%1,%1,%2;" : "=r"(d) : "r"(v), "r"(id)); return d;
}
DEV uint32_t uoff(int s) { return (s ^ ((s >> 3) & 3)) * 16; }
template <bool FULL> DEV void boxes(const uint32_t (&u)[10], uint32_t a, uint32_t a9, uint32_t a7, uint32_t (&pv)[4]) {
  uint32_t v[8], p[8], x[4], y[4];
#pragma unroll
  for (int j = 0; j < 8; ++j) { v[j] = prmt(u[j], u[j + 1], 0x5432); p[j] = hadd2(u[j], v[j]); }
#pragma unroll
  for (int j = 0; j < 4; ++j) { x[j] = hadd2(hadd2(p[j + 1], p[j + 2]), u[j + 3]); y[j] = hadd2(v[j + 3], p[j + 4]); }
  sts4(a + R_A5, x[0], x[1], x[2], x[3]);
  sts4(a + R_A3, y[0], y[1], y[2], y[3]);
  if (FULL) {
#pragma unroll
    for (int j = 0; j < 4; ++j) { x[j] = hadd2(x[j], hadd2(v[j], v[j + 3])); y[j] = hadd2(x[j], hadd2(u[j], u[j + 4])); pv[j] = p[j + 4]; }
    sts4(a7, x[0], x[1], x[2], x[3]);
    sts4(a9, y[0], y[1], y[2], y[3]);
  }
}
DEV void halo(uint32_t (&u)[10], uint32_t a, int lane) {
  asm volatile("{.reg .pred p,q; setp.eq.s32 p,%8,0; setp.lt.s32 q,%8,2;\n@p ld.shared.v4.u32 {%2,%3,%4,%5},[%6];\n@q ld.shared.v2.u32 {%0,%1},[%7];}"
    : "+r"(u[0]), "+r"(u[1]), "+r"(u[2]), "+r"(u[3]), "+r"(u[4]), "+r"(u[5]) : "r"(a), "r"(a + 24 - 16 * lane), "r"(lane));
}
DEV void quad_ld(uint32_t (&q)[4], uint32_t a) { q[0] = lds1(a); q[2] = lds1(a + 16); q[1] = lds1(a - 128); q[3] = lds1(a - 112); }
DEV void half_ld(uint32_t (&q)[4][4], uint32_t a, uint32_t zero) {
  zero = here(zero);
#pragma unroll
  for (int kk = 0; kk < 2; ++kk) {
    q[2 + kk][0] = lds1(a + 32 * kk); q[2 + kk][2] = lds1(a + 32 * kk + 16);
    q[2 + kk][1] = cpy(zero, 2 * kk); q[2 + kk][3] = cpy(zero, 2 * kk + 1);
  }
}

#define ROT 2
#define G1 -1
#define G2 0
#define G3 1
#define TPS 0x6236
#define GMASK ((G1 >= 0 ? 2 : 0) | (G2 >= 0 ? 4 : 0) | (G3 >= 0 ? 8 : 0))
#define GATE1(g, n, p) if (g >= 0 && (g & 3) == p) mbar_arrive1_if(B_G + 8 * n, k4 == (g >> 2));
#define GATE(p) GATE1(G1, 0, p) GATE1(G2, 1, p) GATE1(G3, 2, p)
#define TMASK(p) (((TPS & 15) == p) | ((((TPS >> 4) & 15) == p) << 1) | ((((TPS >> 8) & 15) == p) << 2) | ((((TPS >> 12) & 15) == p) << 3))
#define TURN(p) if (TMASK(p) == 15) bar_arrive(NB_T + 1 + k4, 256); else if (TMASK(p)) { if ((TMASK(p) >> k4) & 1) bar_arrive(NB_T + 1 + k4, 256); }
DEV void w_load(const CUtensorMap* mW, int cg, int h) {
  mbar_expect1(B_W + 8 * h, 24576);
  tma3(SM_S0 + (h & 3) * 24576, mW, 64 * cg, 64 * h, B_W + 8 * h);
}

DEV void conv(const Params& P, const CUtensorMap* mW, int c, int k4, int w, int layer) {
  const uint32_t zero = P.zero;
  PW(4 * k4 + w)
  int lane = lane_here(zero);
  const int g = lane >> 2, t = lane & 3, v = w ^ (ROT * (k4 & 1)), tid = 32 * v + lane;
  const uint32_t reg = SM_R + k4 * 16384, tp = SM_TAP + k4 * TAP_SZ;
  const uint32_t g0 = tp + ((g & 1) ? T_O : T_E) + 2 * (2 * t - g);
  uint32_t F[18][4], U[12];
  {
    const uint32_t ga = g0 - 32 * (w & 1) - 576 * (w >> 1);
    F[0][2] = lds1(ga + 48);
#pragma unroll
    for (int j = 0; j < 12; ++j) { F[j][0] = lds1(ga + 32 - 32 * j); F[j][1] = lds1(ga + 16 - 32 * j); }
#pragma unroll
    for (int j = 0; j < 12; ++j) U[j] = lds1(ga - 352 - 16 * j);
  }
  PROF(5, a_pre);
  if (k4 == 3 && w == 3) {
    mbar_wait(B_E, layer);
    mbar_wait(B_K, 0);
#pragma unroll
    for (int h = 0; h < 4; ++h) w_load(mW, c & 7, h);
  }
  mbar_wait(k4 && ((GMASK >> k4) & 1) ? B_G - 8 + 8 * k4 : B_E, layer);
  PROF(6, a_x);
  const uint32_t ua = reg + R_U + uoff(tid);
  uint4 x[2];
  uint32_t pv[4];
  {
    uint4 s[4];
#pragma unroll
    for (int z = 0; z < 2; ++z) x[z] = lds4(reg + R_B + tid * 16 + z * 2048);
#pragma unroll
    for (int z = 0; z < 4; ++z) s[z] = lds4(SM_RES + tid * 16 + (z >> 1) * 2048 + (z & 1) * 4096);
    sts4z_if(reg + lane * 16 + (w ? w * 3584 + 1024 : 0), w < 3);
    for (int it = 0;; ++it) {
      uint32_t m = min(x[0].x, x[1].x);
#pragma unroll
      for (int z = 0; z < 4; ++z) m = min(m, min(s[z].x, s[z].z));
      if (m) break;
#pragma unroll
      for (int z = 0; z < 2; ++z) x[z] = ldr4(&P.S->XG[layer][(128 * k4 + c) * 256 + opq(tid) + z * 128]);
#pragma unroll
      for (int z = 0; z < 4; ++z) s[z] = ldr4(&P.S->SR[layer][c >> 4][opq(tid) + (z >> 1) * 128 + (z & 1) * 256]);
#pragma unroll
      for (int z = 0; z < 4; ++z) sts4(SM_RES + tid * 16 + (z >> 1) * 2048 + (z & 1) * 4096, s[z].x, s[z].y, s[z].z, s[z].w);
      spin_guard(it);
    }
    __syncwarp();
    uint32_t u[2][10];
#pragma unroll
    for (int z = 0; z < 2; ++z) {
      u[z][6] = hmul2(hsub2(x[z].x, s[2 * z].y), s[2 * z].x); u[z][7] = hmul2(hsub2(x[z].y, s[2 * z].w), s[2 * z].z);
      u[z][8] = hmul2(hsub2(x[z].z, s[2 * z + 1].y), s[2 * z + 1].x); u[z][9] = hmul2(hsub2(x[z].w, s[2 * z + 1].w), s[2 * z + 1].z);
      sts4(ua + z * 2048, u[z][6], u[z][7], u[z][8], u[z][9]);
    }
#pragma unroll
    for (int j = 0; j < 6; ++j) u[0][j] = __shfl_up_sync(0xffffffffu, u[0][j < 2 ? 8 + j : 4 + j], j < 2 ? 2 : 1);
    bar_sync(NB_WG + k4, 128);
    GATE(0)
    PROF(7, a_u);
    const uint32_t h1 = reg + R_U + v * 512 - 64;
    halo(u[0], h1, lane);
    if (v < 2) {
      u[1][0] = 0;
#pragma unroll
      for (int j = 1; j < 6; ++j) u[1][j] = __shfl_up_sync(0xffffffffu, u[1][j < 2 ? 8 + j : 4 + j], j < 2 ? 2 : 1);
      halo(u[1], h1 + 2048, lane);
      boxes<false>(u[1], reg + tid * 16 + 2048, 0, 0, pv);
    }
    const uint32_t bo = reg + R_B + tid * 16 + (v >> 1) * 1056;
    const uint32_t be = tid == 127 ? reg + R_B + 1024 : bo + (tid == 63 ? 2112 : 1056);
    boxes<true>(u[0], reg + tid * 16, (lane & 1) ? be : bo, (lane & 1) ? bo : be, pv);
    sts4z_if(reg + R_B + 1040, tid == 0);
  }
  GATE(1)
  fence_async_smem();
  if (k4 == 3) {
    if (w < 2) {
      const uint32_t src = SM_RES + 8192 + w * 2048;
#pragma unroll
      for (int z = 0; z < 4; ++z) sts4(src + lane * 16 + z * 512, ~0u, ~0u, ~0u, ~0u);
      fence_async_smem();
      __syncwarp();
#pragma unroll
      for (int z = 0; z < 4; ++z) bulk_store(&P.S->O[((c >> 3) * 16 + w * 8 + (c & 7)) * 512] + z * 128, src, 2048);
      bulk_done();
    } else if (w == 2) {
#pragma unroll
      for (int z = 0; z < 8; ++z) str4(&P.S->H[(c + 8) * 256 + lane] + z * 32, 0, 0, 0, 0);
      str4(&P.S->PS[c * 64 + lane], 0, 0, 0, 0); str4(&P.S->PS[c * 64 + lane] + 32, 0, 0, 0, 0);
      if (lane < 16) str1((uint32_t*)P.S->ST + (16 * c + lane), 0);
      else if (lane < 18) str1(P.S->F + ((c >> 3) * 64 + (lane & 1) * 32 + (c & 7)), 0);
      else if (lane >= 27 && c < NCOPY * NSUB) str1(P.S->C + (32 * c + (lane - 22 - 5 * layer) * 1024), 0);
      __syncwarp();
      fence_gpu();
    }
  }
  const uint32_t id = opq(0x3210u);
#pragma unroll
  for (int j = 0; j < 12; ++j) { F[j][3] = cpy(F[j][0], id); if (j) F[j][2] = cpy(F[j - 1][1], id); }
  PROF(8, a_box);
  bar_sync(NB_T + k4, k4 ? 256 : 128);
  PROF(9, a_turn);
  float acc[32], f1[24], f3[16];
  uint32_t qa[4][4], qb[4][4], qc[4][4], yp[16];
  const uint64_t db = mkdesc(reg + R_U, 16, 512, 2) + 2;
#define STEP(mm, n) wg_fence(); mm; wg_commit(); wg_wait<n>();
#define D(j, n) STEP(wg_rs64k(acc, F[j], db - 2 * j, j), n)
#define T(q, j, o, n) STEP(wg_rs48t(f1, q[j], d1 + o + 16 * (j & 1) - 32 * (j >> 1), o | j), n)
#define SPREAD(n) { const uint32_t id = 0x3210u | here(zero); _Pragma("unroll") for (int j = n; j < n + 2; ++j) { \
    F[12 + j][0] = cpy(U[2 * j], id); F[12 + j][1] = cpy(U[2 * j + 1], id); F[12 + j][3] = cpy(F[12 + j][0], id); F[12 + j][2] = cpy(F[11 + j][1], id); } }
  const uint32_t g1 = g0 - 2 * 576 - 16 * w;
  const uint64_t d1 = mkdesc(reg + R_A5, 128, 512, 0);
  undef(acc);
  D(0, 3) TURN(0) D(1, 3) D(2, 3) D(3, 3) D(4, 3) SPREAD(0) D(5, 3) D(6, 3) TURN(1) SPREAD(2) D(7, 3) quad_ld(qa[0], g1);
  D(8, 3) SPREAD(4) D(9, 3) quad_ld(qa[1], g1 + 32); D(10, 3) half_ld(qa, g1 - 64, zero);
  D(11, 3) quad_ld(qb[0], g1 - 192); D(12, 3) TURN(2) quad_ld(qb[1], g1 - 160); D(13, 3) half_ld(qb, g1 - 256, zero);
  D(14, 3) D(15, 3) D(16, 3) D(17, 2)
  TURN(3)
  PROF(10, a_den);
  lane = lane_here(zero);
  const uint32_t g2 = tp + T_C - 258 - 32 * w + 4 * (lane & 3) - (lane & 28);
  undef(f1);
  T(qa, 0, 0, 2) quad_ld(qc[0], g2); T(qa, 1, 0, 2) quad_ld(qc[1], g2 + 32); T(qa, 2, 0, 2) quad_ld(qc[2], g2 + 64); T(qa, 3, 0, 2)
  TURN(4)
  quad_ld(qc[3], g2 + 96);
  constexpr int O3 = (R_A3 - R_A5) / 16;
  uint32_t pin = zero;
#define PACK(n) _Pragma("unroll") for (int z = n; z < n + 4; ++z) { yp[z] = pack2(acc[2 * z], acc[2 * z + 1]); pin &= yp[z]; }
  T(qb, 0, O3, 3) PACK(0) PACK(4) T(qb, 1, O3, 3) PACK(8) T(qb, 2, O3, 3) PACK(12) T(qb, 3, O3, 3)
  TURN(5)
  qc[0][0] |= pin;
  undef(f3);
  wg_fence();
#pragma unroll
  for (int kk = 0; kk < 4; ++kk) wg_rs32t(f3, qc[kk], mkdesc(reg + R_B, 128, 1040, 0) + 16 * kk, kk);
  wg_commit();
  TURN(6)
  uint32_t k1024 = lds16(tp + T_E - 2 * 639);
  lane |= here(zero);
  const int p = (lane + 9 * (w >> 1)) & 31;
  const uint32_t ya = reg + ((w >> 1) ? R_B : R_U) + p * 64 + (((2 * (w & 1)) ^ ((p >> 1) & 3)) * 16);
  const uint32_t up = p < lane ? 2048 : 0;
  const uint32_t fa = reg + R_A5 + (lane >> 3) * 512 + w * 128 + (lane & 7) * 16;
  const uint32_t fc = reg + R_A3 + uoff(64 * (lane >> 4) + 16 * w + 2 * (lane & 7) + 1 - ((lane >> 3) & 1));
  wg_wait<0>();
  GATE(2)
  PROF(11, a_far);
  bar_sync(NB_WG + k4, 128);
#pragma unroll
  for (int z = 0; z < 4; ++z) {
    const uint32_t* a = yp + 8 * (z >> 1) + (z & 1);
    stsm4t((ya + (up ^ ((z >> 1) * 2048))) ^ ((z & 1) * 16), a[0], a[2], a[4], a[6]);
  }
  stsm4(fa, pack2(f1[0], f1[1]), pack2(f1[4], f1[5]), pack2(f1[8] + f1[2], f1[9] + f1[3]), pack2(f1[12] + f1[6], f1[13] + f1[7]));
  stsm2(fa + 2048, pack2(f1[16] + f1[10], f1[17] + f1[11]), pack2(f1[20] + f1[14], f1[21] + f1[15]));
  stsm4(fc, pack2(f3[0], f3[1]), pack2(f3[4], f3[5]), pack2(f3[8] + f3[2], f3[9] + f3[3]), pack2(f3[12] + f3[6], f3[13] + f3[7]));
  bar_sync(NB_WG + k4, 128);
  PROF(12, a_sts);
  {
    const int o = 32 * v + lane;
    const uint32_t a = reg + uoff(o), b = reg + R_A5 + o * 16;
    uint4 y[2];
    y[0] = hadd8(lds4(a + R_U), hadd8(lds4(o >= 36 ? a + R_B : reg), lds4(v >= 2 ? b - 1024 : reg)));
    uint4 h = lds4(a + R_A3);
    k1024 = prmt(k1024, k1024, 0x1010);
    h = make_uint4(hfma2(pv[0], k1024, h.x), hfma2(pv[1], k1024, h.y), hfma2(pv[2], k1024, h.z), hfma2(pv[3], k1024, h.w));
    y[1] = hadd8(lds4(a + R_U + 2048), hadd8(lds4(a + R_B + 2048), hadd8(lds4(b + 1024), h)));
    const int e0 = (o >> 3) * 8192 + (128 * k4 + c) * 16 + (((o & 4) + ((o >> 1) & 1)) ^ (c & 7)) * 2 + (o & 1);
    if (EA != 0x1111) cnt_add(P, 1 + 5 * layer + k4, c, (o ^ 96) | (y[0].x & y[1].x & zero) | (((EA >> (4 * k4)) & 1) << 8));
    const uint32_t me = (e0 & 3) == ((c >> 1) & 3), m0 = me & ~c, m1 = me & c, tag = 1 - layer;
#pragma unroll
    for (int z = 0; z < 2; ++z) {
      const uint4 r = hadd8(x[z], y[z]);
      str2((uint2*)P.S->XF + e0 + z * 131072, tagged(prmt(r.x, r.y, 0x5410), m0, tag), tagged(prmt(r.z, r.w, 0x5410), m1, tag));
      str2((uint2*)P.S->XF + (e0 ^ 4) + z * 131072, tagged(prmt(r.x, r.y, 0x7632), m0, tag), tagged(prmt(r.z, r.w, 0x7632), m1, tag));
    }
  }
  if (EA != 0x2222) cnt_add(P, 1 + 5 * layer + k4, c, 32 * (v ^ 3) + lane + (((EA >> (4 * k4)) & 2) << 8));
  GATE(3)
  PROF(13, a_out);
}

#define HPRI 0
#define XORD 1
DEV void x_load(const Params& P, int c, int q, int layer) {
#pragma unroll
  for (int z = 0; z < 2; ++z) {
    const int e = z ^ (XORD && q == 3 && !(c & 4));
    mbar_expect1(B_X + 16 * q + 8 * e, 16384);
    bulk(xstage(q, e), P.S->XF + ((2 * (c >> 3) + 1 - e) * 4096 + q * 1024), 16384, B_X + 16 * q + 8 * e);
  }
}

DEV void means(uint32_t (&m)[4], int row, int lane, int layer, uint32_t zero) {
  mbar_wait(B_CS, 0);
  mbar_wait(B_ST, layer);
  const uint32_t a = SM_MISC + row * 4 + (lane & 28), k = (lane & 3) ? 0u : ~0u;
  m[0] = lds1(a) & k; m[1] = lds1(a + 32) & k; m[2] = m[0] & zero; m[3] = m[1] & zero;
}

DEV void attn_phase(const Params& P, int c, int e, int w, int lane, int layer) {
  PW(4 * e + w)
  const int cg = c & 7, J = 2 * (c >> 3) + 1 - e;
  float acc[96];
  zerov(acc);
  uint32_t m[4] = {0, 0, 0, 0};
#pragma unroll 1
  for (int q = 0;; ++q) {
    const uint64_t da = mkdesc(xstage(q, e), 16, 1024, 1), db = mkdesc(SM_S0 + (q & 1) * 49152, 8192, 1024, 1);
    mbar_wait(B_X + 16 * q + 8 * e, layer);
    for (int it = 0;; ++it) {
      const uint32_t a = xstage(q, e) + w * 4096 + lane * 132;
      const uint32_t ok = (lds1(a) ^ layer) & (lds1(a ^ 32) ^ layer) & (lds1(a ^ 64) ^ layer) & (lds1(a ^ 96) ^ layer);
      if (!bar_any(NB_WG + e, 128, !(ok & 1))) break;
      EVENT(8 * layer + 2 * q + e);
      refetch(xstage(q, e), P.S->XF + (J * 4096 + q * 1024), 8192, e, w);
      spin_guard(it);
    }
    if (q == 0 && e && w == 0) {
      bar_sync(NB_H, 160);
      cnt_wait(P, 2 + 5 * layer, c, lane);
      x_load(P, c, 1, layer);
      PROF(27, m_xi);
    }
    if (q == 3 && e) means(m, 16 * w, lane, layer, P.zero);
    mbar_wait(B_W + 16 * q, layer);
    const bool all = mbar_test(B_W + 16 * q + 8, layer);
    bar_sync(e ? NB_Q : q ? NB_T : NB_T + 4, 256);
    PROF(14 + q, m_q);
    wg_fence();
#pragma unroll
    for (int k = 0; k < 8; ++k) {
      if (k == 4) { if (!all) mbar_wait(B_W + 16 * q + 8, layer); wg_fence(); }
      wg_ss192(acc, da + k * 128, db + (k >> 2) * 1536 + (k & 3) * 128, 1);
    }
    wg_commit();
    if (q == 3) break;
    bar_arrive(e ? NB_T : NB_Q, 256);
    wg_wait<0>();
    mbar_arrive1(B_F + 8 * q);
  }
  const uint32_t ra = SM_STAT + 256 + (32 - 32 * e + 8 * w) * 16;
  float r0, r1;
  {
    if (!e) means(m, 64 + 16 * w, lane, layer, P.zero);
    PROF(28, m_sub);
    wg_fence();
    wg_rs192t(acc, m, mkdesc(SM_CS, 0, 32, 0));
    wg_commit();
    bar_arrive_if(NB_Q, 256, !e);
    r1 = lds1f(ra + 64 + (lane >> 3) * 16 + (lane & 4)); r0 = lds1f(ra + (lane >> 3) * 16 + (lane & 4));
    mbar_wait(B_F + 16, layer);
    wg_wait<0>();
    mbar_arrive1(B_F + 24);
  }
  PROF(18, m_qkv);
  lane = opq(lane);
  const int g = lane >> 2, t = lane & 3;
  uint32_t Q[4][4], K[4][3][2], V[4][3][2];
  const int pos = 2 - 2 * e + (w >> 1);
  uint4 k0, k1, k2;
  {
    uint32_t pin = P.zero;
#pragma unroll
    for (int z = 0; z < 8; ++z) {
      K[z >> 1][2][z & 1] = pack2(acc[34 + 4 * z], acc[35 + 4 * z]);
      V[z >> 1][2][z & 1] = pack2(acc[66 + 4 * z], acc[67 + 4 * z]);
      K[z >> 1][1][z & 1] = pack2(acc[32 + 4 * z], acc[33 + 4 * z]);
      V[z >> 1][1][z & 1] = pack2(acc[64 + 4 * z], acc[65 + 4 * z]);
      pin &= K[z >> 1][1][z & 1] & V[z >> 1][1][z & 1];
    }
    if (pos == 3) {
      const uint32_t rk = pack2(r1, r1) | pin;
      uint4* h = P.S->H + ((c + 8) * 256 + (w & 1) * 128 + lane);
#pragma unroll
      for (int z = 0; z < 4; ++z) str4(h + z * 32, nz(hmul2(K[z][2][0], rk)), hmul2(K[z][2][1], rk), hmul2(V[z][2][0], rk), hmul2(V[z][2][1], rk));
      bar_arrive(NB_RL, 128 + 64 * HPRI);
    }
    if (HPRI) bar_sync_if(NB_RL, 192, pos == 2);
#pragma unroll
    for (int z = 0; z < 8; ++z) {
      V[z >> 1][2][z & 1] = movm(V[z >> 1][2][z & 1]);
    }
    const uint32_t kv = kvslot(cg, 2 * pos + (w & 1)) + lane * 16;
    if (pos < 3) {
#pragma unroll
      for (int z = 0; z < 4; ++z) sts4(kv + 4096 + z * 512, K[z][2][0], K[z][2][1], V[z][2][0], V[z][2][1]);
      bar_arrive(NB_H + pos + 1, 128);
    }
    k0 = lds4(ra - 192 + 16 * t); k1 = lds4(ra + 16 * t); k2 = lds4(ra + 64 + 16 * t);
    PROF(19, m_kv);
#pragma unroll
    for (int z = 0; z < 8; ++z) {
      V[z >> 1][1][z & 1] = movm(V[z >> 1][1][z & 1]);
      Q[z >> 1][2 * (z & 1)] = pack2(acc[4 * z], acc[4 * z + 1]);
      Q[z >> 1][2 * (z & 1) + 1] = pack2(acc[4 * z + 2], acc[4 * z + 3]);
    }
    mbar_wait(B_F + 24, layer);
    bar_sync(NB_H + pos, 128);
#pragma unroll
    for (int z = 0; z < 4; ++z) {
      const uint4 hv = lds4(kv + z * 512);
      K[z][0][0] = hv.x; K[z][0][1] = hv.y; V[z][0][0] = hv.z; V[z][0][1] = hv.w;
    }
  }
  mbar_arrive1(B_H);
  PROF(20, m_halo);
  const uint32_t ob = e ? SM_S1 : SM_XA;
  {
    const bool p0 = 2 * t > g, p1 = 2 * t + 1 > g, first = c < 8 && pos == 0;
    const uint32_t M = (p0 ? 0xFFFFu : 0u) | (p1 ? 0xFFFF0000u : 0u);
    const float sc0 = r0 * (0.25f * 1.4426950408889634f), sc1 = r1 * (0.25f * 1.4426950408889634f);
    const float sk[4] = {__uint_as_float(p0 ? k0.x : k1.x) * sc0, __uint_as_float(p1 ? k0.y : k1.y) * sc0,
                         __uint_as_float(p0 ? k1.x : k2.x) * sc1, __uint_as_float(p1 ? k1.y : k2.y) * sc1};
    const uint32_t rm[4] = {k0.z & M, k1.z & ~M, k1.z & M, k2.z & ~M}, s0 = k0.w | P.zero, s1 = k1.w | P.zero;
    const int oo = cg * 512 + (2 * (w & 2) + (w & 1)) * 64 + (lane ^ (g >> 1));
    uint4* O = P.S->O + (J * 4096 + oo);
#pragma unroll
    for (int h2 = 0; h2 < 2; ++h2) {
      uint32_t A[2], B[2], mx[2];
#pragma unroll
      for (int z = 0; z < 2; ++z) {
        const int h = 2 * h2 + z;
        float S[3][4];
#pragma unroll
        for (int n = 0; n < 3; ++n) mma16z(S[n], Q[h][0], Q[h][1], Q[h][2], Q[h][3], K[h][n][0], K[h][n][1]);
        if (first) { S[0][0] = __uint_as_float(0xFF800000u); S[0][1] = S[0][0]; }
        A[z] = pack2((p0 ? S[0][0] : S[1][0]) * sk[0], (p0 ? S[1][2] : S[2][2]) * sk[2]);
        B[z] = pack2((p1 ? S[0][1] : S[1][1]) * sk[1], (p1 ? S[1][3] : S[2][3]) * sk[3]);
      }
#pragma unroll
      for (int z = 0; z < 2; ++z) mx[z] = hmax2(A[z], B[z]);
#pragma unroll
      for (int z = 0; z < 2; ++z) mx[z] = hmax2(mx[z], __shfl_xor_sync(0xffffffffu, mx[z], 1));
#pragma unroll
      for (int z = 0; z < 2; ++z) mx[z] = hmax2(mx[z], __shfl_xor_sync(0xffffffffu, mx[z], 2));
      float Oa[2][3][4];
#pragma unroll
      for (int z = 0; z < 2; ++z) {
        const int h = 2 * h2 + z;
        const uint32_t a = hsub2(A[z], mx[z]), b = hsub2(B[z], mx[z]);
        const uint32_t w0 = pack2(ex2(bflo(a)), ex2(bflo(b))), w1 = pack2(ex2(bfhi(a)), ex2(bfhi(b)));
        const uint32_t u0 = hmul2(w0, rm[0]), u1 = hmul2(w0, rm[1]), u2 = hmul2(w1, rm[2]), u3 = hmul2(w1, rm[3]);
        const uint32_t z0 = w0 & P.zero, z1 = w1 & P.zero;
        mma16z(Oa[z][2], u0, z0, u1, u2, s0, s1);
#pragma unroll
        for (int d = 0; d < 2; ++d) mma16z(Oa[z][d], u0, z0, u1, u2, V[h][0][d], V[h][1][d]);
        mma8(Oa[z][2], z1, u3, k2.w);
#pragma unroll
        for (int d = 0; d < 2; ++d) mma8(Oa[z][d], z1, u3, V[h][2][d]);
      }
#pragma unroll
      for (int r = 0; r < 4; r += 2) {
        const float i0 = rcp(Oa[0][2][r]), i1 = rcp(Oa[1][2][r]);
        const uint32_t o0 = pack2(Oa[0][0][r] * i0, Oa[0][0][r + 1] * i0), o1 = pack2(Oa[0][1][r] * i0, Oa[0][1][r + 1] * i0);
        const uint32_t o2 = pack2(Oa[1][0][r] * i1, Oa[1][0][r + 1] * i1), o3 = pack2(Oa[1][1][r] * i1, Oa[1][1][r + 1] * i1);
        str4(O + h2 * 32 + r * 64, o0, o1, o2, o3);
        sts4(ob + oo * 16 + h2 * 512 + r * 1024, o0, o1, o2, o3);
      }
    }
  }
  bar_sync(NB_WG + e, 128);
  if (w == 0) flag_set1(P.S->F + (J * 32 + cg));
  fence_async_smem();
  PROF(21, m_att);
  uint32_t res[8][2];
  mbar_wait(B_RES, layer);
  {
    const uint32_t a = SM_RES + e * 8192 + (lane >> 4) * 1024 + (lane & 7) * 128 + (((2 * (w & 2) + ((lane >> 2) & 2) + (w & 1)) ^ (lane & 7)) * 16);
#pragma unroll
    for (int j = 0; j < 8; j += 2) ldsm4t(res[j][0], res[j][1], res[j + 1][0], res[j + 1][1], a + j * 1024);
  }
  PROF(26, m_res);
  float ac[32];
  bar_sync(NB_WG + e, 128);
#pragma unroll 1
  for (int it = 0;; ++it) {
    zerov(ac);
#pragma unroll 1
    for (int n = 0; n < 8; ++n) {
      const int s = n == 0 ? cg : n - (n <= cg);
      mbar_wait(n ? B_O + 64 * e + 8 * s : B_WO, layer);
      if (n == 1) PROF(22, m_o1);
      if (n == 7) PROF(23, m_o7);
      const uint64_t da = mkdesc(ob + s * 8192, 16, 1024, 2), db = mkdesc(SM_R + s * 8192, 16, 1024, 1);
      wg_fence();
#pragma unroll
      for (int k = 0; k < 4; ++k) wg_ss64(ac, da + (k >> 1) * 32 + (k & 1) * 2, db + k * 128, 1);
      wg_commit();
    }
    wg_wait<0>();
    if (!bar_any(NB_WG + e, 128, ac[0] != ac[0] || ac[2] != ac[2]) || it == 16) break;
    EVENT(24 + 2 * layer + e);
    refetch(ob, P.S->O + J * 4096, 32768, e, w);
  }
  PROF(24, m_wo);
#pragma unroll
  for (int j = 0; j < 8; ++j) {
    res[j][0] = hadd2(res[j][0], pack2(ac[4 * j], ac[4 * j + 1]));
    res[j][1] = hadd2(res[j][1], pack2(ac[4 * j + 2], ac[4 * j + 3]));
  }
  if (layer == 0) {
    const float4 s = gram(res, g);
    if (t == (g >> 1))
      str4(&P.S->PS[((4 * J + w) * 8 + cg) * 8 + g], nz(__float_as_uint(s.x)), __float_as_uint(s.y), __float_as_uint(s.z), __float_as_uint(s.w));
    __syncwarp();
    xg_store<true>(P.S->XG[1] + (64 * cg * 256 + 8 * J), res, ob, NB_WG + e, w, lane);
    __syncwarp();
    mbar_arrive1(B_ED + 8 * e);
  } else {
    const uint32_t stg = ob + w * 2048;
    const int row = (lane & 7) + 8 * ((lane >> 3) & 1);
#pragma unroll
    for (int j = 0; j < 8; j += 2)
      stsm4(stg + row * 128 + (((j + (lane >> 4)) ^ (row & 7)) * 16), res[j][0], res[j][1], res[j + 1][0], res[j + 1][1]);
    __syncwarp();
#pragma unroll
    for (int k = 0; k < 4; ++k) {
      const int r = 4 * k + (lane >> 3);
      const uint4 v = lds4(stg + r * 128 + (((lane & 7) ^ (r & 7)) * 16));
      stw4(P.out + ((64 * J + 16 * w + 2 * (lane >> 3)) * 512 + 64 * cg + 8 * (lane & 7)) + ((k & 1) * 8 + (k >> 1)) * 512, v.x, v.y, v.z, v.w);
    }
  }
  PROF(25, m_epi);
}

#define HDELAY 300
#define ODELAY 0
#define PDELAY 500
#define WOQ 2
#define H5 1
#define RESQ 3
#define SRDELAY 400
#define ZPACE 20

DEV void o_load(const Params& P, int c, int e, int lane, int layer) {
  PW(8 + e)
  const int J = 2 * (c >> 3) + 1 - e;
#pragma unroll 1
  for (int s = 0; s < 8; ++s) mbar_expect1(B_O + 64 * e + 8 * s, s == (c & 7) ? 0 : 8192);
  mbar_wait(B_H, layer);
  if (ODELAY) delay(ODELAY);
  PROF(26, a_go);
  poll(P.S->F + (J * 32 + (lane & 7)), 1);
  PROF(25, h_seen);
#pragma unroll 1
  for (int s = 0; s < 8; ++s)
    if (s != (c & 7)) bulk((e ? SM_S1 : SM_XA) + s * 8192, P.S->O + (J * 4096 + s * 512), 8192, B_O + 64 * e + 8 * s);
  PROF(28, a_o);
}

DEV void stats(const Params& P, int c, int w, int lane, int layer) {
  PW(12 + w)
  lane = opq(lane);
  const int r = (lane & 6) + ((lane >> 3) & 1), k = (2 * (c & 3) + (lane & 1)) ^ r, e = 1 - ((c >> 2) & 1);
  const uint32_t o = (32 * w + 8 * (lane >> 4) + r) * 128 + k * 16;
  const uint32_t mk = ((k & 1) == (r >> 2)) << (r & 3), tag = 1 - layer;
  float v[16];
#pragma unroll
  for (int z = 0; z < 16; ++z) v[z] = 0.f;
#pragma unroll 1
  for (int q = 0; q < 4; ++q) {
    mbar_wait(B_X + 16 * q + 8 * e, layer);
    PROF(19 + q, s_l);
    uint4 x, y;
    for (int it = 0;; ++it) {
      x = lds4v(xstage(q, e) + o); y = lds4v(xstage(q, e) + o + 2048);
      const uint32_t bad = (((x.x ^ tag) | (y.x ^ tag)) & mk) | (((x.y ^ tag) | (y.y ^ tag)) & (mk >> 1)) |
                           (((x.z ^ tag) | (y.z ^ tag)) & (mk >> 2)) | (((x.w ^ tag) | (y.w ^ tag)) & (mk >> 3));
      if (!__any_sync(0xffffffffu, bad & 1)) break;
      spin_guard(it);
    }
    mbar_arrive1(B_F + 8 * q);
    const uint32_t ws[8] = {x.x, x.y, x.z, x.w, y.x, y.y, y.z, y.w};
#pragma unroll
    for (int z = 0; z < 8; ++z) {
      const float lo = bflo(ws[z]), hi = bfhi(ws[z]);
      float* u = v + 4 * (z & 3);
      u[0] += lo; u[1] += lo * lo; u[2] += hi; u[3] += hi * hi;
    }
  }
  PROFD(14, s_part, __float_as_uint(v[0]));
  fold<8>(v, lane, 16); fold<4>(v, lane, 8); fold<2>(v, lane, 4); fold<1>(v, lane, 2);
  PROFD(16, s_fold, __float_as_uint(v[0]));
  if (w) {
    sts1(SM_MISC - 128 + w * 128 + lane * 4, __float_as_uint(v[0]));
    bar_arrive(NB_P, 128);
  } else {
    bar_sync(NB_P, 128);
    v[0] += lds1f(SM_MISC + lane * 4) + lds1f(SM_MISC + 128 + lane * 4) + lds1f(SM_MISC + 256 + lane * 4);
    float m;
    const float sd = ln_sd(v[0], __shfl_xor_sync(0xffffffffu, v[0], 2), m);
    if (!(lane & 2)) str1((uint32_t*)P.S->ST + (16 * c + 8 * (lane & 1) + (lane >> 2)), pack2(m, sd));
    sts4(SM_STAT + (lane & 15) * 16, 0x3F800000u, 0x3F800000u, 0x3F803F80u, 0x3F803F80u);
    fence_async_smem();
    PROF(17, s_pub);
    uint4 s;
    for (int it = 0;; ++it) {
      s = ldr4(P.S->ST + ((c >> 3) * 32 + lane));
      if (__all_sync(0xffffffffu, min4(s) != 0u)) break;
      spin_guard(it);
    }
    PROF(18, s_seen);
    const float r0 = rcp(bfhi(s.x)), r1 = rcp(bfhi(s.y)), r2 = rcp(bfhi(s.z)), r3 = rcp(bfhi(s.w));
    const uint32_t sg = 0x80008000u;
    sts4(SM_MISC + lane * 16, prmt(s.x, s.x, 0x1010) ^ sg, prmt(s.y, s.y, 0x1010) ^ sg, prmt(s.z, s.z, 0x1010) ^ sg, prmt(s.w, s.w, 0x1010) ^ sg);
    sts4(SM_STAT + 256 + lane * 32, __float_as_uint(r0), __float_as_uint(r1), pack2(r0, r1), prmt(s.x, s.y, 0x7632));
    sts4(SM_STAT + 272 + lane * 32, __float_as_uint(r2), __float_as_uint(r3), pack2(r2, r3), prmt(s.z, s.w, 0x7632));
    __syncwarp();
    mbar_arrive1(B_ST);
  }
  PROF(15, s_stat);
  if (w >= 2) {
    const uint4* h = P.S->H + (c * 256 + (w & 1) * 128 + lane);
    uint4 hv[4];
#pragma unroll
    for (int z = 0; z < 4; ++z) hv[z] = make_uint4(0, 0, 0, 0);
    bar_sync(NB_RL, 128 + 64 * HPRI);
    PROFD(26, s_hb, lds1v(SM_MISC));
    delay(HDELAY);
    for (int it = 0; c >= 8; ++it) {
#pragma unroll
      for (int z = 0; z < 4; ++z) hv[z] = ldr4(h + z * 32);
      if (__all_sync(0xffffffffu, min(min(hv[0].x, hv[1].x), min(hv[2].x, hv[3].x)) != 0u)) break;
      spin_guard(it);
    }
#pragma unroll
    for (int z = 0; z < 4; ++z) sts4(kvslot(c & 7, w & 1) + lane * 16 + z * 512, hv[z].x, hv[z].y, movm(hv[z].z), movm(hv[z].w));
    bar_arrive(NB_H, 128);
    mbar_arrive1_if(B_ST + 8, w == 3);
    PROF(25, s_halo);
  }
}

DEV void finalize(const Params& P, int c, int lane, int layer) {
  PW(12)
  float z[4];
  if (layer == 0) {
    bar_sync(NB_P, 256);
    z[0] = z[1] = z[2] = z[3] = 0.f;
#pragma unroll
    for (int k = 0; k < 2; ++k) { const float4 a = lds4f(SM_RES + 8192 + k * 512 + lane * 16); z[0] += a.x; z[1] += a.y; z[2] += a.z; z[3] += a.w; }
  } else {
    mbar_wait(B_ED + 8 - 2 * (c & 4), 0);
    const uint4* ps = &P.S->PS[c * 64 + lane];
    uint4 a, b;
    for (int it = 0;; ++it) {
      a = ldr4(ps); b = ldr4(ps + 32);
      if (__all_sync(0xffffffffu, min(a.x, b.x) != 0u)) break;
      spin_guard(it);
    }
    z[0] = __uint_as_float(a.x) + __uint_as_float(b.x); z[1] = __uint_as_float(a.y) + __uint_as_float(b.y);
    z[2] = __uint_as_float(a.z) + __uint_as_float(b.z); z[3] = __uint_as_float(a.w) + __uint_as_float(b.w);
  }
#pragma unroll
  for (int o = 8; o < 32; o <<= 1)
#pragma unroll
    for (int k = 0; k < 4; ++k) z[k] += __shfl_xor_sync(0xffffffffu, z[k], o);
  float m0, m1;
  const float r0 = rcp(ln_sd(z[0], z[1], m0)), r1 = rcp(ln_sd(z[2], z[3], m1));
  const uint32_t wr = nz(pack2(r0, r1)), wm = pack2(m0, m1);
  uint2* so = (uint2*)P.S->SR[layer] + ((lane >> 3) * 1024 + (lane & 2) * 256 + 4 * c + ((lane >> 1) & 2) + (lane & 1));
  str2(so, wr, wm); str2(so + 4096, wr, wm);
  if (!LATEF) bar_arrive_if(NB_Q, 448, !layer);
  PROF(23, s_sr);
}

DEV void announce(const Params& P, int c, int lane, int layer) {
  PW(13)
  if (layer) { mbar_wait(B_ED, 0); mbar_wait(B_ED + 8, 0); } else bar_sync(NB_H, 288);
  cnt_add(P, 5 * layer, c, lane);
  if (!LATEF) { bar_arrive_if(NB_Q, 448, !layer); fence_async_smem(); }
  PROF(24, s_own);
}

DEV void fetch(const Params& P, int c, int lane, int layer) {
  PW(13)
  mbar_expect1(B_E, 24576);
  cnt_wait(P, 5 * layer, c, lane);
#pragma unroll
  for (int k = 0; k < 4; ++k) bulk(SM_R + k * 16384 + R_B, P.S->XG[layer] + (128 * k + c) * 256, 4096, B_E);
  if (layer) delay(SRDELAY);
  bulk(SM_RES, P.S->SR[layer][c >> 4], 8192, B_E);
  if (!layer) { l2_prefetch(P.wqkv + c * 6144, 12288); l2_prefetch(P.wo + c * 2048, 4096); }
  PROF(25, s_all);
}

DEV void cs_part(const Params& P, int c, int w, int lane, int layer) {
  float cs[8];
#pragma unroll
  for (int k = 0; k < 8; ++k) cs[k] = 0.f;
  const int col = w * 512 + 64 * (c & 7) + 8 * (lane & 7);
#pragma unroll 1
  for (int r = 2 * layer; r < 2; ++r) {
    uint4 v[4];
#pragma unroll
    for (int k = 0; k < 4; ++k) v[k] = ldnc4(P.wqkv + ((32 * (c >> 3) + 16 * r + (lane >> 3)) * 1536 + col) + 4 * k * 1536);
#pragma unroll
    for (int k = 0; k < 4; ++k) {
      cs[0] += bflo(v[k].x); cs[1] += bfhi(v[k].x); cs[2] += bflo(v[k].y); cs[3] += bfhi(v[k].y);
      cs[4] += bflo(v[k].z); cs[5] += bfhi(v[k].z); cs[6] += bflo(v[k].w); cs[7] += bfhi(v[k].w);
    }
  }
  fold<4>(cs, lane, 16); fold<2>(cs, lane, 8);
  str2((float*)P.S->CS + ((c >> 3) * 1536 + col + 2 * (lane >> 3)), max(__float_as_uint(cs[0]), 1u - layer), __float_as_uint(cs[1]));
}

DEV void cs_sum(const Params& P, int c, int w, int lane) {
  float a, b;
  for (int it = 0;; ++it) {
    uint32_t m = ~0u;
    a = b = 0.f;
#pragma unroll
    for (int k = 0; k < 16; ++k) {
      const uint2 u = ldr2((const float*)P.S->CS + (w * 512 + 64 * (c & 7) + 2 * lane) + k * 1536);
      a += __uint_as_float(u.x); b += __uint_as_float(u.y); m = min(m, u.x);
    }
    if (__all_sync(0xffffffffu, m != 0u)) break;
    spin_guard(it);
  }
  const uint32_t hi = pack2(a, b), ad = SM_CS + w * 256 + (lane >> 2) * 32 + (lane & 3) * 4;
  sts1(ad, hi); sts1(ad + 16, pack2(a - bflo(hi), b - bfhi(hi)));
  fence_async_smem();
  __syncwarp();
  mbar_arrive1(B_CS);
}

DEV void x0_get(uint32_t (&x)[8][2], uint32_t a) {
  asm volatile("cp.async.wait_group 0;" ::: "memory");
#pragma unroll
  for (int z = 0; z < 4; ++z) {
    const uint4 v = lds4(a + z * 512);
    x[2 * (z & 2)][z & 1] = v.x; x[2 * (z & 2) + 1][z & 1] = v.y; x[2 * (z & 2) + 2][z & 1] = v.z; x[2 * (z & 2) + 3][z & 1] = v.w;
  }
}

DEV void par_load(const Params& P, int ch, int m, uint32_t (&pv)[8]) {
  const int mo = ch * 128 + m;
  pv[0] = ldnc16(P.Are + mo); pv[1] = ldnc16(P.Aim + mo); pv[2] = ldnc16(P.Bre + mo); pv[3] = ldnc16(P.Bim + mo);
  pv[4] = ldnc16(P.Cre + mo); pv[5] = ldnc16(P.Cim + mo); pv[6] = ldnc16(P.logdt + ch); pv[7] = ldnc16(P.dskip + ch);
}

__global__ void __launch_bounds__(NTHR, 1)
fused_kernel(const __grid_constant__ Params P, const __grid_constant__ CUtensorMap mapW,
             const __grid_constant__ CUtensorMap mapWo) {
  extern __shared__ __align__(1024) uint8_t smem_raw[];
  if (s2u(smem_raw) != SB) __trap();
  const int warp0 = __shfl_sync(0xffffffffu, threadIdx.x >> 5, 0), lane0 = threadIdx.x & 31;
  uint32_t smid; asm volatile("mov.u32 %0,%%smid;" : "=r"(smid));
  const int c = __shfl_sync(0xffffffffu, P.by_sm ? P.role[smid] : blockIdx.x, 0);
  if (c == 255) {
    if (threadIdx.x < NCOPY * NSUB)
#pragma unroll 1
      for (int it = 0; it < 256 && ldr1(P.S->C + 32 * threadIdx.x) < 128 / NSUB; ++it) __nanosleep(200);
    return;
  }
  const int cg = c & 7;
  PW(warp0)
  uint32_t dskip;
  {
    [[maybe_unused]] const int layer = 0;
    const int lane = lane0, g = lane >> 2, t = lane & 3, warp = warp0, k4 = warp >> 2, w = warp & 3;
    uint32_t pv[8];
    if (k4 < 2) par_load(P, 128 * k4 + c, 32 * w + lane, pv);
    else {
#pragma unroll
      for (int n = 0; n < 8; ++n) pv[n] = 0;
#pragma unroll
      for (int n = 0; n < 7; ++n) mbar_init1(SM_BAR + (n < 5 ? warp * 40 - 320 : 152 + warp * 16) + n * 8, n < 5 ? 1 : (CNT >> (4 * warp - 32)) & 15);
    }
    __syncthreads();
    const uint16_t* r = P.x0 + ((k4 < 2 ? 8192 * c + 64 * warp : (128 * (c >> 3) + 16 * (warp - 8)) * 512 + 64 * cg) + 1024 * g + 8 * t);
    const uint32_t xa = SM_R + k4 * 16384 + w * 2048 + lane * 16;
#pragma unroll
    for (int z = 0; z < 4; ++z) cp16(xa + z * 512, r + (z & 1) * 512 + (z & 2) * 16);
    asm volatile("cp.async.commit_group;" ::: "memory");
    sts4(SM_TAP + k4 * TAP_SZ + (32 * w + lane) * 16, 0, 0, 0, 0);
    sts4z_if(SM_TAP + k4 * TAP_SZ + 2048 + (32 * w + lane) * 16, w < 3);
    uint32_t x[8][2];
    if (k4 >= 2) {
      if (threadIdx.x == 448) {
        asm volatile("prefetch.tensormap [%0];" :: "l"(&mapW) : "memory");
        asm volatile("prefetch.tensormap [%0];" :: "l"(&mapWo) : "memory");
      }
      __syncwarp();
      if (PDELAY) delay(PDELAY);
      par_load(P, 128 * k4 + c, 32 * w + lane, pv);
      x0_get(x, xa);
      PROF(27, a_ld);
      xg_store<false>(P.S->XG[0] + (64 * cg * 256 + 16 * (c >> 3) + 8 * (k4 - 2)), x, SM_R + k4 * 16384 + 8192, NB_WG + k4, w, lane);
      bar_arrive(NB_H, 288);
      bar_sync(NB_Q, 448 + 64 * LATEF);
    }
    tables(pv, k4, w, lane);
    if (k4 < 2) {
      x0_get(x, xa);
      const float4 s = gram(x, g);
      if (t == (g >> 1)) sts4f(SM_RES + 8192 + (warp * 8 + g) * 16, s.x, s.y, s.z, s.w);
      __syncwarp();
      bar_arrive_if(NB_P, 256, warp != 7);
    }
    dskip = pv[7];
    PROF(1, a_x0);
  }
#pragma unroll 1
  for (int layer = 0; layer < 2; ++layer) {
    int lane = lane_here(P.zero);
    const int warp = warp0 | (layer & P.zero), k4 = warp >> 2, w = warp & 3;
    if (warp == (layer ? 12 : 7)) finalize(P, c, lane, layer);
    if (warp == (layer ? 13 : 6)) { announce(P, c, lane, layer); if (!LATEF) fetch(P, c, lane, layer); }
    if (layer == 0) {
      taps(dskip, k4, w, lane);
    }
    if (LATEF && warp == (layer ? 13 : 6)) fetch(P, c, lane, layer);
    conv(P, &mapW, c, k4, w, layer);
    lane = lane_here(P.zero);
    if (k4 < 2) {
      bar_arrive_if(NB_H, 160, !k4);
      if (warp == 0) {
        mbar_wait(B_K, 0);
        cnt_wait(P, 1 + 5 * layer, c, lane);
        x_load(P, c, 0, layer);
        PROF(27, m_xi);
      } else if (k4 == 0) cs_part(P, c, w - 1, lane, layer);
      attn_phase(P, c, k4, w, lane, layer);
    } else {
      bar_arrive_if(NB_RL, 256, warp >= 10);
      if (k4 == 3) {
        stats(P, c, w, lane, layer);
      } else if (w < 2) {
        bar_sync_if(NB_RL, 256, w);
        cnt_wait(P, 3 + 5 * layer + w, c, lane);
        bar_sync_if(NB_RL, 256, !w);
        if (w) mbar_wait(B_F, layer);
        x_load(P, c, 2 + w, layer);
        if (H5 && w) w_load(&mapW, cg, 5);
        PROF(14, h_xi);
        if (w == 1) str4(&P.S->SR[layer][lane >> 2][4 * c + (lane & 3)], 0, 0, 0, 0);
      } else if (w == 2) {
        mbar_expect1(B_WO, 65536);
        mbar_expect1(B_RES, 16384);
#pragma unroll 1
        for (int q = 0; q < 4; ++q) {
          mbar_wait(B_F + 8 * q, layer);
          if (q < 2) w_load(&mapW, cg, 4 + 2 * q);
          if (q == 1 || (q == 0 && !H5)) w_load(&mapW, cg, 5 + 2 * q);
          if (WOQ == 0 && ((q + 1) & 2)) tma5(SM_R + (q & 2) * 16384, &mapWo, 64 * cg, 4 * (q & 2), B_WO);
          if (WOQ && q == 2) {
            if (WOQ >= 2) mbar_wait(B_ST, layer);
            tma5(SM_R, &mapWo, 64 * cg, 0, B_WO);
            if (WOQ < 3) tma5(SM_R + 32768, &mapWo, 64 * cg, 8, B_WO);
          }
          if (WOQ == 3 && q == 2) { mbar_wait(B_ST + 8, layer); tma5(SM_R + 32768, &mapWo, 64 * cg, 8, B_WO); }
          if (q == max(cg >> 1, RESQ)) {
#pragma unroll
            for (int e = 0; e < 2; ++e) bulk(SM_RES + e * 8192, P.S->XF + ((2 * (c >> 3) + 1 - e) * 4096 + cg * 512), 8192, B_RES);
          }
          PROF(15 + q, h_w);
        }
      }
      if (k4 == 2 && w != 2) {
        if (layer == 0) cs_sum(P, c, w - (w >> 1), lane);
        if (w == 3) {
          uint4* xz = P.S->XG[layer] + (c * 256 + lane);
          mbar_wait(B_F, layer);
#pragma unroll 1
          for (int k = 0; k < 32; ++k) {
            str4(xz + ((k >> 3) * 32768 + (k & 7) * 32), 0, 0, 0, 0);
            if (ZPACE) __nanosleep(ZPACE);
          }
          PROF(19, h_z);
        }
      }
      if (warp < 10) o_load(P, c, w, lane, layer);
    }
    asm volatile("mov.b32 %0,0;" : "=r"(dskip));
  }
}

typedef CUresult (*EncodeFn)(CUtensorMap*, CUtensorMapDataType, cuuint32_t, void*, const cuuint64_t*, const cuuint64_t*,
                             const cuuint32_t*, const cuuint32_t*, CUtensorMapInterleave, CUtensorMapSwizzle,
                             CUtensorMapL2promotion, CUtensorMapFloatOOBfill);

static int place_roles(uint8_t* role) {
  int dev = 0, nsm = 0;
  cudaGetDevice(&dev);
  cudaDeviceGetAttribute(&nsm, cudaDevAttrMultiProcessorCount, dev);
  if (nsm < 128 || nsm > 144 || (nsm & 1)) return 0;
  cudaFuncSetAttribute(fused_kernel, cudaFuncAttributeNonPortableClusterSizeAllowed, 1);
  int occ[9] = {0};
  for (int k = 2; k <= 8; ++k) {
    cudaLaunchConfig_t cfg = {};
    cudaLaunchAttribute at[1];
    at[0].id = cudaLaunchAttributeClusterDimension;
    at[0].val.clusterDim.x = 2 * k; at[0].val.clusterDim.y = 1; at[0].val.clusterDim.z = 1;
    cfg.gridDim = dim3(2 * k); cfg.blockDim = dim3(NTHR); cfg.dynamicSmemBytes = SM_TOTAL; cfg.attrs = at; cfg.numAttrs = 1;
    if (cudaOccupancyMaxActiveClusters(&occ[k], fused_kernel, &cfg) != cudaSuccess) { cudaGetLastError(); occ[k] = 0; }
  }
  int n[10];
  n[7] = occ[8]; n[6] = occ[7]; n[5] = occ[6] - 0; n[4] = occ[5];
  n[3] = occ[4] - n[7]; n[1] = occ[2] - n[3] - n[5] - n[7]; n[0] = n[2] = n[1];
  n[8] = occ[3] - n[2] - n[5];
  const int ntpc = nsm / 2;
  int sum = 0;
  bool ok = n[0] > 0 && n[0] <= 8;
  for (int r = 0; r < 9; ++r) { ok = ok && n[r] >= 0 && (r == 0 || n[r] <= n[r - 1]); sum += n[r]; }
  if (!ok || sum > ntpc) { for (int r = 0; r < 9; ++r) n[r] = r < 8 ? 8 : 0; sum = 64; }
  int tp[8][9], cnt[8] = {0}, pool[72], np = 0, id = 0;
  for (int r = 0; r < 9; ++r)
    for (int g = n[0] - n[r]; g < n[0]; ++g) tp[g][cnt[g]++] = id++;
  for (; id < ntpc; ++id) pool[np++] = id;
  int order[72], no = 0;
  for (int g = 0; g < n[0]; ++g) {
    const int full = cnt[g] / 4 * 4;
    for (int k = 0; k < cnt[g]; ++k) { if (k < full) order[no++] = tp[g][k]; else pool[np++] = tp[g][k]; }
  }
  for (int k = 0; k < np; ++k) order[no++] = pool[k];
  for (int k = 0; k < 144; ++k) role[k] = 255;
  for (int k = 0; k < 64; ++k) { role[2 * order[k]] = 2 * k; role[2 * order[k] + 1] = 2 * k + 1; }
  return nsm;
}

extern "C" void kernel_launch(void* const* d_in, const int* in_sizes, int n_in, void* d_out, int out_size) {
  (void)in_sizes; (void)n_in; (void)out_size;
  static EncodeFn enc = nullptr;
  static uint8_t role[144];
  static int nsm = 0;
  static void* scratch = nullptr;
  if (!enc) {
    void* fn = nullptr;
    cudaDriverEntryPointQueryResult qr;
    cudaGetDriverEntryPoint("cuTensorMapEncodeTiled", &fn, cudaEnableDefault, &qr);
    enc = (EncodeFn)fn;
    cudaFuncSetAttribute(fused_kernel, cudaFuncAttributeMaxDynamicSharedMemorySize, SM_TOTAL);
    nsm = place_roles(role);
    cudaGetSymbolAddress(&scratch, g_S);
  }
  CUtensorMap mW, mWo;
  {
    cuuint64_t dim[3] = {512, 512, 3}, str[2] = {3072, 1024};
    cuuint32_t box[3] = {64, 64, 3}, es[3] = {1, 1, 1};
    enc(&mW, CU_TENSOR_MAP_DATA_TYPE_BFLOAT16, 3, d_in[10], dim, str, box, es, CU_TENSOR_MAP_INTERLEAVE_NONE,
        CU_TENSOR_MAP_SWIZZLE_128B, CU_TENSOR_MAP_L2_PROMOTION_NONE, CU_TENSOR_MAP_FLOAT_OOB_FILL_NONE);
  }
  {
    cuuint64_t dim[5] = {512, 2, 4, 4, 16}, str[4] = {1024, 8192, 2048, 32768};
    cuuint32_t box[5] = {64, 2, 4, 4, 8}, es[5] = {1, 1, 1, 1, 1};
    enc(&mWo, CU_TENSOR_MAP_DATA_TYPE_BFLOAT16, 5, d_in[11], dim, str, box, es, CU_TENSOR_MAP_INTERLEAVE_NONE,
        CU_TENSOR_MAP_SWIZZLE_128B, CU_TENSOR_MAP_L2_PROMOTION_NONE, CU_TENSOR_MAP_FLOAT_OOB_FILL_NONE);
  }
  Params P;
  P.x0 = (const uint16_t*)d_in[0]; P.Are = (const uint16_t*)d_in[1]; P.Aim = (const uint16_t*)d_in[2];
  P.Bre = (const uint16_t*)d_in[3]; P.Bim = (const uint16_t*)d_in[4]; P.Cre = (const uint16_t*)d_in[5];
  P.Cim = (const uint16_t*)d_in[6]; P.logdt = (const uint16_t*)d_in[7]; P.dskip = (const uint16_t*)d_in[8];
  P.wqkv = (const uint16_t*)d_in[10]; P.wo = (const uint16_t*)d_in[11]; P.out = (uint16_t*)d_out;
  for (int k = 0; k < 144; ++k) P.role[k] = role[k];
  P.by_sm = nsm > 0;
  P.zero = 0;
  P.S = (Scratch*)scratch;
  fused_kernel<<<nsm > 0 ? nsm : 128, NTHR, SM_TOTAL, cudaStreamPerThread>>>(P, mW, mWo);
}
```

```cpp
#include <cuda_runtime.h>
#include <cuda_bf16.h>
#include <cuda.h>
#include <stdint.h>

#define DEV __device__ __forceinline__

#define NCOPY 4
#define NSUB 1
#define EA 0x2121
constexpr int NTHR = 512;
constexpr int SPIN_LIMIT = 1 << 22;

constexpr uint32_t SB = 1024;
constexpr uint32_t SM_XA   = SB;
constexpr uint32_t SM_S0   = SM_XA + 16384;
constexpr uint32_t SM_S1   = SM_S0 + 49152;
constexpr uint32_t SM_XB   = SM_S1 + 49152;
constexpr uint32_t SM_R    = SM_XB + 16384;
constexpr uint32_t SM_RES  = SM_R + 65536;
constexpr uint32_t SM_TAP  = SM_RES + 16384;
constexpr int TAP_SZ = 3584;
constexpr uint32_t SM_CS   = SM_TAP + 4 * TAP_SZ;
constexpr uint32_t SM_STAT = SM_CS + 768;
constexpr uint32_t SM_MISC = SM_STAT + 1280;
constexpr uint32_t SM_BAR  = SM_MISC + 512;
constexpr int SM_TOTAL = SM_BAR + 448 - SB;
constexpr int R_U = 512, R_A5 = 5120, R_A3 = 8704, R_B = 11776;
constexpr int T_E = 1536, T_O = T_E + 1602, T_C = 3714;
constexpr uint32_t B_W = SM_BAR, B_X = SM_BAR + 64, B_O = SM_BAR + 128, B_WO = SM_BAR + 256, B_RES = SM_BAR + 264;
constexpr uint32_t B_ST = SM_BAR + 272, B_R = SM_BAR + 288, B_E = SM_BAR + 304;
constexpr uint32_t B_F = SM_BAR + 320, B_G = SM_BAR + 352, B_K = SM_BAR + 376, B_ED = SM_BAR + 384, B_CS = SM_BAR + 400, B_H = SM_BAR + 416;
constexpr uint32_t CNT = 0x183444CC;
constexpr int NB_WG = 1, NB_T = 5, NB_Q = 10, NB_H = 11, NB_P = 14, NB_RL = 15;

struct Scratch {
  uint4    XG[2][512 * 256];
  uint4    XF[32 * 4096];
  uint4    O[32 * 8 * 512];
  uint32_t F[32 * 32];
  uint4    H[17 * 8 * 256];
  uint4    SR[2][8][512];
  uint4    ST[32 * 16];
  uint4    PS[128 * 64];
  float4   CS[16 * 1536 / 4];
  uint32_t C[10 * 32 * 32];
};
__device__ __align__(1024) Scratch g_S;

struct Params {
  int by_sm;
  uint32_t zero;
  Scratch* S;
  const uint16_t *x0, *Are, *Aim, *Bre, *Bim, *Cre, *Cim, *logdt, *dskip, *wqkv, *wo;
  uint16_t* out;
  uint8_t role[144];
};
#define EVENT(n) do {} while (0)
#define PROFD(slot, name, v) do {} while (0)
#define PROF(slot, name) do {} while (0)
#define PW(x)

DEV uint32_t s2u(const void* p) { return (uint32_t)__cvta_generic_to_shared(p); }
template <class T> DEV T opq(T x) { asm volatile("" : "+r"(x)); return x; }
DEV uint32_t pack2(float lo, float hi) { uint32_t d; asm("cvt.rn.bf16x2.f32 %0,%1,%2;" : "=r"(d) : "f"(hi), "f"(lo)); return d; }
DEV float bflo(uint32_t v) { return __uint_as_float(v << 16); }
DEV float bfhi(uint32_t v) { return __uint_as_float(v & 0xFFFF0000u); }
DEV float bfr(float x) { return bflo(pack2(x, 0.f)); }
DEV uint32_t hadd2(uint32_t a, uint32_t b) { uint32_t d; asm("add.rn.bf16x2 %0,%1,%2;" : "=r"(d) : "r"(a), "r"(b)); return d; }
DEV uint32_t hsub2(uint32_t a, uint32_t b) { uint32_t d; asm("sub.rn.bf16x2 %0,%1,%2;" : "=r"(d) : "r"(a), "r"(b)); return d; }
DEV uint32_t hmul2(uint32_t a, uint32_t b) { uint32_t d; asm("mul.rn.bf16x2 %0,%1,%2;" : "=r"(d) : "r"(a), "r"(b)); return d; }
DEV uint32_t hfma2(uint32_t a, uint32_t b, uint32_t c) { uint32_t d; asm("fma.rn.bf16x2 %0,%1,%2,%3;" : "=r"(d) : "r"(a), "r"(b), "r"(c)); return d; }
DEV uint32_t hmax2(uint32_t a, uint32_t b) { uint32_t d; asm("max.bf16x2 %0,%1,%2;" : "=r"(d) : "r"(a), "r"(b)); return d; }
DEV uint32_t prmt(uint32_t a, uint32_t b, uint32_t s) { uint32_t d; asm("prmt.b32 %0,%1,%2,%3;" : "=r"(d) : "r"(a), "r"(b), "r"(s)); return d; }
DEV uint32_t nz(uint32_t v) { return max(v, 1u); }
DEV uint32_t tagged(uint32_t v, uint32_t m, uint32_t tag) { return (v & ~m) | (tag & m); }
DEV uint4 hadd8(const uint4& a, const uint4& b) { return make_uint4(hadd2(a.x, b.x), hadd2(a.y, b.y), hadd2(a.z, b.z), hadd2(a.w, b.w)); }
DEV uint32_t min4(const uint4& v) { return min(min(v.x, v.y), min(v.z, v.w)); }
DEV float rcp(float x) { float y; asm("rcp.approx.ftz.f32 %0,%1;" : "=f"(y) : "f"(x)); return y; }
DEV float sqrt_(float x) { float y; asm("sqrt.approx.ftz.f32 %0,%1;" : "=f"(y) : "f"(x)); return y; }
DEV float ex2(float x) { float y; asm("ex2.approx.ftz.f32 %0,%1;" : "=f"(y) : "f"(x)); return y; }

DEV uint4 ldr4(const void* p) { uint4 v; asm volatile("ld.relaxed.gpu.global.v4.u32 {%0,%1,%2,%3},[%4];" : "=r"(v.x), "=r"(v.y), "=r"(v.z), "=r"(v.w) : "l"(p) : "memory"); return v; }
DEV void ldr4_if(uint4& v, const void* p, bool c) {
  asm volatile("{.reg .pred q; setp.ne.u32 q,%5,0; @q ld.relaxed.gpu.global.v4.u32 {%0,%1,%2,%3},[%4];}"
    : "+r"(v.x), "+r"(v.y), "+r"(v.z), "+r"(v.w) : "l"(p), "r"((uint32_t)c) : "memory");
}
DEV uint2 ldr2(const void* p) { uint2 v; asm volatile("ld.relaxed.gpu.global.v2.u32 {%0,%1},[%2];" : "=r"(v.x), "=r"(v.y) : "l"(p) : "memory"); return v; }
DEV uint32_t ldr1(const void* p) { uint32_t v; asm volatile("ld.relaxed.gpu.global.u32 %0,[%1];" : "=r"(v) : "l"(p) : "memory"); return v; }
DEV void str4(void* p, uint32_t a, uint32_t b, uint32_t c, uint32_t d) { asm volatile("st.relaxed.gpu.global.v4.u32 [%0],{%1,%2,%3,%4};" :: "l"(p), "r"(a), "r"(b), "r"(c), "r"(d) : "memory"); }
DEV void str2(void* p, uint32_t a, uint32_t b) { asm volatile("st.relaxed.gpu.global.v2.u32 [%0],{%1,%2};" :: "l"(p), "r"(a), "r"(b) : "memory"); }
DEV void str1(void* p, uint32_t a) { asm volatile("st.relaxed.gpu.global.u32 [%0],%1;" :: "l"(p), "r"(a) : "memory"); }
DEV void stw4(void* p, uint32_t a, uint32_t b, uint32_t c, uint32_t d) { asm volatile("st.global.v4.u32 [%0],{%1,%2,%3,%4};" :: "l"(p), "r"(a), "r"(b), "r"(c), "r"(d) : "memory"); }
DEV uint4 ldnc4(const void* p) { uint4 v; asm volatile("ld.global.nc.v4.u32 {%0,%1,%2,%3},[%4];" : "=r"(v.x), "=r"(v.y), "=r"(v.z), "=r"(v.w) : "l"(p)); return v; }
DEV uint4 ldw4(const void* p) { uint4 v; asm volatile("ld.global.v4.u32 {%0,%1,%2,%3},[%4];" : "=r"(v.x), "=r"(v.y), "=r"(v.z), "=r"(v.w) : "l"(p) : "memory"); return v; }
DEV void cp16(uint32_t d, const void* p) { asm volatile("cp.async.cg.shared.global [%0],[%1],16;" :: "r"(d), "l"(p) : "memory"); }
DEV uint32_t ldnc16(const void* p) { uint32_t v; asm volatile("ld.global.u16 %0,[%1];" : "=r"(v) : "l"(p) : "memory"); return v; }

DEV uint32_t lds1v(uint32_t a) { uint32_t v; asm volatile("ld.volatile.shared.u32 %0,[%1];" : "=r"(v) : "r"(a) : "memory"); return v; }
DEV uint4 lds4v(uint32_t a) { uint4 v; asm volatile("ld.volatile.shared.v4.u32 {%0,%1,%2,%3},[%4];" : "=r"(v.x), "=r"(v.y), "=r"(v.z), "=r"(v.w) : "r"(a) : "memory"); return v; }
DEV uint32_t lds1(uint32_t a) { uint32_t v; asm volatile("ld.shared.u32 %0,[%1];" : "=r"(v) : "r"(a)); return v; }
DEV uint2 lds2(uint32_t a) { uint2 v; asm volatile("ld.shared.v2.u32 {%0,%1},[%2];" : "=r"(v.x), "=r"(v.y) : "r"(a)); return v; }
DEV uint4 lds4(uint32_t a) { uint4 v; asm volatile("ld.shared.v4.u32 {%0,%1,%2,%3},[%4];" : "=r"(v.x), "=r"(v.y), "=r"(v.z), "=r"(v.w) : "r"(a)); return v; }
DEV uint32_t lds16(uint32_t a) { uint32_t v; asm volatile("ld.shared.u16 %0,[%1];" : "=r"(v) : "r"(a)); return v; }
DEV float lds1f(uint32_t a) { float v; asm volatile("ld.shared.f32 %0,[%1];" : "=f"(v) : "r"(a)); return v; }
DEV float2 lds2f(uint32_t a) { float2 v; asm volatile("ld.shared.v2.f32 {%0,%1},[%2];" : "=f"(v.x), "=f"(v.y) : "r"(a)); return v; }
DEV float4 lds4f(uint32_t a) { float4 v; asm volatile("ld.shared.v4.f32 {%0,%1,%2,%3},[%4];" : "=f"(v.x), "=f"(v.y), "=f"(v.z), "=f"(v.w) : "r"(a)); return v; }
DEV void sts1(uint32_t a, uint32_t v) { asm volatile("st.shared.u32 [%0],%1;" :: "r"(a), "r"(v) : "memory"); }
DEV void sts16(uint32_t a, uint32_t v) { asm volatile("{.reg .b16 h; cvt.u16.u32 h,%1; st.shared.u16 [%0],h;}" :: "r"(a), "r"(v) : "memory"); }
DEV void sts2f(uint32_t a, float x, float y) { asm volatile("st.shared.v2.f32 [%0],{%1,%2};" :: "r"(a), "f"(x), "f"(y) : "memory"); }
DEV void sts4f(uint32_t a, float x, float y, float z, float w) { asm volatile("st.shared.v4.f32 [%0],{%1,%2,%3,%4};" :: "r"(a), "f"(x), "f"(y), "f"(z), "f"(w) : "memory"); }
DEV void sts4(uint32_t a, uint32_t x, uint32_t y, uint32_t z, uint32_t w) { asm volatile("st.shared.v4.u32 [%0],{%1,%2,%3,%4};" :: "r"(a), "r"(x), "r"(y), "r"(z), "r"(w) : "memory"); }
DEV void sts4z_if(uint32_t a, bool c) { asm volatile("{.reg .pred q; setp.ne.u32 q,%1,0; @q st.shared.v4.u32 [%0],{%2,%2,%2,%2};}" :: "r"(a), "r"((uint32_t)c), "r"(0) : "memory"); }

DEV void ldsm4t(uint32_t& r0, uint32_t& r1, uint32_t& r2, uint32_t& r3, uint32_t a) { asm volatile("ldmatrix.sync.aligned.m8n8.x4.trans.shared.b16 {%0,%1,%2,%3},[%4];" : "=r"(r0), "=r"(r1), "=r"(r2), "=r"(r3) : "r"(a) : "memory"); }
DEV void stsm4(uint32_t a, uint32_t r0, uint32_t r1, uint32_t r2, uint32_t r3) { asm volatile("stmatrix.sync.aligned.m8n8.x4.shared.b16 [%0],{%1,%2,%3,%4};" :: "r"(a), "r"(r0), "r"(r1), "r"(r2), "r"(r3) : "memory"); }
DEV void stsm2(uint32_t a, uint32_t r0, uint32_t r1) { asm volatile("stmatrix.sync.aligned.m8n8.x2.shared.b16 [%0],{%1,%2};" :: "r"(a), "r"(r0), "r"(r1) : "memory"); }
DEV void stsm4t(uint32_t a, uint32_t r0, uint32_t r1, uint32_t r2, uint32_t r3) { asm volatile("stmatrix.sync.aligned.m8n8.x4.trans.shared.b16 [%0],{%1,%2,%3,%4};" :: "r"(a), "r"(r0), "r"(r1), "r"(r2), "r"(r3) : "memory"); }
DEV uint32_t movm(uint32_t a) { uint32_t d; asm volatile("movmatrix.sync.aligned.m8n8.trans.b16 %0,%1;" : "=r"(d) : "r"(a)); return d; }
DEV void mma16(float (&d)[4], uint32_t a0, uint32_t a1, uint32_t a2, uint32_t a3, uint32_t b0, uint32_t b1) {
  asm volatile("mma.sync.aligned.m16n8k16.row.col.f32.bf16.bf16.f32 {%0,%1,%2,%3},{%4,%5,%6,%7},{%8,%9},{%0,%1,%2,%3};"
    : "+f"(d[0]), "+f"(d[1]), "+f"(d[2]), "+f"(d[3]) : "r"(a0), "r"(a1), "r"(a2), "r"(a3), "r"(b0), "r"(b1));
}
DEV void mma16z(float (&d)[4], uint32_t a0, uint32_t a1, uint32_t a2, uint32_t a3, uint32_t b0, uint32_t b1) {
  asm volatile("mma.sync.aligned.m16n8k16.row.col.f32.bf16.bf16.f32 {%0,%1,%2,%3},{%4,%5,%6,%7},{%8,%9},{%10,%10,%10,%10};"
    : "=f"(d[0]), "=f"(d[1]), "=f"(d[2]), "=f"(d[3]) : "r"(a0), "r"(a1), "r"(a2), "r"(a3), "r"(b0), "r"(b1), "f"(0.f));
}
DEV void mma8z(float (&d)[4], uint32_t a0, uint32_t a1, uint32_t b0) {
  asm volatile("mma.sync.aligned.m16n8k8.row.col.f32.bf16.bf16.f32 {%0,%1,%2,%3},{%4,%5},{%6},{%7,%7,%7,%7};"
    : "=f"(d[0]), "=f"(d[1]), "=f"(d[2]), "=f"(d[3]) : "r"(a0), "r"(a1), "r"(b0), "f"(0.f));
}
DEV void mma8(float (&d)[4], uint32_t a0, uint32_t a1, uint32_t b0) {
  asm volatile("mma.sync.aligned.m16n8k8.row.col.f32.bf16.bf16.f32 {%0,%1,%2,%3},{%4,%5},{%6},{%0,%1,%2,%3};"
    : "+f"(d[0]), "+f"(d[1]), "+f"(d[2]), "+f"(d[3]) : "r"(a0), "r"(a1), "r"(b0));
}

DEV void bar_sync(int id, int n) { asm volatile("bar.sync %0,%1;" :: "r"(id), "r"(n) : "memory"); }
DEV void bar_arrive(int id, int n) { asm volatile("bar.arrive %0,%1;" :: "r"(id), "r"(n) : "memory"); }
DEV void bar_sync_if(int id, int n, int c) { asm volatile("{.reg .pred q; setp.ne.s32 q,%2,0; @q bar.sync %0,%1;}" :: "r"(id), "r"(n), "r"(c) : "memory"); }
DEV void bar_arrive_if(int id, int n, int c) { asm volatile("{.reg .pred q; setp.ne.s32 q,%2,0; @q bar.arrive %0,%1;}" :: "r"(id), "r"(n), "r"(c) : "memory"); }
DEV bool bar_any(int id, int n, bool c) {
  uint32_t r; asm volatile("{.reg .pred p,q; setp.ne.u32 q,%3,0; bar.red.or.pred p,%1,%2,q; selp.u32 %0,1,0,p;}" : "=r"(r) : "r"(id), "r"(n), "r"((uint32_t)c) : "memory");
  return __any_sync(0xffffffffu, r);
}
DEV void fence_async_glob() { asm volatile("fence.proxy.async.global;" ::: "memory"); }
DEV void fence_async_smem() { asm volatile("fence.proxy.async.shared::cta;" ::: "memory"); }
DEV void fence_gpu() { asm volatile("fence.acq_rel.gpu;" ::: "memory"); }
DEV void mbar_wait(uint32_t b, uint32_t ph) {
  asm volatile("{\n.reg .pred p;\nW: mbarrier.try_wait.parity.shared::cta.b64 p,[%0],%1;\n@!p bra W;\n}" :: "r"(b), "r"(ph) : "memory");
}
DEV bool mbar_test(uint32_t b, uint32_t ph) {
  uint32_t r; asm volatile("{.reg .pred p; mbarrier.test_wait.parity.shared::cta.b64 p,[%1],%2; selp.u32 %0,1,0,p;}" : "=r"(r) : "r"(b), "r"(ph) : "memory");
  return __all_sync(0xffffffffu, r);
}
DEV void spin_guard(int it) { asm volatile("{.reg .pred p; setp.gt.s32 p,%0,%1; @p trap;}" :: "r"(it), "n"(SPIN_LIMIT)); }
DEV uint32_t here(uint32_t zero) {
  uint32_t d; asm volatile("mov.u32 %0,%%clock;" : "=r"(d) :: "memory"); return d & zero;
}
DEV int lane_here(uint32_t zero) {
  uint32_t d; asm volatile("mov.u32 %0,%%laneid;" : "=r"(d)); return d | here(zero);
}
DEV void delay(uint32_t n) { const uint32_t t0 = clock(); while ((uint32_t)clock() - t0 < n); __syncwarp(); }
DEV void poll(const uint32_t* p, uint32_t n) {
  for (int it = 0; !__all_sync(0xffffffffu, ldr1(p) >= n); ++it) spin_guard(it);
}
DEV void cnt_add(const Params& P, int n, int c, int lane) { asm volatile("{.reg .pred p; setp.lt.s32 p,%1,%2; @p red.relaxed.gpu.global.add.u32 [%0],1;}" :: "l"(P.S->C + (32 * (NSUB * lane + c % NSUB) + n * 1024)), "r"(lane), "n"(NCOPY) : "memory"); }
DEV void cnt_wait(const Params& P, int n, int c, int lane) { poll(P.S->C + (32 * (NSUB * (c / (128 / NCOPY)) + lane % NSUB) + n * 1024), 128 / NSUB); }
DEV void mbar_init1(uint32_t b, int n) { asm volatile("{.reg .pred p; elect.sync _|p,0xffffffff; @p mbarrier.init.shared::cta.b64 [%0],%1;}" :: "r"(b), "r"(n) : "memory"); }
DEV void mbar_arrive1(uint32_t b) { asm volatile("{.reg .pred p; elect.sync _|p,0xffffffff; @p mbarrier.arrive.shared::cta.b64 _,[%0];}" :: "r"(b) : "memory"); }
DEV void mbar_arrive1_if(uint32_t b, int c) {
  asm volatile("{.reg .pred p,q; setp.ne.s32 q,%1,0; elect.sync _|p,0xffffffff; and.pred p,p,q; @p mbarrier.arrive.shared::cta.b64 _,[%0];}" :: "r"(b), "r"(c) : "memory");
}
DEV void mbar_expect1(uint32_t b, int bytes) { asm volatile("{.reg .pred p; elect.sync _|p,0xffffffff; @p mbarrier.arrive.expect_tx.shared::cta.b64 _,[%0],%1;}" :: "r"(b), "r"(bytes) : "memory"); }
DEV void flag_set1(uint32_t* q) { asm volatile("{.reg .pred p; elect.sync _|p,0xffffffff; @p st.relaxed.gpu.global.u32 [%0],1;}" :: "l"(q) : "memory"); }
DEV void tma3(uint32_t dst, const CUtensorMap* m, int c0, int c1, uint32_t bar) {
  asm volatile("{.reg .pred p; elect.sync _|p,0xffffffff;\n"
    "@p cp.async.bulk.tensor.3d.shared::cluster.global.mbarrier::complete_tx::bytes [%0],[%1,{%2,%3,%5}],[%4];}"
    :: "r"(dst), "l"(m), "r"(c0), "r"(c1), "r"(bar), "r"(0) : "memory");
}
DEV void tma5(uint32_t dst, const CUtensorMap* m, int c0, int c4, uint32_t bar) {
  asm volatile("{.reg .pred p; elect.sync _|p,0xffffffff;\n"
    "@p cp.async.bulk.tensor.5d.shared::cluster.global.mbarrier::complete_tx::bytes [%0],[%1,{%2,%5,%5,%5,%3}],[%4];}"
    :: "r"(dst), "l"(m), "r"(c0), "r"(c4), "r"(bar), "r"(0) : "memory");
}
DEV void bulk(uint32_t dst, const void* src, int bytes, uint32_t bar) {
  asm volatile("{.reg .pred p; elect.sync _|p,0xffffffff;\n@p cp.async.bulk.shared::cluster.global.mbarrier::complete_tx::bytes [%0],[%1],%2,[%3];}" :: "r"(dst), "l"(src), "r"(bytes), "r"(bar) : "memory");
}
DEV void bulk_store(void* dst, uint32_t src, int bytes) {
  asm volatile("{.reg .pred p; elect.sync _|p,0xffffffff;\n@p cp.async.bulk.global.shared::cta.bulk_group [%0],[%1],%2;}" :: "l"(dst), "r"(src), "r"(bytes) : "memory");
}
DEV void l2_prefetch(const void* src, int bytes) {
  asm volatile("{.reg .pred p; elect.sync _|p,0xffffffff;\n@p cp.async.bulk.prefetch.L2.global [%0],%1;}" :: "l"(src), "r"(bytes) : "memory");
}

DEV uint64_t mkdesc(uint32_t addr, uint32_t lbo, uint32_t sbo, uint32_t swz) {
  return (uint64_t)((addr >> 4) | ((lbo >> 4) << 16)) | ((uint64_t)((sbo >> 4) | (swz << 30)) << 32);
}
DEV void wg_fence() { asm volatile("wgmma.fence.sync.aligned;" ::: "memory"); }
DEV void wg_commit() { asm volatile("wgmma.commit_group.sync.aligned;" ::: "memory"); }
template <int N> DEV void wg_wait() { asm volatile("wgmma.wait_group.sync.aligned %0;" :: "n"(N) : "memory"); }
template <int N> DEV void zerov(float (&d)[N]) {
#pragma unroll
  for (int i = 0; i < N; ++i) asm volatile("mov.b32 %0,0;" : "=f"(d[i]));
}
template <int N> DEV void undef(float (&d)[N]) {
#pragma unroll
  for (int i = 0; i < N; ++i) asm volatile("" : "=f"(d[i]));
}
#define R4(d, o) "+f"(d[o]), "+f"(d[o + 1]), "+f"(d[o + 2]), "+f"(d[o + 3])
#define R8(d, o) R4(d, o), R4(d, o + 4)
#define R16(d, o) R8(d, o), R8(d, o + 8)
#define R32(d, o) R16(d, o), R16(d, o + 16)
#define L0 "%0,%1,%2,%3,%4,%5,%6,%7,%8,%9,"
#define L10(a) "%" #a "0,%" #a "1,%" #a "2,%" #a "3,%" #a "4,%" #a "5,%" #a "6,%" #a "7,%" #a "8,%" #a "9,"
#define WG_HEAD(pr, n) "{.reg .pred p; setp.ne.s32 p,%" #pr ",0;\nwgmma.mma_async.sync.aligned.m64n" #n "k16.f32.bf16.bf16 {"
DEV void wg_rs64k(float (&d)[32], const uint32_t (&a)[4], uint64_t db, int acc) {
  asm volatile(WG_HEAD(37, 64) L0 L10(1) L10(2) "%30,%31},{%32,%33,%34,%35},%36,p,1,1,0;}"
    : R32(d, 0) : "r"(a[0]), "r"(a[1]), "r"(a[2]), "r"(a[3]), "l"(db), "r"(acc));
}
DEV void wg_rs48t(float (&d)[24], const uint32_t (&a)[4], uint64_t db, int acc) {
  asm volatile(WG_HEAD(29, 48) L0 L10(1) "%20,%21,%22,%23},{%24,%25,%26,%27},%28,p,1,1,1;}"
    : R16(d, 0), R8(d, 16) : "r"(a[0]), "r"(a[1]), "r"(a[2]), "r"(a[3]), "l"(db), "r"(acc));
}
DEV void wg_rs32t(float (&d)[16], const uint32_t (&a)[4], uint64_t db, int acc) {
  asm volatile(WG_HEAD(21, 32) L0 "%10,%11,%12,%13,%14,%15},{%16,%17,%18,%19},%20,p,1,1,1;}"
    : R16(d, 0) : "r"(a[0]), "r"(a[1]), "r"(a[2]), "r"(a[3]), "l"(db), "r"(acc));
}
DEV void wg_ss48(float (&d)[24], uint64_t da, uint64_t db, int acc) {
  asm volatile(WG_HEAD(26, 48) L0 L10(1) "%20,%21,%22,%23},%24,%25,p,1,1,1,1;}" : R16(d, 0), R8(d, 16) : "l"(da), "l"(db), "r"(acc));
}
DEV void wg_ss64(float (&d)[32], uint64_t da, uint64_t db, int acc) {
  asm volatile(WG_HEAD(34, 64) L0 L10(1) L10(2) "%30,%31},%32,%33,p,1,1,0,1;}" : R32(d, 0) : "l"(da), "l"(db), "r"(acc));
}
DEV void wg_ss192(float (&d)[96], uint64_t da, uint64_t db, int acc) {
  asm volatile(WG_HEAD(98, 192) L0 L10(1) L10(2) L10(3) L10(4) L10(5) L10(6) L10(7) L10(8) "%90,%91,%92,%93,%94,%95},%96,%97,p,1,1,1,1;}"
    : R32(d, 0), R32(d, 32), R32(d, 64) : "l"(da), "l"(db), "r"(acc));
}

DEV void wg_rs192t(float (&d)[96], const uint32_t (&a)[4], uint64_t db) {
  asm volatile("wgmma.mma_async.sync.aligned.m64n192k16.f32.bf16.bf16 {" L0 L10(1) L10(2) L10(3) L10(4) L10(5) L10(6) L10(7) L10(8) "%90,%91,%92,%93,%94,%95},{%96,%97,%98,%99},%100,1,1,1,1;"
    : R32(d, 0), R32(d, 32), R32(d, 64) : "r"(a[0]), "r"(a[1]), "r"(a[2]), "r"(a[3]), "l"(db));
}

DEV float ln_sd(float s, float q, float& m) {
  m = s * (1.f / 512.f);
  return bfr(sqrt_(bfr(bfr(fmaxf(q * (1.f / 512.f) - m * m, 0.f)) + 1e-5f)));
}
template <int N> DEV float4 gram(const uint32_t (&w)[N][2], int g) {
  float s0[4], s1[4];
  const uint32_t one = 0x3F803F80u;
  mma16z(s0, w[0][0], one, w[1][0], one, w[0][0], w[1][0]); mma16z(s1, w[0][1], one, w[1][1], one, w[0][1], w[1][1]);
#pragma unroll
  for (int j = 2; j < N; j += 2) {
    mma16(s0, w[j][0], one, w[j + 1][0], one, w[j][0], w[j + 1][0]); mma16(s1, w[j][1], one, w[j + 1][1], one, w[j][1], w[j + 1][1]);
  }
  const bool od = g & 1;
  return make_float4(od ? s0[3] : s0[2], od ? s0[1] : s0[0], od ? s1[3] : s1[2], od ? s1[1] : s1[0]);
}
template <bool FRAG> DEV void xg_store(uint4* dst, const uint32_t (&w)[8][2], uint32_t stg, int nb, int wp, int lane) {
  const int t = lane & 3;
  const uint32_t a = stg + t * (FRAG ? 256 : 1024) + ((wp ^ t) * 32) + (lane >> 2) * 4;
#pragma unroll
  for (int n = 0; n < 8; ++n) {
    const uint32_t b = (a ^ ((n & 3) * 32)) + (FRAG ? n * 1024 : (n >> 2) * 4096 + (n & 3) * 256);
    sts1(b, prmt(w[n][0], w[n][1], 0x5410)); sts1(b + 128, prmt(w[n][0], w[n][1], 0x7632));
  }
  bar_sync(nb, 128);
  const int r = 4 * wp + (lane >> 3);
  const uint32_t b = stg + r * 128 + (((lane & 7) ^ (2 * (((r >> 1) ^ (r >> 3)) & 3))) * 16);
#pragma unroll
  for (int k = 0; k < 4; ++k) {
    const uint4 v = lds4((b ^ ((k & 1) * 64)) + k * 2048);
    str4(dst + (r * 256 + (lane & 7)) + k * 4096, nz(v.x), v.y, v.z, v.w);
  }
}
template <int N, int M> DEV void fold(float (&v)[M], int lane, int bit) {
  const bool b = lane & bit;
#pragma unroll
  for (int k = 0; k < N; ++k) { const float sn = b ? v[k] : v[k + N], kp = b ? v[k + N] : v[k]; v[k] = kp + __shfl_xor_sync(0xffffffffu, sn, bit); }
}
DEV void refetch(uint32_t dst, const uint4* src, int half, int e, int w) {
#pragma unroll 1
  for (int r = 0; r < 2; ++r) {
    if (w == 0) { mbar_expect1(B_R + 8 * e, half); bulk(dst + r * half, src + r * (half >> 4), half, B_R + 8 * e); }
    mbar_wait(B_R + 8 * e, r);
    bar_sync(NB_WG + e, 128);
  }
}
DEV uint32_t kvslot(int cg, int n) { return SM_XA + (cg < 4 ? 5 : 2) * 8192 + n * 2048; }
DEV uint32_t xstage(int q, int e) { return ((q + 1) & 2) ? SM_R + ((q & 2) + e) * 16384 : e ? SM_XB : SM_XA; }
DEV void cmul(float& orr, float& oi, float ar, float ai, float br, float bi) {
  float r = ar * br - ai * bi, i = ar * bi + ai * br; orr = r; oi = i;
}
DEV void cexp_(float al, float bt, float s, float& er, float& ei) {
  float mag = ex2(al * s), ph = bt * s;
  ph -= rintf(ph);
  float ang = ph * 6.283185307179586f;
  er = mag * __cosf(ang); ei = mag * __sinf(ang);
}

#define KS 2048
#define LATEF 0
DEV void put8(uint32_t a, const float (&r)[8], const float (&i)[8]) {
  sts4(a, pack2(r[0], r[1]), pack2(r[2], r[3]), pack2(r[4], r[5]), pack2(r[6], r[7]));
  sts4(a + 1024, pack2(i[0], i[1]), pack2(i[2], i[3]), pack2(i[4], i[5]), pack2(i[6], i[7]));
}
DEV void tables(const uint32_t (&pv)[8], int k4, int w, int lane) {
  PW(4 * k4 + w)
  [[maybe_unused]] const int layer = 0;
  const float dt = bfr(__expf(bflo(pv[6])));
  const float al = dt * bflo(pv[0]) * 1.4426950408889634f, bt = dt * bflo(pv[1]) * 0.15915494309189535f;
  float qr[8], qi[8], yr[8], yi[8];
  cmul(qr[0], qi[0], bflo(pv[4]), bflo(pv[5]), dt * bflo(pv[2]), dt * bflo(pv[3]));
  PROFD(2, a_par, __float_as_uint(qr[0] + al + bt));
  float e1r, e1i, eMr, eMi, eLr, eLi;
  cexp_(al, bt, 1.f, e1r, e1i); cexp_(al, -bt, 8.f, yr[1], yi[1]); cexp_(al, -bt, 64.f, eMr, eMi); cexp_(al, bt, 256.f, eLr, eLi);
  const uint32_t ad = SB + k4 * 32768 + (w & 1) * 512 + lane * 16, am = ad + (w >> 1) * KS, an = ad + (8 + 3 * (w >> 1)) * KS;
  yr[0] = 1.f; yi[0] = 0.f;
#pragma unroll
  for (int k = 1; k < 8; ++k) {
    cmul(qr[k], qi[k], qr[k - 1], qi[k - 1], e1r, e1i);
    if (k > 1) cmul(yr[k], yi[k], yr[k - 1], yi[k - 1], yr[1], yi[1]);
  }
  put8(an, qr, qi);
#pragma unroll
  for (int j = 0; j < 4; ++j) {
    put8(am + j * 2 * KS, yr, yi);
#pragma unroll
    for (int k = 0; k < 8; ++k) {
      if (j == 0 && k == 0) { yr[0] = eMr; yi[0] = eMi; } else if (j < 3) cmul(yr[k], yi[k], yr[k], yi[k], eMr, eMi);
    }
    if (j == 0) {
#pragma unroll
      for (int k = 0; k < 8; ++k) { const int o = k < 4 ? 2 * k : k < 6 ? 2 * k - 8 : k - 2; cmul(qr[k], qi[k], qr[o], qi[o], eLr, eLi); }
      put8(an + KS, qr, qi);
    } else if (j == 1) {
#pragma unroll
      for (int k = 0; k < 5; ++k) cmul(qr[k], qi[k], qr[k ? k - 1 : 6], qi[k ? k - 1 : 6], eLr, eLi);
      put8(an + 2 * KS, qr, qi);
    }
  }
  PROF(3, a_tab);
}

DEV void sts16_if(uint32_t a, uint32_t v, bool c) { asm volatile("{.reg .pred q; .reg .b16 h; setp.ne.u32 q,%2,0; cvt.u16.u32 h,%1; @q st.shared.u16 [%0],h;}" :: "r"(a), "r"(v), "r"((uint32_t)c) : "memory"); }
DEV void sts1_if(uint32_t a, uint32_t v, bool c) { asm volatile("{.reg .pred q; setp.ne.u32 q,%2,0; @q st.shared.u32 [%0],%1;}" :: "r"(a), "r"(v), "r"((uint32_t)c) : "memory"); }
DEV void taps(uint32_t dskip, int k4, int w, int lane) {
  PW(4 * k4 + w)
  [[maybe_unused]] const int layer = 0;
  fence_async_smem();
  bar_sync(k4 > LATEF ? NB_WG + k4 : NB_Q, k4 > LATEF ? 128 : 448 + 64 * LATEF);
  float d[24];
  undef(d);
  const uint64_t da = mkdesc(SB + k4 * 32768, 1024, KS, 0);
  wg_fence();
#pragma unroll
  for (int j = 0; j < 8; ++j) wg_ss48(d, da + j * 8, da + KS / 2 + j * 8, j);
  wg_commit();
  const int b = 8 * w + (lane >> 2), t = lane & 3, id = 32 * w + lane;
  constexpr int DO = T_O - T_E;
  const uint32_t te = SM_TAP + k4 * TAP_SZ + T_E, a0 = te - 16 * b - 4 * t;
  const uint32_t a1 = a0 - 512 - 4 * t, a2 = te - 2 * (511 + b) - 64 * t, a3 = te + (T_C - T_E) - 2 * (127 + b) - 128 * t;
  wg_wait<0>();
  PROF(4, a_mma);
  {
    const uint32_t v = pack2(d[1] + d[15], d[0] + d[14] + (id ? 0.f : bflo(dskip)));
    sts1(a0 + DO - 2, v); sts16(a0 - 2, v); sts16(a0, v >> 16);
  }
  {
    const uint32_t v = pack2(d[5] + d[19], d[4] + d[18]), u = prmt(v, v, 0x3232);
    const bool lo = t < 2, k512 = id == 2;
    sts1_if(k512 ? te - 2 * 512 : a1, u, (lo && id) || k512);
    sts1_if(k512 ? te - 2 * 514 : a1 - 4, k512 ? u : v, lo || k512);
    sts1_if(k512 ? te + DO - 2 * 513 : a1 + DO - 2, u, lo || k512);
    sts16(lo ? a1 + DO - 4 : a2 + DO - 194, v);
    sts16(lo ? (id ? a1 + DO + 2 : a1) : k512 ? te + DO - 2 * 511 : a2 + DO, u);
    sts16_if(a2 - 194, v, !lo);
    sts16_if(k512 ? te + DO - 2 * 514 : a2, u, !lo);
  }
  {
    const uint32_t v = pack2(d[8] + d[22], d[9] + d[23]);
    sts16_if(id ? a3 : te - 2 * 639, v, t < 2 || id == 2);
    sts16_if(a3 - 64, v >> 16, t < 2);
    sts16_if(te + DO - 2 * 639, v, id == 0);
  }
  bar_sync(NB_WG + k4, 128);
  mbar_arrive1_if(B_K, w == 0);
}

DEV uint32_t cpy(uint32_t v, uint32_t id) {
  uint32_t d; asm volatile("prmt.b32 %0,%1,%1,%2;" : "=r"(d) : "r"(v), "r"(id)); return d;
}
DEV uint32_t uoff(int s) { return (s ^ ((s >> 3) & 3)) * 16; }
template <bool FULL> DEV void boxes(const uint32_t (&u)[10], uint32_t a, uint32_t a9, uint32_t a7, uint32_t (&pv)[4]) {
  uint32_t v[8], p[8], x[4], y[4];
#pragma unroll
  for (int j = 0; j < 8; ++j) { v[j] = prmt(u[j], u[j + 1], 0x5432); p[j] = hadd2(u[j], v[j]); }
#pragma unroll
  for (int j = 0; j < 4; ++j) { x[j] = hadd2(hadd2(p[j + 1], p[j + 2]), u[j + 3]); y[j] = hadd2(v[j + 3], p[j + 4]); }
  sts4(a + R_A5, x[0], x[1], x[2], x[3]);
  sts4(a + R_A3, y[0], y[1], y[2], y[3]);
  if (FULL) {
#pragma unroll
    for (int j = 0; j < 4; ++j) { x[j] = hadd2(x[j], hadd2(v[j], v[j + 3])); y[j] = hadd2(x[j], hadd2(u[j], u[j + 4])); pv[j] = p[j + 4]; }
    sts4(a7, x[0], x[1], x[2], x[3]);
    sts4(a9, y[0], y[1], y[2], y[3]);
  }
}
DEV void halo(uint32_t (&u)[10], uint32_t a, int lane) {
  asm volatile("{.reg .pred p,q; setp.eq.s32 p,%8,0; setp.lt.s32 q,%8,2;\n@p ld.shared.v4.u32 {%2,%3,%4,%5},[%6];\n@q ld.shared.v2.u32 {%0,%1},[%7];}"
    : "+r"(u[0]), "+r"(u[1]), "+r"(u[2]), "+r"(u[3]), "+r"(u[4]), "+r"(u[5]) : "r"(a), "r"(a + 24 - 16 * lane), "r"(lane));
}
DEV void quad_ld(uint32_t (&q)[4], uint32_t a) { q[0] = lds1(a); q[2] = lds1(a + 16); q[1] = lds1(a - 128); q[3] = lds1(a - 112); }
DEV void half_ld(uint32_t (&q)[4][4], uint32_t a, uint32_t zero) {
  zero = here(zero);
#pragma unroll
  for (int kk = 0; kk < 2; ++kk) {
    q[2 + kk][0] = lds1(a + 32 * kk); q[2 + kk][2] = lds1(a + 32 * kk + 16);
    q[2 + kk][1] = cpy(zero, 2 * kk); q[2 + kk][3] = cpy(zero, 2 * kk + 1);
  }
}

#define ROT 2
#define G1 -1
#define G2 0
#define G3 1
#define TPS 0x6236
#define GMASK ((G1 >= 0 ? 2 : 0) | (G2 >= 0 ? 4 : 0) | (G3 >= 0 ? 8 : 0))
#define GATE1(g, n, p) if (g >= 0 && (g & 3) == p) mbar_arrive1_if(B_G + 8 * n, k4 == (g >> 2));
#define GATE(p) GATE1(G1, 0, p) GATE1(G2, 1, p) GATE1(G3, 2, p)
#define TMASK(p) (((TPS & 15) == p) | ((((TPS >> 4) & 15) == p) << 1) | ((((TPS >> 8) & 15) == p) << 2) | ((((TPS >> 12) & 15) == p) << 3))
#define TURN(p) if (TMASK(p) == 15) bar_arrive(NB_T + 1 + k4, 256); else if (TMASK(p)) { if ((TMASK(p) >> k4) & 1) bar_arrive(NB_T + 1 + k4, 256); }
#define ANN(p, dep) if (EA & (0x1111 * p)) cnt_add(P, 1 + 5 * layer + k4, c, (32 * (v ^ 3) + lane) | (dep) | ((~(EA >> (4 * k4)) & p) << 8));
DEV void w_load(const CUtensorMap* mW, int cg, int h) {
  mbar_expect1(B_W + 8 * h, 24576);
  tma3(SM_S0 + (h & 3) * 24576, mW, 64 * cg, 64 * h, B_W + 8 * h);
}

DEV void conv(const Params& P, const CUtensorMap* mW, int c, int k4, int w, int layer) {
  const uint32_t zero = P.zero;
  PW(4 * k4 + w)
  int lane = lane_here(zero);
  const int g = lane >> 2, t = lane & 3, v = w ^ (ROT * (k4 & 1)), tid = 32 * v + lane;
  const uint32_t reg = SM_R + k4 * 16384, tp = SM_TAP + k4 * TAP_SZ;
  const uint32_t g0 = tp + ((g & 1) ? T_O : T_E) + 2 * (2 * t - g);
  uint32_t F[18][4], U[12];
  {
    const uint32_t ga = g0 - 32 * (w & 1) - 576 * (w >> 1);
    F[0][2] = lds1(ga + 48);
#pragma unroll
    for (int j = 0; j < 12; ++j) { F[j][0] = lds1(ga + 32 - 32 * j); F[j][1] = lds1(ga + 16 - 32 * j); }
#pragma unroll
    for (int j = 0; j < 12; ++j) U[j] = lds1(ga - 352 - 16 * j);
  }
  PROF(5, a_pre);
  if (k4 == 3 && w == 3) {
    mbar_wait(B_E, layer);
    mbar_wait(B_K, 0);
#pragma unroll
    for (int h = 0; h < 4; ++h) w_load(mW, c & 7, h);
  }
  mbar_wait(k4 && ((GMASK >> k4) & 1) ? B_G - 8 + 8 * k4 : B_E, layer);
  PROF(6, a_x);
  const uint32_t ua = reg + R_U + uoff(tid);
  uint4 x[2];
  uint32_t pv[4];
  {
    uint4 s[4];
#pragma unroll
    for (int z = 0; z < 2; ++z) x[z] = lds4(reg + R_B + tid * 16 + z * 2048);
#pragma unroll
    for (int z = 0; z < 4; ++z) s[z] = lds4(SM_RES + tid * 16 + (z >> 1) * 2048 + (z & 1) * 4096);
    sts4z_if(reg + lane * 16 + (w ? w * 3584 + 1024 : 0), w < 3);
    for (int it = 0;; ++it) {
      uint32_t m = min(x[0].x, x[1].x);
#pragma unroll
      for (int z = 0; z < 4; ++z) m = min(m, min(s[z].x, s[z].z));
      if (m) break;
#pragma unroll
      for (int z = 0; z < 2; ++z) x[z] = ldr4(&P.S->XG[layer][(128 * k4 + c) * 256 + opq(tid) + z * 128]);
#pragma unroll
      for (int z = 0; z < 4; ++z) s[z] = ldr4(&P.S->SR[layer][c >> 4][opq(tid) + (z >> 1) * 128 + (z & 1) * 256]);
#pragma unroll
      for (int z = 0; z < 4; ++z) sts4(SM_RES + tid * 16 + (z >> 1) * 2048 + (z & 1) * 4096, s[z].x, s[z].y, s[z].z, s[z].w);
      spin_guard(it);
    }
    __syncwarp();
    uint32_t u[2][10];
#pragma unroll
    for (int z = 0; z < 2; ++z) {
      u[z][6] = hmul2(hsub2(x[z].x, s[2 * z].y), s[2 * z].x); u[z][7] = hmul2(hsub2(x[z].y, s[2 * z].w), s[2 * z].z);
      u[z][8] = hmul2(hsub2(x[z].z, s[2 * z + 1].y), s[2 * z + 1].x); u[z][9] = hmul2(hsub2(x[z].w, s[2 * z + 1].w), s[2 * z + 1].z);
      sts4(ua + z * 2048, u[z][6], u[z][7], u[z][8], u[z][9]);
    }
#pragma unroll
    for (int j = 0; j < 6; ++j) u[0][j] = __shfl_up_sync(0xffffffffu, u[0][j < 2 ? 8 + j : 4 + j], j < 2 ? 2 : 1);
    bar_sync(NB_WG + k4, 128);
    GATE(0)
    PROF(7, a_u);
    const uint32_t h1 = reg + R_U + v * 512 - 64;
    halo(u[0], h1, lane);
    if (v < 2) {
      u[1][0] = 0;
#pragma unroll
      for (int j = 1; j < 6; ++j) u[1][j] = __shfl_up_sync(0xffffffffu, u[1][j < 2 ? 8 + j : 4 + j], j < 2 ? 2 : 1);
      halo(u[1], h1 + 2048, lane);
      boxes<false>(u[1], reg + tid * 16 + 2048, 0, 0, pv);
    }
    const uint32_t bo = reg + R_B + tid * 16 + (v >> 1) * 1056;
    const uint32_t be = tid == 127 ? reg + R_B + 1024 : bo + (tid == 63 ? 2112 : 1056);
    boxes<true>(u[0], reg + tid * 16, (lane & 1) ? be : bo, (lane & 1) ? bo : be, pv);
    sts4z_if(reg + R_B + 1040, tid == 0);
  }
  GATE(1)
  fence_async_smem();
  if (k4 == 3 && w < 3) {
    const uint32_t src = SM_RES + 8192 + w * 2048, f = (w >> 1) - 1;
#pragma unroll
    for (int z = 0; z < 4; ++z) sts4(src + lane * 16 + z * 512, f, f, f, f);
    fence_async_smem();
    __syncwarp();
    if (w < 2) {
#pragma unroll
      for (int z = 0; z < 4; ++z) bulk_store(&P.S->O[((c >> 3) * 16 + w * 8 + (c & 7)) * 512] + z * 128, src, 2048);
    } else {
#pragma unroll
      for (int z = 0; z < 2; ++z) {
        bulk_store(&P.S->H[(c + 8) * 256] + z * 128, src, 2048);
        bulk_store(P.S->F + ((c >> 3) * 64 + 4 * (c & 7)) + z * 32, src, 16);
      }
      bulk_store(&P.S->PS[c * 64], src, 1024);
      bulk_store(&P.S->ST[c * 4], src, 64);
      if (c < 5) bulk_store(P.S->C + (c + 5 - 5 * layer) * 1024, src, 128 * NCOPY * NSUB);
    }
    asm volatile("cp.async.bulk.commit_group;" ::: "memory");
  }
  const uint32_t id = opq(0x3210u);
#pragma unroll
  for (int j = 0; j < 12; ++j) { F[j][3] = cpy(F[j][0], id); if (j) F[j][2] = cpy(F[j - 1][1], id); }
  PROF(8, a_box);
  bar_sync(NB_T + k4, k4 ? 256 : 128);
  PROF(9, a_turn);
  float acc[32], f1[24], f3[16];
  uint32_t qa[4][4], qb[4][4], qc[4][4], yp[16];
  const uint64_t db = mkdesc(reg + R_U, 16, 512, 2) + 2;
#define STEP(mm, n) wg_fence(); mm; wg_commit(); wg_wait<n>();
#define D(j, n) STEP(wg_rs64k(acc, F[j], db - 2 * j, j), n)
#define T(q, j, o, n) STEP(wg_rs48t(f1, q[j], d1 + o + 16 * (j & 1) - 32 * (j >> 1), o | j), n)
#define SPREAD(n) { const uint32_t id = 0x3210u | here(zero); _Pragma("unroll") for (int j = n; j < n + 2; ++j) { \
    F[12 + j][0] = cpy(U[2 * j], id); F[12 + j][1] = cpy(U[2 * j + 1], id); F[12 + j][3] = cpy(F[12 + j][0], id); F[12 + j][2] = cpy(F[11 + j][1], id); } }
  const uint32_t g1 = g0 - 2 * 576 - 16 * w;
  const uint64_t d1 = mkdesc(reg + R_A5, 128, 512, 0);
  undef(acc);
  D(0, 3) TURN(0) D(1, 3) D(2, 3) D(3, 3) D(4, 3) SPREAD(0) D(5, 3) D(6, 3) TURN(1) SPREAD(2) D(7, 3) quad_ld(qa[0], g1);
  D(8, 3) SPREAD(4) D(9, 3) quad_ld(qa[1], g1 + 32); D(10, 3) half_ld(qa, g1 - 64, zero);
  D(11, 3) quad_ld(qb[0], g1 - 192); D(12, 3) TURN(2) quad_ld(qb[1], g1 - 160); D(13, 3) half_ld(qb, g1 - 256, zero);
  D(14, 3) D(15, 3) D(16, 3) D(17, 2)
  TURN(3)
  PROF(10, a_den);
  lane = lane_here(zero);
  const uint32_t g2 = tp + T_C - 258 - 32 * w + 4 * (lane & 3) - (lane & 28);
  undef(f1);
  T(qa, 0, 0, 2) quad_ld(qc[0], g2); T(qa, 1, 0, 2) quad_ld(qc[1], g2 + 32); T(qa, 2, 0, 2) quad_ld(qc[2], g2 + 64); T(qa, 3, 0, 2)
  TURN(4)
  quad_ld(qc[3], g2 + 96);
  constexpr int O3 = (R_A3 - R_A5) / 16;
  uint32_t pin = zero;
#define PACK(n) _Pragma("unroll") for (int z = n; z < n + 4; ++z) { yp[z] = pack2(acc[2 * z], acc[2 * z + 1]); pin &= yp[z]; }
  T(qb, 0, O3, 3) PACK(0) PACK(4) T(qb, 1, O3, 3) PACK(8) T(qb, 2, O3, 3) PACK(12) T(qb, 3, O3, 3)
  TURN(5)
  qc[0][0] |= pin;
  undef(f3);
  wg_fence();
#pragma unroll
  for (int kk = 0; kk < 4; ++kk) wg_rs32t(f3, qc[kk], mkdesc(reg + R_B, 128, 1040, 0) + 16 * kk, kk);
  wg_commit();
  TURN(6)
  asm volatile("cp.async.bulk.wait_group 0;" ::: "memory");
  uint32_t k1024 = lds16(tp + T_E - 2 * 639);
  lane |= here(zero);
  const int p = (lane + 9 * (w >> 1)) & 31;
  const uint32_t ya = reg + ((w >> 1) ? R_B : R_U) + p * 64 + (((2 * (w & 1)) ^ ((p >> 1) & 3)) * 16);
  const uint32_t up = p < lane ? 2048 : 0;
  const uint32_t fa = reg + R_A5 + (lane >> 3) * 512 + w * 128 + (lane & 7) * 16;
  const uint32_t fc = reg + R_A3 + uoff(64 * (lane >> 4) + 16 * w + 2 * (lane & 7) + 1 - ((lane >> 3) & 1));
  wg_wait<0>();
  GATE(2)
  PROF(11, a_far);
  bar_sync(NB_WG + k4, 128);
#pragma unroll
  for (int z = 0; z < 4; ++z) {
    const uint32_t* a = yp + 8 * (z >> 1) + (z & 1);
    stsm4t((ya + (up ^ ((z >> 1) * 2048))) ^ ((z & 1) * 16), a[0], a[2], a[4], a[6]);
  }
  stsm4(fa, pack2(f1[0], f1[1]), pack2(f1[4], f1[5]), pack2(f1[8] + f1[2], f1[9] + f1[3]), pack2(f1[12] + f1[6], f1[13] + f1[7]));
  stsm2(fa + 2048, pack2(f1[16] + f1[10], f1[17] + f1[11]), pack2(f1[20] + f1[14], f1[21] + f1[15]));
  stsm4(fc, pack2(f3[0], f3[1]), pack2(f3[4], f3[5]), pack2(f3[8] + f3[2], f3[9] + f3[3]), pack2(f3[12] + f3[6], f3[13] + f3[7]));
  bar_sync(NB_WG + k4, 128);
  PROF(12, a_sts);
  {
    const int o = 32 * v + lane;
    const uint32_t a = reg + uoff(o), b = reg + R_A5 + o * 16;
    uint4 y[2];
    y[0] = hadd8(lds4(a + R_U), hadd8(lds4(o >= 36 ? a + R_B : reg), lds4(v >= 2 ? b - 1024 : reg)));
    uint4 h = lds4(a + R_A3);
    k1024 = prmt(k1024, k1024, 0x1010);
    h = make_uint4(hfma2(pv[0], k1024, h.x), hfma2(pv[1], k1024, h.y), hfma2(pv[2], k1024, h.z), hfma2(pv[3], k1024, h.w));
    y[1] = hadd8(lds4(a + R_U + 2048), hadd8(lds4(a + R_B + 2048), hadd8(lds4(b + 1024), h)));
    const int e0 = (o >> 3) * 8192 + (128 * k4 + c) * 16 + (((o & 4) + ((o >> 1) & 1)) ^ (c & 7)) * 2 + (o & 1);
    ANN(2, y[0].x & y[1].x & zero)
    const uint32_t me = (e0 & 3) == ((c >> 1) & 3), m0 = me & ~c, m1 = me & c, tag = 1 - layer;
#pragma unroll
    for (int z = 0; z < 2; ++z) {
      const uint4 r = hadd8(x[z], y[z]);
      str2((uint2*)P.S->XF + e0 + z * 131072, tagged(prmt(r.x, r.y, 0x5410), m0, tag), tagged(prmt(r.z, r.w, 0x5410), m1, tag));
      str2((uint2*)P.S->XF + (e0 ^ 4) + z * 131072, tagged(prmt(r.x, r.y, 0x7632), m0, tag), tagged(prmt(r.z, r.w, 0x7632), m1, tag));
    }
  }
  ANN(1, 0)
  GATE(3)
  PROF(13, a_out);
}

#define HPRI 0
#define XORD 1
DEV void x_load(const Params& P, int c, int q, int layer) {
#pragma unroll
  for (int z = 0; z < 2; ++z) {
    const int e = z ^ (XORD && q == 3 && !(c & 4));
    mbar_expect1(B_X + 16 * q + 8 * e, 16384);
    bulk(xstage(q, e), P.S->XF + ((2 * (c >> 3) + 1 - e) * 4096 + q * 1024), 16384, B_X + 16 * q + 8 * e);
  }
}

DEV void means(uint32_t (&m)[4], int row, int lane, int layer, uint32_t zero) {
  mbar_wait(B_CS, 0);
  mbar_wait(B_ST, layer);
  const uint32_t a = SM_MISC + row * 4 + (lane & 28), k = (lane & 3) ? 0u : ~0u;
  m[0] = lds1(a) & k; m[1] = lds1(a + 32) & k; m[2] = m[0] & zero; m[3] = m[1] & zero;
}

DEV void attn_phase(const Params& P, int c, int e, int w, int lane, int layer) {
  PW(4 * e + w)
  const int cg = c & 7, J = 2 * (c >> 3) + 1 - e;
  float acc[96];
  zerov(acc);
  uint32_t m[4] = {0, 0, 0, 0};
#pragma unroll 1
  for (int q = 0;; ++q) {
    const uint64_t da = mkdesc(xstage(q, e), 16, 1024, 1), db = mkdesc(SM_S0 + (q & 1) * 49152, 8192, 1024, 1);
    bool all = mbar_test(B_W + 16 * q, layer) && mbar_test(B_W + 16 * q + 8, layer);
    mbar_wait(B_X + 16 * q + 8 * e, layer);
    for (int it = 0;; ++it) {
      const uint32_t a = xstage(q, e) + w * 4096 + lane * 132;
      const uint32_t ok = (lds1(a) ^ layer) & (lds1(a ^ 32) ^ layer) & (lds1(a ^ 64) ^ layer) & (lds1(a ^ 96) ^ layer);
      if (!bar_any(NB_WG + e, 128, !(ok & 1))) break;
      EVENT(8 * layer + 2 * q + e);
      refetch(xstage(q, e), P.S->XF + (J * 4096 + q * 1024), 8192, e, w);
      spin_guard(it);
    }
    if (q == 0 && e && w == 0) {
      bar_sync(NB_H, 160);
      cnt_wait(P, 2 + 5 * layer, c, lane);
      x_load(P, c, 1, layer);
      PROF(27, m_xi);
    }
    if (q == 3 && e) means(m, 16 * w, lane, layer, P.zero);
    if (!all) { mbar_wait(B_W + 16 * q, layer); all = mbar_test(B_W + 16 * q + 8, layer); }
    bar_sync(e ? NB_Q : q ? NB_T : NB_T + 4, 256);
    PROF(14 + q, m_q);
    wg_fence();
#pragma unroll
    for (int k = 0; k < 8; ++k) {
      if (k == 4) { if (!all) mbar_wait(B_W + 16 * q + 8, layer); wg_fence(); }
      wg_ss192(acc, da + k * 128, db + (k >> 2) * 1536 + (k & 3) * 128, 1);
    }
    wg_commit();
    if (q == 3) break;
    bar_arrive(e ? NB_T : NB_Q, 256);
    wg_wait<0>();
    mbar_arrive1(B_F + 8 * q);
  }
  const uint32_t ra = SM_STAT + 256 + (32 - 32 * e + 8 * w) * 16;
  float r0, r1;
  {
    if (!e) means(m, 64 + 16 * w, lane, layer, P.zero);
    PROF(28, m_sub);
    wg_fence();
    wg_rs192t(acc, m, mkdesc(SM_CS, 0, 32, 0));
    wg_commit();
    bar_arrive_if(NB_Q, 256, !e);
    r1 = lds1f(ra + 64 + (lane >> 3) * 16 + (lane & 4)); r0 = lds1f(ra + (lane >> 3) * 16 + (lane & 4));
    mbar_wait(B_F + 16, layer);
    wg_wait<0>();
    mbar_arrive1(B_F + 24);
  }
  PROF(18, m_qkv);
  lane = opq(lane);
  const int g = lane >> 2, t = lane & 3;
  uint32_t Q[4][4], K[4][3][2], V[4][3][2];
  const int pos = 2 - 2 * e + (w >> 1);
  uint4 k0, k1, k2;
  {
    uint32_t pin = P.zero;
#pragma unroll
    for (int z = 0; z < 8; ++z) {
      K[z >> 1][2][z & 1] = pack2(acc[34 + 4 * z], acc[35 + 4 * z]);
      V[z >> 1][2][z & 1] = pack2(acc[66 + 4 * z], acc[67 + 4 * z]);
      K[z >> 1][1][z & 1] = pack2(acc[32 + 4 * z], acc[33 + 4 * z]);
      V[z >> 1][1][z & 1] = pack2(acc[64 + 4 * z], acc[65 + 4 * z]);
      pin &= K[z >> 1][1][z & 1] & V[z >> 1][1][z & 1];
    }
    if (pos == 3) {
      const uint32_t rk = pack2(r1, r1) | pin;
      uint4* h = P.S->H + ((c + 8) * 256 + (w & 1) * 128 + lane);
#pragma unroll
      for (int z = 0; z < 4; ++z) str4(h + z * 32, nz(hmul2(K[z][2][0], rk)), hmul2(K[z][2][1], rk), hmul2(V[z][2][0], rk), hmul2(V[z][2][1], rk));
      bar_arrive(NB_RL, 128 + 64 * HPRI);
    }
    if (HPRI) bar_sync_if(NB_RL, 192, pos == 2);
#pragma unroll
    for (int z = 0; z < 8; ++z) {
      V[z >> 1][2][z & 1] = movm(V[z >> 1][2][z & 1]);
    }
    const uint32_t kv = kvslot(cg, 2 * pos + (w & 1)) + lane * 16;
    if (pos < 3) {
#pragma unroll
      for (int z = 0; z < 4; ++z) sts4(kv + 4096 + z * 512, K[z][2][0], K[z][2][1], V[z][2][0], V[z][2][1]);
      bar_arrive(NB_H + pos + 1, 128);
    }
    k0 = lds4(ra - 192 + 16 * t); k1 = lds4(ra + 16 * t); k2 = lds4(ra + 64 + 16 * t);
    PROF(19, m_kv);
#pragma unroll
    for (int z = 0; z < 8; ++z) {
      V[z >> 1][1][z & 1] = movm(V[z >> 1][1][z & 1]);
      Q[z >> 1][2 * (z & 1)] = pack2(acc[4 * z], acc[4 * z + 1]);
      Q[z >> 1][2 * (z & 1) + 1] = pack2(acc[4 * z + 2], acc[4 * z + 3]);
    }
    mbar_wait(B_F + 24, layer);
    bar_sync(NB_H + pos, 128);
#pragma unroll
    for (int z = 0; z < 4; ++z) {
      const uint4 hv = lds4(kv + z * 512);
      K[z][0][0] = hv.x; K[z][0][1] = hv.y; V[z][0][0] = hv.z; V[z][0][1] = hv.w;
    }
  }
  mbar_arrive1(B_H);
  PROF(20, m_halo);
  const uint32_t ob = e ? SM_S1 : SM_XA;
  {
    const bool p0 = 2 * t > g, p1 = 2 * t + 1 > g, first = c < 8 && pos == 0;
    const uint32_t M = (p0 ? 0xFFFFu : 0u) | (p1 ? 0xFFFF0000u : 0u);
    const float sc0 = r0 * (0.25f * 1.4426950408889634f), sc1 = r1 * (0.25f * 1.4426950408889634f);
    const float sk[4] = {__uint_as_float(p0 ? k0.x : k1.x) * sc0, __uint_as_float(p1 ? k0.y : k1.y) * sc0,
                         __uint_as_float(p0 ? k1.x : k2.x) * sc1, __uint_as_float(p1 ? k1.y : k2.y) * sc1};
    const uint32_t rm[4] = {k0.z & M, k1.z & ~M, k1.z & M, k2.z & ~M}, s0 = k0.w | P.zero, s1 = k1.w | P.zero;
    const int oo = cg * 512 + (2 * (w & 2) + (w & 1)) * 64 + (lane ^ (g >> 1));
    uint4* O = P.S->O + (J * 4096 + oo);
#pragma unroll
    for (int h2 = 0; h2 < 2; ++h2) {
      uint32_t A[2], B[2], mx[2];
#pragma unroll
      for (int z = 0; z < 2; ++z) {
        const int h = 2 * h2 + z;
        float S[3][4];
#pragma unroll
        for (int n = 0; n < 3; ++n) mma16z(S[n], Q[h][0], Q[h][1], Q[h][2], Q[h][3], K[h][n][0], K[h][n][1]);
        if (first) { S[0][0] = __uint_as_float(0xFF800000u); S[0][1] = S[0][0]; }
        A[z] = pack2((p0 ? S[0][0] : S[1][0]) * sk[0], (p0 ? S[1][2] : S[2][2]) * sk[2]);
        B[z] = pack2((p1 ? S[0][1] : S[1][1]) * sk[1], (p1 ? S[1][3] : S[2][3]) * sk[3]);
      }
#pragma unroll
      for (int z = 0; z < 2; ++z) mx[z] = hmax2(A[z], B[z]);
#pragma unroll
      for (int z = 0; z < 2; ++z) mx[z] = hmax2(mx[z], __shfl_xor_sync(0xffffffffu, mx[z], 1));
#pragma unroll
      for (int z = 0; z < 2; ++z) mx[z] = hmax2(mx[z], __shfl_xor_sync(0xffffffffu, mx[z], 2));
      float Oa[2][3][4];
#pragma unroll
      for (int z = 0; z < 2; ++z) {
        const int h = 2 * h2 + z;
        const uint32_t a = hsub2(A[z], mx[z]), b = hsub2(B[z], mx[z]);
        const uint32_t w0 = pack2(ex2(bflo(a)), ex2(bflo(b))), w1 = pack2(ex2(bfhi(a)), ex2(bfhi(b)));
        const uint32_t u0 = hmul2(w0, rm[0]), u1 = hmul2(w0, rm[1]), u2 = hmul2(w1, rm[2]), u3 = hmul2(w1, rm[3]);
        const uint32_t z0 = w0 & P.zero, z1 = w1 & P.zero;
        mma16z(Oa[z][2], u0, z0, u1, u2, s0, s1);
#pragma unroll
        for (int d = 0; d < 2; ++d) mma16z(Oa[z][d], u0, z0, u1, u2, V[h][0][d], V[h][1][d]);
        mma8(Oa[z][2], z1, u3, k2.w);
#pragma unroll
        for (int d = 0; d < 2; ++d) mma8(Oa[z][d], z1, u3, V[h][2][d]);
      }
#pragma unroll
      for (int r = 0; r < 4; r += 2) {
        const float i0 = rcp(Oa[0][2][r]), i1 = rcp(Oa[1][2][r]);
        const uint32_t o0 = pack2(Oa[0][0][r] * i0, Oa[0][0][r + 1] * i0), o1 = pack2(Oa[0][1][r] * i0, Oa[0][1][r + 1] * i0);
        const uint32_t o2 = pack2(Oa[1][0][r] * i1, Oa[1][0][r + 1] * i1), o3 = pack2(Oa[1][1][r] * i1, Oa[1][1][r + 1] * i1);
        str4(O + h2 * 32 + r * 64, o0, o1, o2, o3);
        sts4(ob + oo * 16 + h2 * 512 + r * 1024, o0, o1, o2, o3);
      }
    }
  }
  bar_sync(NB_WG + e, 128);
  if (w == 0) flag_set1(P.S->F + (J * 32 + 4 * cg));
  fence_async_smem();
  PROF(21, m_att);
  uint32_t res[8][2];
  mbar_wait(B_RES, layer);
  {
    const uint32_t a = SM_RES + e * 8192 + (lane >> 4) * 1024 + (lane & 7) * 128 + (((2 * (w & 2) + ((lane >> 2) & 2) + (w & 1)) ^ (lane & 7)) * 16);
#pragma unroll
    for (int j = 0; j < 8; j += 2) ldsm4t(res[j][0], res[j][1], res[j + 1][0], res[j + 1][1], a + j * 1024);
  }
  PROF(26, m_res);
  float ac[32];
  bar_sync(NB_WG + e, 128);
#pragma unroll 1
  for (int it = 0;; ++it) {
    zerov(ac);
#pragma unroll 1
    for (int n = 0; n < 8; ++n) {
      const int s = n == 0 ? cg : n - (n <= cg);
      mbar_wait(n ? B_O + 64 * e + 8 * s : B_WO, layer);
      if (n == 1) PROF(22, m_o1);
      if (n == 7) PROF(23, m_o7);
      const uint64_t da = mkdesc(ob + s * 8192, 16, 1024, 2), db = mkdesc(SM_R + s * 8192, 16, 1024, 1);
      wg_fence();
#pragma unroll
      for (int k = 0; k < 4; ++k) wg_ss64(ac, da + (k >> 1) * 32 + (k & 1) * 2, db + k * 128, 1);
      wg_commit();
    }
    wg_wait<0>();
    if (!bar_any(NB_WG + e, 128, ac[0] != ac[0] || ac[2] != ac[2]) || it == 16) break;
    EVENT(24 + 2 * layer + e);
    refetch(ob, P.S->O + J * 4096, 32768, e, w);
  }
  PROF(24, m_wo);
#pragma unroll
  for (int j = 0; j < 8; ++j) {
    res[j][0] = hadd2(res[j][0], pack2(ac[4 * j], ac[4 * j + 1]));
    res[j][1] = hadd2(res[j][1], pack2(ac[4 * j + 2], ac[4 * j + 3]));
  }
  if (layer == 0) {
    const float4 s = gram(res, g);
    if (t == (g >> 1))
      str4(&P.S->PS[((4 * J + w) * 8 + cg) * 8 + g], nz(__float_as_uint(s.x)), __float_as_uint(s.y), __float_as_uint(s.z), __float_as_uint(s.w));
    __syncwarp();
    xg_store<true>(P.S->XG[1] + (64 * cg * 256 + 8 * J), res, ob, NB_WG + e, w, lane);
    __syncwarp();
    mbar_arrive1(B_ED + 8 * e);
  } else {
    const uint32_t stg = ob + w * 2048;
    const int row = (lane & 7) + 8 * ((lane >> 3) & 1);
#pragma unroll
    for (int j = 0; j < 8; j += 2)
      stsm4(stg + row * 128 + (((j + (lane >> 4)) ^ (row & 7)) * 16), res[j][0], res[j][1], res[j + 1][0], res[j + 1][1]);
    __syncwarp();
#pragma unroll
    for (int k = 0; k < 4; ++k) {
      const int r = 4 * k + (lane >> 3);
      const uint4 v = lds4(stg + r * 128 + (((lane & 7) ^ (r & 7)) * 16));
      stw4(P.out + ((64 * J + 16 * w + 2 * (lane >> 3)) * 512 + 64 * cg + 8 * (lane & 7)) + ((k & 1) * 8 + (k >> 1)) * 512, v.x, v.y, v.z, v.w);
    }
  }
  PROF(25, m_epi);
}

#define HDELAY 300
#define ODELAY 0
#define PDELAY 500
#define WOQ 2
#define H5 1
#define RESQ 3
#define SRDELAY 400
#define ZPACE 20

DEV void o_load(const Params& P, int c, int e, int lane, int layer) {
  PW(8 + e)
  const int J = 2 * (c >> 3) + 1 - e;
#pragma unroll 1
  for (int s = 0; s < 8; ++s) mbar_expect1(B_O + 64 * e + 8 * s, s == (c & 7) ? 0 : 8192);
  mbar_wait(B_H, layer);
  if (ODELAY) delay(ODELAY);
  PROF(26, a_go);
  poll(P.S->F + (J * 32 + (lane & 28)), 1);
  PROF(25, h_seen);
#pragma unroll 1
  for (int s = 0; s < 8; ++s)
    if (s != (c & 7)) bulk((e ? SM_S1 : SM_XA) + s * 8192, P.S->O + (J * 4096 + s * 512), 8192, B_O + 64 * e + 8 * s);
  PROF(28, a_o);
}

DEV void stats(const Params& P, int c, int w, int lane, int layer) {
  PW(12 + w)
  lane = opq(lane);
  const int r = (lane & 6) + ((lane >> 3) & 1), k = (2 * (c & 3) + (lane & 1)) ^ r, e = 1 - ((c >> 2) & 1);
  const uint32_t o = (32 * w + 8 * (lane >> 4) + r) * 128 + k * 16;
  const uint32_t mk = ((k & 1) == (r >> 2)) << (r & 3), tag = 1 - layer;
  float v[16];
#pragma unroll
  for (int z = 0; z < 16; ++z) v[z] = 0.f;
#pragma unroll 1
  for (int q = 0; q < 4; ++q) {
    mbar_wait(B_X + 16 * q + 8 * e, layer);
    PROF(19 + q, s_l);
    uint4 x, y;
    for (int it = 0;; ++it) {
      x = lds4v(xstage(q, e) + o); y = lds4v(xstage(q, e) + o + 2048);
      const uint32_t bad = (((x.x ^ tag) | (y.x ^ tag)) & mk) | (((x.y ^ tag) | (y.y ^ tag)) & (mk >> 1)) |
                           (((x.z ^ tag) | (y.z ^ tag)) & (mk >> 2)) | (((x.w ^ tag) | (y.w ^ tag)) & (mk >> 3));
      if (!__any_sync(0xffffffffu, bad & 1)) break;
      spin_guard(it);
    }
    mbar_arrive1(B_F + 8 * q);
    const uint32_t ws[8] = {x.x, x.y, x.z, x.w, y.x, y.y, y.z, y.w};
#pragma unroll
    for (int z = 0; z < 8; ++z) {
      const float lo = bflo(ws[z]), hi = bfhi(ws[z]);
      float* u = v + 4 * (z & 3);
      u[0] += lo; u[1] += lo * lo; u[2] += hi; u[3] += hi * hi;
    }
  }
  PROFD(14, s_part, __float_as_uint(v[0]));
  fold<8>(v, lane, 16); fold<4>(v, lane, 8); fold<2>(v, lane, 4); fold<1>(v, lane, 2);
  PROFD(16, s_fold, __float_as_uint(v[0]));
  if (w) {
    sts1(SM_MISC - 128 + w * 128 + lane * 4, __float_as_uint(v[0]));
    bar_arrive(NB_P, 128);
  } else {
    bar_sync(NB_P, 128);
    v[0] += lds1f(SM_MISC + lane * 4) + lds1f(SM_MISC + 128 + lane * 4) + lds1f(SM_MISC + 256 + lane * 4);
    float m;
    const float sd = ln_sd(v[0], __shfl_xor_sync(0xffffffffu, v[0], 2), m);
    if (!(lane & 2)) str1((uint32_t*)P.S->ST + (16 * c + 8 * (lane & 1) + (lane >> 2)), pack2(m, sd));
    sts4(SM_STAT + (lane & 15) * 16, 0x3F800000u, 0x3F800000u, 0x3F803F80u, 0x3F803F80u);
    fence_async_smem();
    PROF(17, s_pub);
    uint4 s;
    for (int it = 0;; ++it) {
      s = ldr4(P.S->ST + ((c >> 3) * 32 + lane));
      if (__all_sync(0xffffffffu, min4(s) != 0u)) break;
      spin_guard(it);
    }
    PROF(18, s_seen);
    const float r0 = rcp(bfhi(s.x)), r1 = rcp(bfhi(s.y)), r2 = rcp(bfhi(s.z)), r3 = rcp(bfhi(s.w));
    const uint32_t sg = 0x80008000u;
    sts4(SM_MISC + lane * 16, prmt(s.x, s.x, 0x1010) ^ sg, prmt(s.y, s.y, 0x1010) ^ sg, prmt(s.z, s.z, 0x1010) ^ sg, prmt(s.w, s.w, 0x1010) ^ sg);
    sts4(SM_STAT + 256 + lane * 32, __float_as_uint(r0), __float_as_uint(r1), pack2(r0, r1), prmt(s.x, s.y, 0x7632));
    sts4(SM_STAT + 272 + lane * 32, __float_as_uint(r2), __float_as_uint(r3), pack2(r2, r3), prmt(s.z, s.w, 0x7632));
    __syncwarp();
    mbar_arrive1(B_ST);
  }
  PROF(15, s_stat);
  if (w >= 2) {
    const uint4* h = P.S->H + (c * 256 + (w & 1) * 128 + lane);
    uint4 hv[4];
#pragma unroll
    for (int z = 0; z < 4; ++z) hv[z] = make_uint4(0, 0, 0, 0);
    bar_sync(NB_RL, 128 + 64 * HPRI);
    PROFD(26, s_hb, lds1v(SM_MISC));
    delay(HDELAY);
    for (int it = 0; c >= 8; ++it) {
#pragma unroll
      for (int z = 0; z < 4; ++z) hv[z] = ldr4(h + z * 32);
      if (__all_sync(0xffffffffu, min(min(hv[0].x, hv[1].x), min(hv[2].x, hv[3].x)) != 0u)) break;
      spin_guard(it);
    }
#pragma unroll
    for (int z = 0; z < 4; ++z) sts4(kvslot(c & 7, w & 1) + lane * 16 + z * 512, hv[z].x, hv[z].y, movm(hv[z].z), movm(hv[z].w));
    bar_arrive(NB_H, 128);
    mbar_arrive1_if(B_ST + 8, w == 3);
    PROF(25, s_halo);
  }
}

DEV void finalize(const Params& P, int c, int lane, int layer) {
  PW(12)
  float z[4];
  if (layer == 0) {
    bar_sync(NB_P, 256);
    z[0] = z[1] = z[2] = z[3] = 0.f;
#pragma unroll
    for (int k = 0; k < 2; ++k) { const float4 a = lds4f(SM_RES + 8192 + k * 512 + lane * 16); z[0] += a.x; z[1] += a.y; z[2] += a.z; z[3] += a.w; }
  } else {
    mbar_wait(B_ED + 8 - 2 * (c & 4), 0);
    const uint4* ps = &P.S->PS[c * 64 + lane];
    uint4 a, b;
    for (int it = 0;; ++it) {
      a = ldr4(ps); b = ldr4(ps + 32);
      if (__all_sync(0xffffffffu, min(a.x, b.x) != 0u)) break;
      spin_guard(it);
    }
    z[0] = __uint_as_float(a.x) + __uint_as_float(b.x); z[1] = __uint_as_float(a.y) + __uint_as_float(b.y);
    z[2] = __uint_as_float(a.z) + __uint_as_float(b.z); z[3] = __uint_as_float(a.w) + __uint_as_float(b.w);
  }
#pragma unroll
  for (int o = 8; o < 32; o <<= 1)
#pragma unroll
    for (int k = 0; k < 4; ++k) z[k] += __shfl_xor_sync(0xffffffffu, z[k], o);
  float m0, m1;
  const float r0 = rcp(ln_sd(z[0], z[1], m0)), r1 = rcp(ln_sd(z[2], z[3], m1));
  const uint32_t wr = nz(pack2(r0, r1)), wm = pack2(m0, m1);
  uint2* so = (uint2*)P.S->SR[layer] + ((lane >> 3) * 1024 + (lane & 2) * 256 + 4 * c + ((lane >> 1) & 2) + (lane & 1));
  str2(so, wr, wm); str2(so + 4096, wr, wm);
  if (!LATEF) bar_arrive_if(NB_Q, 448, !layer);
  PROF(23, s_sr);
}

DEV void announce(const Params& P, int c, int lane, int layer) {
  PW(13)
  if (layer) { mbar_wait(B_ED, 0); mbar_wait(B_ED + 8, 0); } else bar_sync(NB_H, 288);
  cnt_add(P, 5 * layer, c, lane);
  if (!LATEF) { bar_arrive_if(NB_Q, 448, !layer); fence_async_smem(); }
  PROF(24, s_own);
}

DEV void fetch(const Params& P, int c, int lane, int layer) {
  PW(13)
  mbar_expect1(B_E, 24576);
  cnt_wait(P, 5 * layer, c, lane);
#pragma unroll
  for (int k = 0; k < 4; ++k) bulk(SM_R + k * 16384 + R_B, P.S->XG[layer] + (128 * k + c) * 256, 4096, B_E);
  if (layer) delay(SRDELAY);
  bulk(SM_RES, P.S->SR[layer][c >> 4], 8192, B_E);
  if (!layer) { l2_prefetch(P.wqkv + c * 6144, 12288); l2_prefetch(P.wo + c * 2048, 4096); }
  PROF(25, s_all);
}

DEV void cs_part(const Params& P, int c, int w, int lane, int layer) {
  float cs[8];
#pragma unroll
  for (int k = 0; k < 8; ++k) cs[k] = 0.f;
  const int col = w * 512 + 64 * (c & 7) + 8 * (lane & 7);
#pragma unroll 1
  for (int r = 2 * layer; r < 2; ++r) {
    uint4 v[4];
#pragma unroll
    for (int k = 0; k < 4; ++k) v[k] = ldnc4(P.wqkv + ((32 * (c >> 3) + 16 * r + (lane >> 3)) * 1536 + col) + 4 * k * 1536);
#pragma unroll
    for (int k = 0; k < 4; ++k) {
      cs[0] += bflo(v[k].x); cs[1] += bfhi(v[k].x); cs[2] += bflo(v[k].y); cs[3] += bfhi(v[k].y);
      cs[4] += bflo(v[k].z); cs[5] += bfhi(v[k].z); cs[6] += bflo(v[k].w); cs[7] += bfhi(v[k].w);
    }
  }
  fold<4>(cs, lane, 16); fold<2>(cs, lane, 8);
  str2((float*)P.S->CS + ((c >> 3) * 1536 + col + 2 * (lane >> 3)), max(__float_as_uint(cs[0]), 1u - layer), __float_as_uint(cs[1]));
}

DEV void cs_sum(const Params& P, int c, int w, int lane) {
  float a, b;
  for (int it = 0;; ++it) {
    uint32_t m = ~0u;
    a = b = 0.f;
#pragma unroll
    for (int k = 0; k < 16; ++k) {
      const uint2 u = ldr2((const float*)P.S->CS + (w * 512 + 64 * (c & 7) + 2 * lane) + k * 1536);
      a += __uint_as_float(u.x); b += __uint_as_float(u.y); m = min(m, u.x);
    }
    if (__all_sync(0xffffffffu, m != 0u)) break;
    spin_guard(it);
  }
  const uint32_t hi = pack2(a, b), ad = SM_CS + w * 256 + (lane >> 2) * 32 + (lane & 3) * 4;
  sts1(ad, hi); sts1(ad + 16, pack2(a - bflo(hi), b - bfhi(hi)));
  fence_async_smem();
  __syncwarp();
  mbar_arrive1(B_CS);
}

DEV void x0_get(uint32_t (&x)[8][2], uint32_t a) {
  asm volatile("cp.async.wait_group 0;" ::: "memory");
#pragma unroll
  for (int z = 0; z < 4; ++z) {
    const uint4 v = lds4(a + z * 512);
    x[2 * (z & 2)][z & 1] = v.x; x[2 * (z & 2) + 1][z & 1] = v.y; x[2 * (z & 2) + 2][z & 1] = v.z; x[2 * (z & 2) + 3][z & 1] = v.w;
  }
}

DEV void par_load(const Params& P, int ch, int m, uint32_t (&pv)[8]) {
  const int mo = ch * 128 + m;
  pv[0] = ldnc16(P.Are + mo); pv[1] = ldnc16(P.Aim + mo); pv[2] = ldnc16(P.Bre + mo); pv[3] = ldnc16(P.Bim + mo);
  pv[4] = ldnc16(P.Cre + mo); pv[5] = ldnc16(P.Cim + mo); pv[6] = ldnc16(P.logdt + ch); pv[7] = ldnc16(P.dskip + ch);
}

__global__ void __launch_bounds__(NTHR, 1)
fused_kernel(const __grid_constant__ Params P, const __grid_constant__ CUtensorMap mapW,
             const __grid_constant__ CUtensorMap mapWo) {
  extern __shared__ __align__(1024) uint8_t smem_raw[];
  if (s2u(smem_raw) != SB) __trap();
  const int warp0 = __shfl_sync(0xffffffffu, threadIdx.x >> 5, 0), lane0 = threadIdx.x & 31;
  uint32_t smid; asm volatile("mov.u32 %0,%%smid;" : "=r"(smid));
  const int c = __shfl_sync(0xffffffffu, P.by_sm ? P.role[smid] : blockIdx.x, 0);
  if (c == 255) {
    if (threadIdx.x < NCOPY * NSUB)
#pragma unroll 1
      for (int it = 0; it < 256 && ldr1(P.S->C + 32 * threadIdx.x) < 128 / NSUB; ++it) __nanosleep(200);
    return;
  }
  const int cg = c & 7;
  PW(warp0)
  uint32_t dskip;
  {
    [[maybe_unused]] const int layer = 0;
    const int lane = lane0, g = lane >> 2, t = lane & 3, warp = warp0, k4 = warp >> 2, w = warp & 3;
    uint32_t pv[8];
    if (k4 < 2) par_load(P, 128 * k4 + c, 32 * w + lane, pv);
    else {
#pragma unroll
      for (int n = 0; n < 8; ++n) pv[n] = 0;
#pragma unroll
      for (int n = 0; n < 7; ++n) mbar_init1(SM_BAR + (n < 5 ? warp * 40 - 320 : 152 + warp * 16) + n * 8, n < 5 ? 1 : (CNT >> (4 * warp - 32)) & 15);
    }
    __syncthreads();
    const uint16_t* r = P.x0 + ((k4 < 2 ? 8192 * c + 64 * warp : (128 * (c >> 3) + 16 * (warp - 8)) * 512 + 64 * cg) + 1024 * g + 8 * t);
    const uint32_t xa = SM_R + k4 * 16384 + w * 2048 + lane * 16;
#pragma unroll
    for (int z = 0; z < 4; ++z) cp16(xa + z * 512, r + (z & 1) * 512 + (z & 2) * 16);
    asm volatile("cp.async.commit_group;" ::: "memory");
    sts4(SM_TAP + k4 * TAP_SZ + (32 * w + lane) * 16, 0, 0, 0, 0);
    sts4z_if(SM_TAP + k4 * TAP_SZ + 2048 + (32 * w + lane) * 16, w < 3);
    uint32_t x[8][2];
    if (k4 >= 2) {
      if (threadIdx.x == 448) {
        asm volatile("prefetch.tensormap [%0];" :: "l"(&mapW) : "memory");
        asm volatile("prefetch.tensormap [%0];" :: "l"(&mapWo) : "memory");
      }
      __syncwarp();
      if (PDELAY) delay(PDELAY);
      par_load(P, 128 * k4 + c, 32 * w + lane, pv);
      x0_get(x, xa);
      PROF(27, a_ld);
      xg_store<false>(P.S->XG[0] + (64 * cg * 256 + 16 * (c >> 3) + 8 * (k4 - 2)), x, SM_R + k4 * 16384 + 8192, NB_WG + k4, w, lane);
      bar_arrive(NB_H, 288);
      bar_sync(NB_Q, 448 + 64 * LATEF);
    }
    tables(pv, k4, w, lane);
    if (k4 < 2) {
      x0_get(x, xa);
      const float4 s = gram(x, g);
      if (t == (g >> 1)) sts4f(SM_RES + 8192 + (warp * 8 + g) * 16, s.x, s.y, s.z, s.w);
      __syncwarp();
      bar_arrive_if(NB_P, 256, warp != 7);
    }
    dskip = pv[7];
    PROF(1, a_x0);
  }
#pragma unroll 1
  for (int layer = 0; layer < 2; ++layer) {
    int lane = lane_here(P.zero);
    const int warp = warp0 | (layer & P.zero), k4 = warp >> 2, w = warp & 3;
    if (warp == (layer ? 12 : 7)) finalize(P, c, lane, layer);
    if (warp == (layer ? 13 : 6)) { announce(P, c, lane, layer); if (!LATEF) fetch(P, c, lane, layer); }
    if (layer == 0) {
      taps(dskip, k4, w, lane);
    }
    if (LATEF && warp == (layer ? 13 : 6)) fetch(P, c, lane, layer);
    conv(P, &mapW, c, k4, w, layer);
    lane = lane_here(P.zero);
    if (k4 < 2) {
      bar_arrive_if(NB_H, 160, !k4);
      if (warp == 0) {
        mbar_wait(B_K, 0);
        cnt_wait(P, 1 + 5 * layer, c, lane);
        x_load(P, c, 0, layer);
        PROF(27, m_xi);
      } else if (k4 == 0) cs_part(P, c, w - 1, lane, layer);
      attn_phase(P, c, k4, w, lane, layer);
    } else {
      bar_arrive_if(NB_RL, 256, warp >= 10);
      if (k4 == 3) {
        stats(P, c, w, lane, layer);
      } else if (w < 2) {
        bar_sync_if(NB_RL, 256, w);
        cnt_wait(P, 3 + 5 * layer + w, c, lane);
        bar_sync_if(NB_RL, 256, !w);
        if (w) mbar_wait(B_F, layer);
        x_load(P, c, 2 + w, layer);
        if (H5 && w) w_load(&mapW, cg, 5);
        PROF(14, h_xi);
        if (w == 1) str4(&P.S->SR[layer][lane >> 2][4 * c + (lane & 3)], 0, 0, 0, 0);
      } else if (w == 2) {
        mbar_expect1(B_WO, 65536);
        mbar_expect1(B_RES, 16384);
#pragma unroll 1
        for (int q = 0; q < 4; ++q) {
          mbar_wait(B_F + 8 * q, layer);
          if (q < 2) w_load(&mapW, cg, 4 + 2 * q);
          if (q == 1 || (q == 0 && !H5)) w_load(&mapW, cg, 5 + 2 * q);
          if (WOQ == 0 && ((q + 1) & 2)) tma5(SM_R + (q & 2) * 16384, &mapWo, 64 * cg, 4 * (q & 2), B_WO);
          if (WOQ && q == 2) {
            if (WOQ >= 2) mbar_wait(B_ST, layer);
            tma5(SM_R, &mapWo, 64 * cg, 0, B_WO);
            if (WOQ < 3) tma5(SM_R + 32768, &mapWo, 64 * cg, 8, B_WO);
          }
          if (WOQ == 3 && q == 2) { mbar_wait(B_ST + 8, layer); tma5(SM_R + 32768, &mapWo, 64 * cg, 8, B_WO); }
          if (q == max(cg >> 1, RESQ)) {
#pragma unroll
            for (int e = 0; e < 2; ++e) bulk(SM_RES + e * 8192, P.S->XF + ((2 * (c >> 3) + 1 - e) * 4096 + cg * 512), 8192, B_RES);
          }
          PROF(15 + q, h_w);
        }
      }
      if (k4 == 2 && w != 2) {
        if (layer == 0) cs_sum(P, c, w - (w >> 1), lane);
        if (w == 3) {
          uint4* xz = P.S->XG[layer] + (c * 256 + lane);
          mbar_wait(B_F, layer);
#pragma unroll 1
          for (int k = 0; k < 32; ++k) {
            str4(xz + ((k >> 3) * 32768 + (k & 7) * 32), 0, 0, 0, 0);
            if (ZPACE) __nanosleep(ZPACE);
          }
          PROF(19, h_z);
        }
      }
      if (warp < 10) o_load(P, c, w, lane, layer);
    }
    asm volatile("mov.b32 %0,0;" : "=r"(dskip));
  }
}

typedef CUresult (*EncodeFn)(CUtensorMap*, CUtensorMapDataType, cuuint32_t, void*, const cuuint64_t*, const cuuint64_t*,
                             const cuuint32_t*, const cuuint32_t*, CUtensorMapInterleave, CUtensorMapSwizzle,
                             CUtensorMapL2promotion, CUtensorMapFloatOOBfill);

static int place_roles(uint8_t* role) {
  int dev = 0, nsm = 0;
  cudaGetDevice(&dev);
  cudaDeviceGetAttribute(&nsm, cudaDevAttrMultiProcessorCount, dev);
  if (nsm < 128 || nsm > 144 || (nsm & 1)) return 0;
  cudaFuncSetAttribute(fused_kernel, cudaFuncAttributeNonPortableClusterSizeAllowed, 1);
  int occ[9] = {0};
  for (int k = 2; k <= 8; ++k) {
    cudaLaunchConfig_t cfg = {};
    cudaLaunchAttribute at[1];
    at[0].id = cudaLaunchAttributeClusterDimension;
    at[0].val.clusterDim.x = 2 * k; at[0].val.clusterDim.y = 1; at[0].val.clusterDim.z = 1;
    cfg.gridDim = dim3(2 * k); cfg.blockDim = dim3(NTHR); cfg.dynamicSmemBytes = SM_TOTAL; cfg.attrs = at; cfg.numAttrs = 1;
    if (cudaOccupancyMaxActiveClusters(&occ[k], fused_kernel, &cfg) != cudaSuccess) { cudaGetLastError(); occ[k] = 0; }
  }
  int n[10];
  n[7] = occ[8]; n[6] = occ[7]; n[5] = occ[6] - 0; n[4] = occ[5];
  n[3] = occ[4] - n[7]; n[1] = occ[2] - n[3] - n[5] - n[7]; n[0] = n[2] = n[1];
  n[8] = occ[3] - n[2] - n[5];
  const int ntpc = nsm / 2;
  int sum = 0;
  bool ok = n[0] > 0 && n[0] <= 8;
  for (int r = 0; r < 9; ++r) { ok = ok && n[r] >= 0 && (r == 0 || n[r] <= n[r - 1]); sum += n[r]; }
  if (!ok || sum > ntpc) { for (int r = 0; r < 9; ++r) n[r] = r < 8 ? 8 : 0; sum = 64; }
  int tp[8][9], cnt[8] = {0}, pool[72], np = 0, id = 0;
  for (int r = 0; r < 9; ++r)
    for (int g = n[0] - n[r]; g < n[0]; ++g) tp[g][cnt[g]++] = id++;
  for (; id < ntpc; ++id) pool[np++] = id;
  int order[72], no = 0;
  for (int g = 0; g < n[0]; ++g) {
    const int full = cnt[g] / 4 * 4;
    for (int k = 0; k < cnt[g]; ++k) { if (k < full) order[no++] = tp[g][k]; else pool[np++] = tp[g][k]; }
  }
  for (int k = 0; k < np; ++k) order[no++] = pool[k];
  for (int k = 0; k < 144; ++k) role[k] = 255;
  for (int k = 0; k < 64; ++k) { role[2 * order[k]] = 2 * k; role[2 * order[k] + 1] = 2 * k + 1; }
  return nsm;
}

extern "C" void kernel_launch(void* const* d_in, const int* in_sizes, int n_in, void* d_out, int out_size) {
  (void)in_sizes; (void)n_in; (void)out_size;
  static EncodeFn enc = nullptr;
  static uint8_t role[144];
  static int nsm = 0;
  static void* scratch = nullptr;
  if (!enc) {
    void* fn = nullptr;
    cudaDriverEntryPointQueryResult qr;
    cudaGetDriverEntryPoint("cuTensorMapEncodeTiled", &fn, cudaEnableDefault, &qr);
    enc = (EncodeFn)fn;
    cudaFuncSetAttribute(fused_kernel, cudaFuncAttributeMaxDynamicSharedMemorySize, SM_TOTAL);
    nsm = place_roles(role);
    cudaGetSymbolAddress(&scratch, g_S);
  }
  CUtensorMap mW, mWo;
  {
    cuuint64_t dim[3] = {512, 512, 3}, str[2] = {3072, 1024};
    cuuint32_t box[3] = {64, 64, 3}, es[3] = {1, 1, 1};
    enc(&mW, CU_TENSOR_MAP_DATA_TYPE_BFLOAT16, 3, d_in[10], dim, str, box, es, CU_TENSOR_MAP_INTERLEAVE_NONE,
        CU_TENSOR_MAP_SWIZZLE_128B, CU_TENSOR_MAP_L2_PROMOTION_NONE, CU_TENSOR_MAP_FLOAT_OOB_FILL_NONE);
  }
  {
    cuuint64_t dim[5] = {512, 2, 4, 4, 16}, str[4] = {1024, 8192, 2048, 32768};
    cuuint32_t box[5] = {64, 2, 4, 4, 8}, es[5] = {1, 1, 1, 1, 1};
    enc(&mWo, CU_TENSOR_MAP_DATA_TYPE_BFLOAT16, 5, d_in[11], dim, str, box, es, CU_TENSOR_MAP_INTERLEAVE_NONE,
        CU_TENSOR_MAP_SWIZZLE_128B, CU_TENSOR_MAP_L2_PROMOTION_NONE, CU_TENSOR_MAP_FLOAT_OOB_FILL_NONE);
  }
  Params P;
  P.x0 = (const uint16_t*)d_in[0]; P.Are = (const uint16_t*)d_in[1]; P.Aim = (const uint16_t*)d_in[2];
  P.Bre = (const uint16_t*)d_in[3]; P.Bim = (const uint16_t*)d_in[4]; P.Cre = (const uint16_t*)d_in[5];
  P.Cim = (const uint16_t*)d_in[6]; P.logdt = (const uint16_t*)d_in[7]; P.dskip = (const uint16_t*)d_in[8];
  P.wqkv = (const uint16_t*)d_in[10]; P.wo = (const uint16_t*)d_in[11]; P.out = (uint16_t*)d_out;
  for (int k = 0; k < 144; ++k) P.role[k] = role[k];
  P.by_sm = nsm > 0;
  P.zero = 0;
  P.S = (Scratch*)scratch;
  fused_kernel<<<nsm > 0 ? nsm : 128, NTHR, SM_TOTAL, cudaStreamPerThread>>>(P, mW, mWo);
}
```

```cpp
#include <cuda_runtime.h>
#include <cuda_bf16.h>
#include <cuda.h>
#include <stdint.h>

#define DEV __device__ __forceinline__

#define NCOPY 4
#define NSUB 1
#define EA 0x2121
constexpr int NTHR = 512;
constexpr int SPIN_LIMIT = 1 << 22;

constexpr uint32_t SB = 1024;
constexpr uint32_t SM_XA   = SB;
constexpr uint32_t SM_S0   = SM_XA + 16384;
constexpr uint32_t SM_S1   = SM_S0 + 49152;
constexpr uint32_t SM_XB   = SM_S1 + 49152;
constexpr uint32_t SM_R    = SM_XB + 16384;
constexpr uint32_t SM_RES  = SM_R + 65536;
constexpr uint32_t SM_TAP  = SM_RES + 16384;
constexpr int TAP_SZ = 3584;
constexpr uint32_t SM_CS   = SM_TAP + 4 * TAP_SZ;
constexpr uint32_t SM_STAT = SM_CS + 768;
constexpr uint32_t SM_MISC = SM_STAT + 1280;
constexpr uint32_t SM_BAR  = SM_MISC + 512;
constexpr int SM_TOTAL = SM_BAR + 448 - SB;
constexpr int R_U = 512, R_A5 = 5120, R_A3 = 8704, R_B = 11776;
constexpr int T_E = 1536, T_O = T_E + 1602, T_C = 3714;
constexpr uint32_t B_W = SM_BAR, B_X = SM_BAR + 64, B_O = SM_BAR + 128, B_WO = SM_BAR + 256, B_RES = SM_BAR + 264;
constexpr uint32_t B_ST = SM_BAR + 272, B_R = SM_BAR + 288, B_E = SM_BAR + 304;
constexpr uint32_t B_F = SM_BAR + 320, B_G = SM_BAR + 352, B_K = SM_BAR + 376, B_ED = SM_BAR + 384, B_CS = SM_BAR + 400;
constexpr uint32_t CNT = 0x183444CC;
constexpr int NB_WG = 1, NB_T = 5, NB_Q = 10, NB_H = 11, NB_P = 14, NB_RL = 15;

struct Scratch {
  uint4    XG[2][512 * 256];
  uint4    XF[32 * 4096];
  uint4    O[32 * 8 * 512];
  uint32_t F[32 * 32];
  uint4    H[17 * 8 * 256];
  uint4    SR[2][8][512];
  uint4    ST[32 * 16];
  uint4    PS[128 * 64];
  float4   CS[16 * 1536 / 4];
  uint32_t C[10 * 32 * 32];
};
__device__ __align__(1024) Scratch g_S;

struct Params {
  int by_sm;
  uint32_t zero;
  Scratch* S;
  const uint16_t *x0, *Are, *Aim, *Bre, *Bim, *Cre, *Cim, *logdt, *dskip, *wqkv, *wo;
  uint16_t* out;
  uint8_t role[144];
};
#define EVENT(n) do {} while (0)
#define PROFD(slot, name, v) do {} while (0)
#define PROF(slot, name) do {} while (0)
#define PW(x)

DEV uint32_t s2u(const void* p) { return (uint32_t)__cvta_generic_to_shared(p); }
template <class T> DEV T opq(T x) { asm volatile("" : "+r"(x)); return x; }
DEV uint32_t pack2(float lo, float hi) { uint32_t d; asm("cvt.rn.bf16x2.f32 %0,%1,%2;" : "=r"(d) : "f"(hi), "f"(lo)); return d; }
DEV float bflo(uint32_t v) { return __uint_as_float(v << 16); }
DEV float bfhi(uint32_t v) { return __uint_as_float(v & 0xFFFF0000u); }
DEV float bfr(float x) { return bflo(pack2(x, 0.f)); }
DEV uint32_t hadd2(uint32_t a, uint32_t b) { uint32_t d; asm("add.rn.bf16x2 %0,%1,%2;" : "=r"(d) : "r"(a), "r"(b)); return d; }
DEV uint32_t hsub2(uint32_t a, uint32_t b) { uint32_t d; asm("sub.rn.bf16x2 %0,%1,%2;" : "=r"(d) : "r"(a), "r"(b)); return d; }
DEV uint32_t hmul2(uint32_t a, uint32_t b) { uint32_t d; asm("mul.rn.bf16x2 %0,%1,%2;" : "=r"(d) : "r"(a), "r"(b)); return d; }
DEV uint32_t hfma2(uint32_t a, uint32_t b, uint32_t c) { uint32_t d; asm("fma.rn.bf16x2 %0,%1,%2,%3;" : "=r"(d) : "r"(a), "r"(b), "r"(c)); return d; }
DEV uint32_t hmax2(uint32_t a, uint32_t b) { uint32_t d; asm("max.bf16x2 %0,%1,%2;" : "=r"(d) : "r"(a), "r"(b)); return d; }
DEV uint32_t prmt(uint32_t a, uint32_t b, uint32_t s) { uint32_t d; asm("prmt.b32 %0,%1,%2,%3;" : "=r"(d) : "r"(a), "r"(b), "r"(s)); return d; }
DEV uint32_t nz(uint32_t v) { uint32_t d; asm("max.u32 %0,%1,1;" : "=r"(d) : "r"(v)); return d; }
DEV uint32_t tagged(uint32_t v, uint32_t m, uint32_t tag) { return (v & ~m) | (tag & m); }
DEV uint4 hadd8(const uint4& a, const uint4& b) { return make_uint4(hadd2(a.x, b.x), hadd2(a.y, b.y), hadd2(a.z, b.z), hadd2(a.w, b.w)); }
DEV uint32_t min4(const uint4& v) { return min(min(v.x, v.y), min(v.z, v.w)); }
DEV float rcp(float x) { float y; asm("rcp.approx.ftz.f32 %0,%1;" : "=f"(y) : "f"(x)); return y; }
DEV float sqrt_(float x) { float y; asm("sqrt.approx.ftz.f32 %0,%1;" : "=f"(y) : "f"(x)); return y; }
DEV float ex2(float x) { float y; asm("ex2.approx.ftz.f32 %0,%1;" : "=f"(y) : "f"(x)); return y; }

DEV uint4 ldr4(const void* p) { uint4 v; asm volatile("ld.relaxed.gpu.global.v4.u32 {%0,%1,%2,%3},[%4];" : "=r"(v.x), "=r"(v.y), "=r"(v.z), "=r"(v.w) : "l"(p) : "memory"); return v; }
DEV void ldr4_if(uint4& v, const void* p, bool c) {
  asm volatile("{.reg .pred q; setp.ne.u32 q,%5,0; @q ld.relaxed.gpu.global.v4.u32 {%0,%1,%2,%3},[%4];}"
    : "+r"(v.x), "+r"(v.y), "+r"(v.z), "+r"(v.w) : "l"(p), "r"((uint32_t)c) : "memory");
}
DEV uint2 ldr2(const void* p) { uint2 v; asm volatile("ld.relaxed.gpu.global.v2.u32 {%0,%1},[%2];" : "=r"(v.x), "=r"(v.y) : "l"(p) : "memory"); return v; }
DEV uint32_t ldr1(const void* p) { uint32_t v; asm volatile("ld.relaxed.gpu.global.u32 %0,[%1];" : "=r"(v) : "l"(p) : "memory"); return v; }
DEV void str4(void* p, uint32_t a, uint32_t b, uint32_t c, uint32_t d) { asm volatile("st.relaxed.gpu.global.v4.u32 [%0],{%1,%2,%3,%4};" :: "l"(p), "r"(a), "r"(b), "r"(c), "r"(d) : "memory"); }
DEV void str4_if(void* p, uint32_t a, uint32_t b, uint32_t c, uint32_t d, bool q) {
  asm volatile("{.reg .pred q; setp.ne.u32 q,%5,0; @q st.relaxed.gpu.global.v4.u32 [%0],{%1,%2,%3,%4};}" :: "l"(p), "r"(a), "r"(b), "r"(c), "r"(d), "r"((uint32_t)q) : "memory");
}
DEV void str2(void* p, uint32_t a, uint32_t b) { asm volatile("st.relaxed.gpu.global.v2.u32 [%0],{%1,%2};" :: "l"(p), "r"(a), "r"(b) : "memory"); }
DEV void str1(void* p, uint32_t a) { asm volatile("st.relaxed.gpu.global.u32 [%0],%1;" :: "l"(p), "r"(a) : "memory"); }
DEV void stw4(void* p, uint32_t a, uint32_t b, uint32_t c, uint32_t d) { asm volatile("st.global.v4.u32 [%0],{%1,%2,%3,%4};" :: "l"(p), "r"(a), "r"(b), "r"(c), "r"(d) : "memory"); }
DEV uint4 ldnc4(const void* p) { uint4 v; asm volatile("ld.global.nc.v4.u32 {%0,%1,%2,%3},[%4];" : "=r"(v.x), "=r"(v.y), "=r"(v.z), "=r"(v.w) : "l"(p)); return v; }
DEV uint4 ldw4(const void* p) { uint4 v; asm volatile("ld.global.v4.u32 {%0,%1,%2,%3},[%4];" : "=r"(v.x), "=r"(v.y), "=r"(v.z), "=r"(v.w) : "l"(p) : "memory"); return v; }
DEV void cp16(uint32_t d, const void* p) { asm volatile("cp.async.cg.shared.global [%0],[%1],16;" :: "r"(d), "l"(p) : "memory"); }
DEV uint32_t ldnc16(const void* p) { uint32_t v; asm volatile("ld.global.u16 %0,[%1];" : "=r"(v) : "l"(p) : "memory"); return v; }

DEV uint32_t lds1v(uint32_t a) { uint32_t v; asm volatile("ld.volatile.shared.u32 %0,[%1];" : "=r"(v) : "r"(a) : "memory"); return v; }
DEV uint4 lds4v(uint32_t a) { uint4 v; asm volatile("ld.volatile.shared.v4.u32 {%0,%1,%2,%3},[%4];" : "=r"(v.x), "=r"(v.y), "=r"(v.z), "=r"(v.w) : "r"(a) : "memory"); return v; }
DEV uint32_t lds1(uint32_t a) { uint32_t v; asm volatile("ld.shared.u32 %0,[%1];" : "=r"(v) : "r"(a)); return v; }
DEV uint2 lds2(uint32_t a) { uint2 v; asm volatile("ld.shared.v2.u32 {%0,%1},[%2];" : "=r"(v.x), "=r"(v.y) : "r"(a)); return v; }
DEV uint4 lds4(uint32_t a) { uint4 v; asm volatile("ld.shared.v4.u32 {%0,%1,%2,%3},[%4];" : "=r"(v.x), "=r"(v.y), "=r"(v.z), "=r"(v.w) : "r"(a)); return v; }
DEV uint32_t lds16(uint32_t a) { uint32_t v; asm volatile("ld.shared.u16 %0,[%1];" : "=r"(v) : "r"(a)); return v; }
DEV float lds1f(uint32_t a) { float v; asm volatile("ld.shared.f32 %0,[%1];" : "=f"(v) : "r"(a)); return v; }
DEV float2 lds2f(uint32_t a) { float2 v; asm volatile("ld.shared.v2.f32 {%0,%1},[%2];" : "=f"(v.x), "=f"(v.y) : "r"(a)); return v; }
DEV float4 lds4f(uint32_t a) { float4 v; asm volatile("ld.shared.v4.f32 {%0,%1,%2,%3},[%4];" : "=f"(v.x), "=f"(v.y), "=f"(v.z), "=f"(v.w) : "r"(a)); return v; }
DEV void sts1(uint32_t a, uint32_t v) { asm volatile("st.shared.u32 [%0],%1;" :: "r"(a), "r"(v) : "memory"); }
DEV void sts16(uint32_t a, uint32_t v) { asm volatile("{.reg .b16 h; cvt.u16.u32 h,%1; st.shared.u16 [%0],h;}" :: "r"(a), "r"(v) : "memory"); }
DEV void sts2f(uint32_t a, float x, float y) { asm volatile("st.shared.v2.f32 [%0],{%1,%2};" :: "r"(a), "f"(x), "f"(y) : "memory"); }
DEV void sts4f(uint32_t a, float x, float y, float z, float w) { asm volatile("st.shared.v4.f32 [%0],{%1,%2,%3,%4};" :: "r"(a), "f"(x), "f"(y), "f"(z), "f"(w) : "memory"); }
DEV void sts4(uint32_t a, uint32_t x, uint32_t y, uint32_t z, uint32_t w) { asm volatile("st.shared.v4.u32 [%0],{%1,%2,%3,%4};" :: "r"(a), "r"(x), "r"(y), "r"(z), "r"(w) : "memory"); }
DEV void sts4z_if(uint32_t a, bool c) { asm volatile("{.reg .pred q; setp.ne.u32 q,%1,0; @q st.shared.v4.u32 [%0],{%2,%2,%2,%2};}" :: "r"(a), "r"((uint32_t)c), "r"(0) : "memory"); }

DEV void ldsm4t(uint32_t& r0, uint32_t& r1, uint32_t& r2, uint32_t& r3, uint32_t a) { asm volatile("ldmatrix.sync.aligned.m8n8.x4.trans.shared.b16 {%0,%1,%2,%3},[%4];" : "=r"(r0), "=r"(r1), "=r"(r2), "=r"(r3) : "r"(a) : "memory"); }
DEV void stsm4(uint32_t a, uint32_t r0, uint32_t r1, uint32_t r2, uint32_t r3) { asm volatile("stmatrix.sync.aligned.m8n8.x4.shared.b16 [%0],{%1,%2,%3,%4};" :: "r"(a), "r"(r0), "r"(r1), "r"(r2), "r"(r3) : "memory"); }
DEV void stsm2(uint32_t a, uint32_t r0, uint32_t r1) { asm volatile("stmatrix.sync.aligned.m8n8.x2.shared.b16 [%0],{%1,%2};" :: "r"(a), "r"(r0), "r"(r1) : "memory"); }
DEV void stsm4t(uint32_t a, uint32_t r0, uint32_t r1, uint32_t r2, uint32_t r3) { asm volatile("stmatrix.sync.aligned.m8n8.x4.trans.shared.b16 [%0],{%1,%2,%3,%4};" :: "r"(a), "r"(r0), "r"(r1), "r"(r2), "r"(r3) : "memory"); }
DEV uint32_t movm(uint32_t a) { uint32_t d; asm volatile("movmatrix.sync.aligned.m8n8.trans.b16 %0,%1;" : "=r"(d) : "r"(a)); return d; }
DEV void mma16(float (&d)[4], uint32_t a0, uint32_t a1, uint32_t a2, uint32_t a3, uint32_t b0, uint32_t b1) {
  asm volatile("mma.sync.aligned.m16n8k16.row.col.f32.bf16.bf16.f32 {%0,%1,%2,%3},{%4,%5,%6,%7},{%8,%9},{%0,%1,%2,%3};"
    : "+f"(d[0]), "+f"(d[1]), "+f"(d[2]), "+f"(d[3]) : "r"(a0), "r"(a1), "r"(a2), "r"(a3), "r"(b0), "r"(b1));
}
DEV void mma16z(float (&d)[4], uint32_t a0, uint32_t a1, uint32_t a2, uint32_t a3, uint32_t b0, uint32_t b1) {
  asm volatile("mma.sync.aligned.m16n8k16.row.col.f32.bf16.bf16.f32 {%0,%1,%2,%3},{%4,%5,%6,%7},{%8,%9},{%10,%10,%10,%10};"
    : "=f"(d[0]), "=f"(d[1]), "=f"(d[2]), "=f"(d[3]) : "r"(a0), "r"(a1), "r"(a2), "r"(a3), "r"(b0), "r"(b1), "f"(0.f));
}
DEV void mma8z(float (&d)[4], uint32_t a0, uint32_t a1, uint32_t b0) {
  asm volatile("mma.sync.aligned.m16n8k8.row.col.f32.bf16.bf16.f32 {%0,%1,%2,%3},{%4,%5},{%6},{%7,%7,%7,%7};"
    : "=f"(d[0]), "=f"(d[1]), "=f"(d[2]), "=f"(d[3]) : "r"(a0), "r"(a1), "r"(b0), "f"(0.f));
}
DEV void mma8(float (&d)[4], uint32_t a0, uint32_t a1, uint32_t b0) {
  asm volatile("mma.sync.aligned.m16n8k8.row.col.f32.bf16.bf16.f32 {%0,%1,%2,%3},{%4,%5},{%6},{%0,%1,%2,%3};"
    : "+f"(d[0]), "+f"(d[1]), "+f"(d[2]), "+f"(d[3]) : "r"(a0), "r"(a1), "r"(b0));
}

DEV void bar_sync(int id, int n) { asm volatile("bar.sync %0,%1;" :: "r"(id), "r"(n) : "memory"); }
DEV void bar_arrive(int id, int n) { asm volatile("bar.arrive %0,%1;" :: "r"(id), "r"(n) : "memory"); }
DEV void bar_sync_if(int id, int n, int c) { asm volatile("{.reg .pred q; setp.ne.s32 q,%2,0; @q bar.sync %0,%1;}" :: "r"(id), "r"(n), "r"(c) : "memory"); }
DEV void bar_arrive_if(int id, int n, int c) { asm volatile("{.reg .pred q; setp.ne.s32 q,%2,0; @q bar.arrive %0,%1;}" :: "r"(id), "r"(n), "r"(c) : "memory"); }
DEV bool bar_any(int id, int n, bool c) {
  uint32_t r; asm volatile("{.reg .pred p,q; setp.ne.u32 q,%3,0; bar.red.or.pred p,%1,%2,q; selp.u32 %0,1,0,p;}" : "=r"(r) : "r"(id), "r"(n), "r"((uint32_t)c) : "memory");
  return __any_sync(0xffffffffu, r);
}
DEV void fence_async_glob() { asm volatile("fence.proxy.async.global;" ::: "memory"); }
DEV void fence_async_smem() { asm volatile("fence.proxy.async.shared::cta;" ::: "memory"); }
DEV void fence_gpu() { asm volatile("fence.acq_rel.gpu;" ::: "memory"); }
DEV void mbar_wait(uint32_t b, uint32_t ph) {
  asm volatile("{\n.reg .pred p;\nW: mbarrier.try_wait.parity.shared::cta.b64 p,[%0],%1;\n@!p bra W;\n}" :: "r"(b), "r"(ph) : "memory");
}
DEV bool mbar_test(uint32_t b, uint32_t ph) {
  uint32_t r; asm volatile("{.reg .pred p; mbarrier.test_wait.parity.shared::cta.b64 p,[%1],%2; selp.u32 %0,1,0,p;}" : "=r"(r) : "r"(b), "r"(ph) : "memory");
  return __all_sync(0xffffffffu, r);
}
DEV void spin_guard(int it) { asm volatile("{.reg .pred p; setp.gt.s32 p,%0,%1; @p trap;}" :: "r"(it), "n"(SPIN_LIMIT)); }
DEV uint32_t here(uint32_t zero) {
  uint32_t d; asm volatile("mov.u32 %0,%%clock;" : "=r"(d) :: "memory"); return d & zero;
}
DEV int lane_here(uint32_t zero) {
  uint32_t d; asm volatile("mov.u32 %0,%%laneid;" : "=r"(d)); return d | here(zero);
}
DEV void delay(uint32_t n) { const uint32_t t0 = clock(); while ((uint32_t)clock() - t0 < n); __syncwarp(); }
DEV void poll(const uint32_t* p, uint32_t n) {
  for (int it = 0; !__all_sync(0xffffffffu, ldr1(p) >= n); ++it) spin_guard(it);
}
DEV void cnt_add(const Params& P, int n, int c, int lane) { asm volatile("{.reg .pred p; setp.lt.s32 p,%1,%2; @p red.relaxed.gpu.global.add.u32 [%0],1;}" :: "l"(P.S->C + (32 * (NSUB * lane + c % NSUB) + n * 1024)), "r"(lane), "n"(NCOPY) : "memory"); }
DEV void cnt_wait(const Params& P, int n, int c, int lane) { poll(P.S->C + (32 * (NSUB * (c / (128 / NCOPY)) + lane % NSUB) + n * 1024), 128 / NSUB); }
DEV void mbar_init1(uint32_t b, int n) { asm volatile("{.reg .pred p; elect.sync _|p,0xffffffff; @p mbarrier.init.shared::cta.b64 [%0],%1;}" :: "r"(b), "r"(n) : "memory"); }
DEV void mbar_arrive1(uint32_t b) { asm volatile("{.reg .pred p; elect.sync _|p,0xffffffff; @p mbarrier.arrive.shared::cta.b64 _,[%0];}" :: "r"(b) : "memory"); }
DEV void mbar_arrive1_if(uint32_t b, int c) {
  asm volatile("{.reg .pred p,q; setp.ne.s32 q,%1,0; elect.sync _|p,0xffffffff; and.pred p,p,q; @p mbarrier.arrive.shared::cta.b64 _,[%0];}" :: "r"(b), "r"(c) : "memory");
}
DEV void mbar_expect1(uint32_t b, int bytes) { asm volatile("{.reg .pred p; elect.sync _|p,0xffffffff; @p mbarrier.arrive.expect_tx.shared::cta.b64 _,[%0],%1;}" :: "r"(b), "r"(bytes) : "memory"); }
DEV void flag_set1(uint32_t* q) { asm volatile("{.reg .pred p; elect.sync _|p,0xffffffff; @p st.relaxed.gpu.global.u32 [%0],1;}" :: "l"(q) : "memory"); }
DEV void tma3(uint32_t dst, const CUtensorMap* m, int c0, int c1, uint32_t bar) {
  asm volatile("{.reg .pred p; elect.sync _|p,0xffffffff;\n"
    "@p cp.async.bulk.tensor.3d.shared::cluster.global.mbarrier::complete_tx::bytes [%0],[%1,{%2,%3,%5}],[%4];}"
    :: "r"(dst), "l"(m), "r"(c0), "r"(c1), "r"(bar), "r"(0) : "memory");
}
DEV void tma5(uint32_t dst, const CUtensorMap* m, int c0, int c4, uint32_t bar) {
  asm volatile("{.reg .pred p; elect.sync _|p,0xffffffff;\n"
    "@p cp.async.bulk.tensor.5d.shared::cluster.global.mbarrier::complete_tx::bytes [%0],[%1,{%2,%5,%5,%5,%3}],[%4];}"
    :: "r"(dst), "l"(m), "r"(c0), "r"(c4), "r"(bar), "r"(0) : "memory");
}
DEV void bulk(uint32_t dst, const void* src, int bytes, uint32_t bar) {
  asm volatile("{.reg .pred p; elect.sync _|p,0xffffffff;\n@p cp.async.bulk.shared::cluster.global.mbarrier::complete_tx::bytes [%0],[%1],%2,[%3];}" :: "r"(dst), "l"(src), "r"(bytes), "r"(bar) : "memory");
}
DEV void bulk_store(void* dst, uint32_t src, int bytes) {
  asm volatile("{.reg .pred p; elect.sync _|p,0xffffffff;\n@p cp.async.bulk.global.shared::cta.bulk_group [%0],[%1],%2;}" :: "l"(dst), "r"(src), "r"(bytes) : "memory");
}
DEV void l2_prefetch(const void* src, int bytes) {
  asm volatile("{.reg .pred p; elect.sync _|p,0xffffffff;\n@p cp.async.bulk.prefetch.L2.global [%0],%1;}" :: "l"(src), "r"(bytes) : "memory");
}

DEV uint64_t mkdesc(uint32_t addr, uint32_t lbo, uint32_t sbo, uint32_t swz) {
  return (uint64_t)((addr >> 4) | ((lbo >> 4) << 16)) | ((uint64_t)((sbo >> 4) | (swz << 30)) << 32);
}
DEV void wg_fence() { asm volatile("wgmma.fence.sync.aligned;" ::: "memory"); }
DEV void wg_commit() { asm volatile("wgmma.commit_group.sync.aligned;" ::: "memory"); }
template <int N> DEV void wg_wait() { asm volatile("wgmma.wait_group.sync.aligned %0;" :: "n"(N) : "memory"); }
template <int N> DEV void zerov(float (&d)[N]) {
#pragma unroll
  for (int i = 0; i < N; ++i) asm volatile("mov.b32 %0,0;" : "=f"(d[i]));
}
template <int N> DEV void undef(float (&d)[N]) {
#pragma unroll
  for (int i = 0; i < N; ++i) asm volatile("" : "=f"(d[i]));
}
#define R4(d, o) "+f"(d[o]), "+f"(d[o + 1]), "+f"(d[o + 2]), "+f"(d[o + 3])
#define R8(d, o) R4(d, o), R4(d, o + 4)
#define R16(d, o) R8(d, o), R8(d, o + 8)
#define R32(d, o) R16(d, o), R16(d, o + 16)
#define L0 "%0,%1,%2,%3,%4,%5,%6,%7,%8,%9,"
#define L10(a) "%" #a "0,%" #a "1,%" #a "2,%" #a "3,%" #a "4,%" #a "5,%" #a "6,%" #a "7,%" #a "8,%" #a "9,"
#define WG_HEAD(pr, n) "{.reg .pred p; setp.ne.s32 p,%" #pr ",0;\nwgmma.mma_async.sync.aligned.m64n" #n "k16.f32.bf16.bf16 {"
DEV void wg_rs64k(float (&d)[32], const uint32_t (&a)[4], uint64_t db, int acc) {
  asm volatile(WG_HEAD(37, 64) L0 L10(1) L10(2) "%30,%31},{%32,%33,%34,%35},%36,p,1,1,0;}"
    : R32(d, 0) : "r"(a[0]), "r"(a[1]), "r"(a[2]), "r"(a[3]), "l"(db), "r"(acc));
}
DEV void wg_rs48t(float (&d)[24], const uint32_t (&a)[4], uint64_t db, int acc) {
  asm volatile(WG_HEAD(29, 48) L0 L10(1) "%20,%21,%22,%23},{%24,%25,%26,%27},%28,p,1,1,1;}"
    : R16(d, 0), R8(d, 16) : "r"(a[0]), "r"(a[1]), "r"(a[2]), "r"(a[3]), "l"(db), "r"(acc));
}
DEV void wg_rs32t(float (&d)[16], const uint32_t (&a)[4], uint64_t db, int acc) {
  asm volatile(WG_HEAD(21, 32) L0 "%10,%11,%12,%13,%14,%15},{%16,%17,%18,%19},%20,p,1,1,1;}"
    : R16(d, 0) : "r"(a[0]), "r"(a[1]), "r"(a[2]), "r"(a[3]), "l"(db), "r"(acc));
}
DEV void wg_ss48(float (&d)[24], uint64_t da, uint64_t db, int acc) {
  asm volatile(WG_HEAD(26, 48) L0 L10(1) "%20,%21,%22,%23},%24,%25,p,1,1,1,1;}" : R16(d, 0), R8(d, 16) : "l"(da), "l"(db), "r"(acc));
}
DEV void wg_ss64(float (&d)[32], uint64_t da, uint64_t db, int acc) {
  asm volatile(WG_HEAD(34, 64) L0 L10(1) L10(2) "%30,%31},%32,%33,p,1,1,0,1;}" : R32(d, 0) : "l"(da), "l"(db), "r"(acc));
}
DEV void wg_ss192(float (&d)[96], uint64_t da, uint64_t db, int acc) {
  asm volatile(WG_HEAD(98, 192) L0 L10(1) L10(2) L10(3) L10(4) L10(5) L10(6) L10(7) L10(8) "%90,%91,%92,%93,%94,%95},%96,%97,p,1,1,1,1;}"
    : R32(d, 0), R32(d, 32), R32(d, 64) : "l"(da), "l"(db), "r"(acc));
}

DEV void wg_rs192t(float (&d)[96], const uint32_t (&a)[4], uint64_t db) {
  asm volatile("wgmma.mma_async.sync.aligned.m64n192k16.f32.bf16.bf16 {" L0 L10(1) L10(2) L10(3) L10(4) L10(5) L10(6) L10(7) L10(8) "%90,%91,%92,%93,%94,%95},{%96,%97,%98,%99},%100,1,1,1,1;"
    : R32(d, 0), R32(d, 32), R32(d, 64) : "r"(a[0]), "r"(a[1]), "r"(a[2]), "r"(a[3]), "l"(db));
}

DEV float ln_sd(float s, float q, float& m) {
  m = s * (1.f / 512.f);
  return bfr(sqrt_(bfr(bfr(fmaxf(q * (1.f / 512.f) - m * m, 0.f)) + 1e-5f)));
}
DEV float4 gram(const uint32_t (&w)[8][2], int g, uint32_t zero) {
  float s[4], q[4][4];
  const uint32_t o0 = 0x3F803F80u | zero, o1 = 0x3F803F80u ^ zero;
#pragma unroll
  for (int j = 0; j < 8; ++j) {
#pragma unroll
    for (int h = 0; h < 2; ++h) { if (j < 2) mma8z(q[2 * j + h], w[j][0], w[j][1], w[j][h]); else mma8(q[2 * (j & 1) + h], w[j][0], w[j][1], w[j][h]); }
    if (j == 1) mma16z(s, w[0][0], w[0][1], w[1][0], w[1][1], o0, o1);
    else if (j & 1) mma16(s, w[j - 1][0], w[j - 1][1], w[j][0], w[j][1], o0, o1);
  }
  const bool od = g & 1;
  return make_float4(s[0], od ? q[0][1] + q[2][1] : q[0][0] + q[2][0], s[2], od ? q[1][3] + q[3][3] : q[1][2] + q[3][2]);
}
DEV void keep(uint32_t v, uint32_t zero) {
  asm volatile("{.reg .pred p; setp.ne.u32 p,%1,0; @p st.shared.u32 [%0],%0;}" :: "r"(v), "r"(zero) : "memory");
}
DEV void keep(const void* v, uint32_t zero) { asm volatile("{.reg .pred p; setp.ne.u32 p,%1,0; @p st.global.u32 [%0],%1;}" :: "l"(v), "r"(zero) : "memory"); }
struct XgAddr { uint32_t a, b; uint4* dst; };
template <bool FRAG> DEV XgAddr xg_addr(uint4* dst, uint32_t stg, int wp, int lane, uint32_t zero) {
  const int t = lane & 3, r = 4 * wp + (lane >> 3);
  XgAddr x = {stg + t * (FRAG ? 256 : 1024) + ((wp ^ t) * 32) + (lane >> 2) * 4,
              stg + r * 128 + (((lane & 7) ^ (2 * (((r >> 1) ^ (r >> 3)) & 3))) * 16), dst + (r * 256 + (lane & 7))};
  keep(x.a, zero); keep(x.b, zero); keep(x.dst, zero);
  return x;
}
template <bool FRAG> DEV void xg_put(const XgAddr& x, const uint32_t (&w)[8][2]) {
#pragma unroll
  for (int n = 0; n < 8; ++n) {
    const uint32_t b = (x.a ^ ((n & 3) * 32)) + (FRAG ? n * 1024 : (n >> 2) * 4096 + (n & 3) * 256);
    sts1(b, prmt(w[n][0], w[n][1], 0x5410)); sts1(b + 128, prmt(w[n][0], w[n][1], 0x7632));
  }
}
DEV void xg_store(const XgAddr& x, int nb) {
  bar_sync(nb, 128);
#pragma unroll
  for (int k = 0; k < 4; ++k) {
    const uint4 v = lds4((x.b ^ ((k & 1) * 64)) + k * 2048);
    str4(x.dst + k * 4096, nz(v.x), v.y, v.z, v.w);
  }
}
template <int N, int M> DEV void fold(float (&v)[M], int lane, int bit) {
  const bool b = lane & bit;
#pragma unroll
  for (int k = 0; k < N; ++k) { const float sn = b ? v[k] : v[k + N], kp = b ? v[k + N] : v[k]; v[k] = kp + __shfl_xor_sync(0xffffffffu, sn, bit); }
}
DEV void refetch(uint32_t dst, const uint4* src, int half, int e, int w) {
#pragma unroll 1
  for (int r = 0; r < 2; ++r) {
    if (w == 0) { mbar_expect1(B_R + 8 * e, half); bulk(dst + r * half, src + r * (half >> 4), half, B_R + 8 * e); }
    mbar_wait(B_R + 8 * e, r);
    bar_sync(NB_WG + e, 128);
  }
}
DEV uint32_t kvslot(int cg, int pos) { return (pos & 2 ? SM_XA : SM_S1) + (cg < 4 ? 5 : 2) * 8192 + (pos & 1) * 4096; }
DEV uint32_t xstage(int q, int e) { return ((q + 1) & 2) ? SM_R + ((q & 2) + e) * 16384 : e ? SM_XB : SM_XA; }
DEV void cmul(float& orr, float& oi, float ar, float ai, float br, float bi) {
  float r = ar * br - ai * bi, i = ar * bi + ai * br; orr = r; oi = i;
}
DEV void cexp_(float al, float bt, float s, float& er, float& ei) {
  float mag = ex2(al * s), ph = bt * s;
  ph -= rintf(ph);
  float ang = ph * 6.283185307179586f;
  er = mag * __cosf(ang); ei = mag * __sinf(ang);
}

#define KS 2048
#define LATEF 0
DEV void put8(uint32_t a, const float (&r)[8], const float (&i)[8]) {
  sts4(a, pack2(r[0], r[1]), pack2(r[2], r[3]), pack2(r[4], r[5]), pack2(r[6], r[7]));
  sts4(a + 1024, pack2(i[0], i[1]), pack2(i[2], i[3]), pack2(i[4], i[5]), pack2(i[6], i[7]));
}
DEV void tables(const uint32_t (&pv)[8], int k4, int w, int lane) {
  PW(4 * k4 + w)
  [[maybe_unused]] const int layer = 0;
  const float dt = bfr(__expf(bflo(pv[6])));
  const float al = dt * bflo(pv[0]) * 1.4426950408889634f, bt = dt * bflo(pv[1]) * 0.15915494309189535f;
  float qr[8], qi[8], yr[8], yi[8];
  cmul(qr[0], qi[0], bflo(pv[4]), bflo(pv[5]), dt * bflo(pv[2]), dt * bflo(pv[3]));
  PROFD(2, a_par, __float_as_uint(qr[0] + al + bt));
  float e1r, e1i, eMr, eMi, eLr, eLi;
  cexp_(al, bt, 1.f, e1r, e1i); cexp_(al, -bt, 8.f, yr[1], yi[1]); cexp_(al, -bt, 64.f, eMr, eMi); cexp_(al, bt, 256.f, eLr, eLi);
  const uint32_t ad = SB + k4 * 32768 + (w & 1) * 512 + lane * 16, am = ad + (w >> 1) * KS, an = ad + (8 + 3 * (w >> 1)) * KS;
  yr[0] = 1.f; yi[0] = 0.f;
#pragma unroll
  for (int k = 1; k < 8; ++k) {
    cmul(qr[k], qi[k], qr[k - 1], qi[k - 1], e1r, e1i);
    if (k > 1) cmul(yr[k], yi[k], yr[k - 1], yi[k - 1], yr[1], yi[1]);
  }
  put8(an, qr, qi);
#pragma unroll
  for (int j = 0; j < 4; ++j) {
    put8(am + j * 2 * KS, yr, yi);
#pragma unroll
    for (int k = 0; k < 8; ++k) {
      if (j == 0 && k == 0) { yr[0] = eMr; yi[0] = eMi; } else if (j < 3) cmul(yr[k], yi[k], yr[k], yi[k], eMr, eMi);
    }
    if (j == 0) {
#pragma unroll
      for (int k = 0; k < 8; ++k) { const int o = k < 4 ? 2 * k : k < 6 ? 2 * k - 8 : k - 2; cmul(qr[k], qi[k], qr[o], qi[o], eLr, eLi); }
      put8(an + KS, qr, qi);
    } else if (j == 1) {
#pragma unroll
      for (int k = 0; k < 5; ++k) cmul(qr[k], qi[k], qr[k ? k - 1 : 6], qi[k ? k - 1 : 6], eLr, eLi);
      put8(an + 2 * KS, qr, qi);
    }
  }
  PROF(3, a_tab);
}

DEV void sts16_if(uint32_t a, uint32_t v, bool c) { asm volatile("{.reg .pred q; .reg .b16 h; setp.ne.u32 q,%2,0; cvt.u16.u32 h,%1; @q st.shared.u16 [%0],h;}" :: "r"(a), "r"(v), "r"((uint32_t)c) : "memory"); }
DEV void sts1_if(uint32_t a, uint32_t v, bool c) { asm volatile("{.reg .pred q; setp.ne.u32 q,%2,0; @q st.shared.u32 [%0],%1;}" :: "r"(a), "r"(v), "r"((uint32_t)c) : "memory"); }
DEV void taps(uint32_t dskip, int k4, int w, int lane) {
  PW(4 * k4 + w)
  [[maybe_unused]] const int layer = 0;
  fence_async_smem();
  bar_sync(k4 > LATEF ? NB_WG + k4 : NB_Q, k4 > LATEF ? 128 : 448 + 64 * LATEF);
  float d[24];
  undef(d);
  const uint64_t da = mkdesc(SB + k4 * 32768, 1024, KS, 0);
  wg_fence();
#pragma unroll
  for (int j = 0; j < 8; ++j) wg_ss48(d, da + j * 8, da + KS / 2 + j * 8, j);
  wg_commit();
  const int b = 8 * w + (lane >> 2), t = lane & 3, id = 32 * w + lane;
  constexpr int DO = T_O - T_E;
  const uint32_t te = SM_TAP + k4 * TAP_SZ + T_E, a0 = te - 16 * b - 4 * t;
  const uint32_t a1 = a0 - 512 - 4 * t, a2 = te - 2 * (511 + b) - 64 * t, a3 = te + (T_C - T_E) - 2 * (127 + b) - 128 * t;
  wg_wait<0>();
  PROF(4, a_mma);
  {
    const uint32_t v = pack2(d[1] + d[15], d[0] + d[14] + (id ? 0.f : bflo(dskip)));
    sts1(a0 + DO - 2, v); sts16(a0 - 2, v); sts16(a0, v >> 16);
  }
  {
    const uint32_t v = pack2(d[5] + d[19], d[4] + d[18]), u = prmt(v, v, 0x3232);
    const bool lo = t < 2, k512 = id == 2;
    sts1_if(k512 ? te - 2 * 512 : a1, u, (lo && id) || k512);
    sts1_if(k512 ? te - 2 * 514 : a1 - 4, k512 ? u : v, lo || k512);
    sts1_if(k512 ? te + DO - 2 * 513 : a1 + DO - 2, u, lo || k512);
    sts16(lo ? a1 + DO - 4 : a2 + DO - 194, v);
    sts16(lo ? (id ? a1 + DO + 2 : a1) : k512 ? te + DO - 2 * 511 : a2 + DO, u);
    sts16_if(a2 - 194, v, !lo);
    sts16_if(k512 ? te + DO - 2 * 514 : a2, u, !lo);
  }
  {
    const uint32_t v = pack2(d[8] + d[22], d[9] + d[23]);
    sts16_if(id ? a3 : te - 2 * 639, v, t < 2 || id == 2);
    sts16_if(a3 - 64, v >> 16, t < 2);
    sts16_if(te + DO - 2 * 639, v, id == 0);
  }
  bar_sync(NB_WG + k4, 128);
  mbar_arrive1_if(B_K, w == 0);
}

DEV uint32_t cpy(uint32_t v, uint32_t id) {
  uint32_t d; asm volatile("prmt.b32 %0,%1,%1,%2;" : "=r"(d) : "r"(v), "r"(id)); return d;
}
DEV uint32_t uoff(int s) { return (s ^ ((s >> 3) & 3)) * 16; }
template <bool FULL> DEV void boxes(const uint32_t (&u)[10], uint32_t a, uint32_t a9, uint32_t a7, uint32_t (&pv)[4]) {
  uint32_t v[8], p[8], x[4], y[4];
#pragma unroll
  for (int j = 0; j < 8; ++j) { v[j] = prmt(u[j], u[j + 1], 0x5432); p[j] = hadd2(u[j], v[j]); }
#pragma unroll
  for (int j = 0; j < 4; ++j) { x[j] = hadd2(hadd2(p[j + 1], p[j + 2]), u[j + 3]); y[j] = hadd2(v[j + 3], p[j + 4]); }
  sts4(a + R_A5, x[0], x[1], x[2], x[3]);
  sts4(a + R_A3, y[0], y[1], y[2], y[3]);
  if (FULL) {
#pragma unroll
    for (int j = 0; j < 4; ++j) { x[j] = hadd2(x[j], hadd2(v[j], v[j + 3])); y[j] = hadd2(x[j], hadd2(u[j], u[j + 4])); pv[j] = p[j + 4]; }
    sts4(a7, x[0], x[1], x[2], x[3]);
    sts4(a9, y[0], y[1], y[2], y[3]);
  }
}
DEV void halo(uint32_t (&u)[10], uint32_t a, int lane) {
  asm volatile("{.reg .pred p,q; setp.eq.s32 p,%8,0; setp.lt.s32 q,%8,2;\n@p ld.shared.v4.u32 {%2,%3,%4,%5},[%6];\n@q ld.shared.v2.u32 {%0,%1},[%7];}"
    : "+r"(u[0]), "+r"(u[1]), "+r"(u[2]), "+r"(u[3]), "+r"(u[4]), "+r"(u[5]) : "r"(a), "r"(a + 24 - 16 * lane), "r"(lane));
}
DEV void quad_ld(uint32_t (&q)[4], uint32_t a) { q[0] = lds1(a); q[2] = lds1(a + 16); q[1] = lds1(a - 128); q[3] = lds1(a - 112); }
DEV void half_ld(uint32_t (&q)[4][4], uint32_t a, uint32_t zero) {
  zero = here(zero);
#pragma unroll
  for (int kk = 0; kk < 2; ++kk) {
    q[2 + kk][0] = lds1(a + 32 * kk); q[2 + kk][2] = lds1(a + 32 * kk + 16);
    q[2 + kk][1] = cpy(zero, 2 * kk); q[2 + kk][3] = cpy(zero, 2 * kk + 1);
  }
}

#define ROT 2
#define G1 -1
#define G2 0
#define G3 1
#define TPS 0x6236
#define GMASK ((G1 >= 0 ? 2 : 0) | (G2 >= 0 ? 4 : 0) | (G3 >= 0 ? 8 : 0))
#define GATE1(g, n, p) if (g >= 0 && (g & 3) == p) mbar_arrive1_if(B_G + 8 * n, k4 == (g >> 2));
#define GATE(p) GATE1(G1, 0, p) GATE1(G2, 1, p) GATE1(G3, 2, p)
#define TMASK(p) (((TPS & 15) == p) | ((((TPS >> 4) & 15) == p) << 1) | ((((TPS >> 8) & 15) == p) << 2) | ((((TPS >> 12) & 15) == p) << 3))
#define TURN(p) if (TMASK(p) == 15) bar_arrive(NB_T + 1 + k4, 256); else if (TMASK(p)) { if ((TMASK(p) >> k4) & 1) bar_arrive(NB_T + 1 + k4, 256); }
#define ANN(p, dep) if (EA & (0x1111 * p)) cnt_add(P, 1 + 5 * layer + k4, c, (32 * (v ^ 3) + lane) | (dep) | ((~(EA >> (4 * k4)) & p) << 8));
DEV void w_load(const CUtensorMap* mW, int cg, int h) {
  mbar_expect1(B_W + 8 * h, 24576);
  tma3(SM_S0 + (h & 3) * 24576, mW, 64 * cg, 64 * h, B_W + 8 * h);
}

DEV void conv(const Params& P, const CUtensorMap* mW, int c, int k4, int w, int layer) {
  const uint32_t zero = P.zero;
  PW(4 * k4 + w)
  int lane = lane_here(zero);
  const int g = lane >> 2, t = lane & 3, v = w ^ (ROT * (k4 & 1)), tid = 32 * v + lane;
  const uint32_t reg = SM_R + k4 * 16384, tp = SM_TAP + k4 * TAP_SZ;
  const uint32_t g0 = tp + ((g & 1) ? T_O : T_E) + 2 * (2 * t - g);
  uint32_t F[18][4], U[12];
  {
    const uint32_t ga = g0 - 32 * (w & 1) - 576 * (w >> 1);
    F[0][2] = lds1(ga + 48);
#pragma unroll
    for (int j = 0; j < 12; ++j) { F[j][0] = lds1(ga + 32 - 32 * j); F[j][1] = lds1(ga + 16 - 32 * j); }
#pragma unroll
    for (int j = 0; j < 12; ++j) U[j] = lds1(ga - 352 - 16 * j);
  }
  PROF(5, a_pre);
  if (k4 == 3 && w == 3) {
    mbar_wait(B_E, layer);
    mbar_wait(B_K, 0);
#pragma unroll
    for (int h = 0; h < 4; ++h) w_load(mW, c & 7, h);
  }
  mbar_wait(k4 && ((GMASK >> k4) & 1) ? B_G - 8 + 8 * k4 : B_E, layer);
  PROF(6, a_x);
  const uint32_t ua = reg + R_U + uoff(tid);
  uint4 x[2];
  uint32_t pv[4];
  {
    uint4 s[4];
#pragma unroll
    for (int z = 0; z < 2; ++z) x[z] = lds4(reg + R_B + tid * 16 + z * 2048);
#pragma unroll
    for (int z = 0; z < 4; ++z) s[z] = lds4(SM_RES + tid * 16 + (z >> 1) * 2048 + (z & 1) * 4096);
    sts4z_if(reg + lane * 16 + (w ? w * 3584 + 1024 : 0), w < 3);
    for (int it = 0;; ++it) {
      uint32_t m = min(x[0].x, x[1].x);
#pragma unroll
      for (int z = 0; z < 4; ++z) m = min(m, min(s[z].x, s[z].z));
      if (m) break;
#pragma unroll
      for (int z = 0; z < 2; ++z) x[z] = ldr4(&P.S->XG[layer][(128 * k4 + c) * 256 + opq(tid) + z * 128]);
#pragma unroll
      for (int z = 0; z < 4; ++z) s[z] = ldr4(&P.S->SR[layer][c >> 4][opq(tid) + (z >> 1) * 128 + (z & 1) * 256]);
#pragma unroll
      for (int z = 0; z < 4; ++z) sts4(SM_RES + tid * 16 + (z >> 1) * 2048 + (z & 1) * 4096, s[z].x, s[z].y, s[z].z, s[z].w);
      spin_guard(it);
    }
    __syncwarp();
    uint32_t u[2][10];
#pragma unroll
    for (int z = 0; z < 2; ++z) {
      u[z][6] = hmul2(hsub2(x[z].x, s[2 * z].y), s[2 * z].x); u[z][7] = hmul2(hsub2(x[z].y, s[2 * z].w), s[2 * z].z);
      u[z][8] = hmul2(hsub2(x[z].z, s[2 * z + 1].y), s[2 * z + 1].x); u[z][9] = hmul2(hsub2(x[z].w, s[2 * z + 1].w), s[2 * z + 1].z);
      sts4(ua + z * 2048, u[z][6], u[z][7], u[z][8], u[z][9]);
    }
#pragma unroll
    for (int j = 0; j < 6; ++j) u[0][j] = __shfl_up_sync(0xffffffffu, u[0][j < 2 ? 8 + j : 4 + j], j < 2 ? 2 : 1);
    bar_sync(NB_WG + k4, 128);
    GATE(0)
    PROF(7, a_u);
    const uint32_t h1 = reg + R_U + v * 512 - 64;
    halo(u[0], h1, lane);
    if (v < 2) {
      u[1][0] = 0;
#pragma unroll
      for (int j = 1; j < 6; ++j) u[1][j] = __shfl_up_sync(0xffffffffu, u[1][j < 2 ? 8 + j : 4 + j], j < 2 ? 2 : 1);
      halo(u[1], h1 + 2048, lane);
      boxes<false>(u[1], reg + tid * 16 + 2048, 0, 0, pv);
    }
    const uint32_t bo = reg + R_B + tid * 16 + (v >> 1) * 1056;
    const uint32_t be = tid == 127 ? reg + R_B + 1024 : bo + (tid == 63 ? 2112 : 1056);
    boxes<true>(u[0], reg + tid * 16, (lane & 1) ? be : bo, (lane & 1) ? bo : be, pv);
    sts4z_if(reg + R_B + 1040, tid == 0);
  }
  GATE(1)
  fence_async_smem();
  if (k4 == 3 && w < 3) {
    const uint32_t src = SM_RES + 8192 + w * 2048, f = (w >> 1) - 1;
#pragma unroll
    for (int z = 0; z < 4; ++z) sts4(src + lane * 16 + z * 512, f, f, f, f);
    fence_async_smem();
    __syncwarp();
    if (w < 2) {
#pragma unroll
      for (int z = 0; z < 4; ++z) bulk_store(&P.S->O[((c >> 3) * 16 + w * 8 + (c & 7)) * 512] + z * 128, src, 2048);
    } else {
#pragma unroll
      for (int z = 0; z < 2; ++z) {
        bulk_store(&P.S->H[(c + 8) * 256] + z * 128, src, 2048);
        bulk_store(P.S->F + ((c >> 3) * 64 + 4 * (c & 7)) + z * 32, src, 16);
      }
      bulk_store(&P.S->PS[c * 64], src, 1024);
      bulk_store(&P.S->ST[c * 4], src, 64);
      if (c < 5) bulk_store(P.S->C + (c + 5 - 5 * layer) * 1024, src, 128 * NCOPY * NSUB);
    }
    asm volatile("cp.async.bulk.commit_group;" ::: "memory");
  }
  const uint32_t id = opq(0x3210u);
#pragma unroll
  for (int j = 0; j < 12; ++j) { F[j][3] = cpy(F[j][0], id); if (j) F[j][2] = cpy(F[j - 1][1], id); }
  PROF(8, a_box);
  bar_sync(NB_T + k4, k4 ? 256 : 128);
  PROF(9, a_turn);
  float acc[32], f1[24], f3[16];
  uint32_t qa[4][4], qb[4][4], qc[4][4], yp[16];
  const uint64_t db = mkdesc(reg + R_U, 16, 512, 2) + 2;
#define STEP(mm, n) wg_fence(); mm; wg_commit(); wg_wait<n>();
#define D(j, n) STEP(wg_rs64k(acc, F[j], db - 2 * j, j), n)
#define T(q, j, o, n) STEP(wg_rs48t(f1, q[j], d1 + o + 16 * (j & 1) - 32 * (j >> 1), o | j), n)
#define SPREAD(n) { const uint32_t id = 0x3210u | here(zero); _Pragma("unroll") for (int j = n; j < n + 2; ++j) { \
    F[12 + j][0] = cpy(U[2 * j], id); F[12 + j][1] = cpy(U[2 * j + 1], id); F[12 + j][3] = cpy(F[12 + j][0], id); F[12 + j][2] = cpy(F[11 + j][1], id); } }
  const uint32_t g1 = g0 - 2 * 576 - 16 * w;
  const uint64_t d1 = mkdesc(reg + R_A5, 128, 512, 0);
  undef(acc);
  D(0, 3) TURN(0) D(1, 3) D(2, 3) D(3, 3) D(4, 3) SPREAD(0) D(5, 3) D(6, 3) TURN(1) SPREAD(2) D(7, 3) quad_ld(qa[0], g1);
  D(8, 3) SPREAD(4) D(9, 3) quad_ld(qa[1], g1 + 32); D(10, 3) half_ld(qa, g1 - 64, zero);
  D(11, 3) quad_ld(qb[0], g1 - 192); D(12, 3) TURN(2) quad_ld(qb[1], g1 - 160); D(13, 3) half_ld(qb, g1 - 256, zero);
  D(14, 3) D(15, 3) D(16, 3) D(17, 2)
  TURN(3)
  PROF(10, a_den);
  lane = lane_here(zero);
  const uint32_t g2 = tp + T_C - 258 - 32 * w + 4 * (lane & 3) - (lane & 28);
  undef(f1);
  T(qa, 0, 0, 2) quad_ld(qc[0], g2); T(qa, 1, 0, 2) quad_ld(qc[1], g2 + 32); T(qa, 2, 0, 2) quad_ld(qc[2], g2 + 64); T(qa, 3, 0, 2)
  TURN(4)
  quad_ld(qc[3], g2 + 96);
  constexpr int O3 = (R_A3 - R_A5) / 16;
  uint32_t pin = zero;
#define PACK(n) _Pragma("unroll") for (int z = n; z < n + 4; ++z) { yp[z] = pack2(acc[2 * z], acc[2 * z + 1]); pin &= yp[z]; }
  T(qb, 0, O3, 3) PACK(0) PACK(4) T(qb, 1, O3, 3) PACK(8) T(qb, 2, O3, 3) PACK(12) T(qb, 3, O3, 3)
  TURN(5)
  qc[0][0] |= pin;
  undef(f3);
  wg_fence();
#pragma unroll
  for (int kk = 0; kk < 4; ++kk) wg_rs32t(f3, qc[kk], mkdesc(reg + R_B, 128, 1040, 0) + 16 * kk, kk);
  wg_commit();
  TURN(6)
  asm volatile("cp.async.bulk.wait_group 0;" ::: "memory");
  uint32_t k1024 = lds16(tp + T_E - 2 * 639);
  lane |= here(zero);
  const int p = (lane + 9 * (w >> 1)) & 31;
  const uint32_t ya = reg + ((w >> 1) ? R_B : R_U) + p * 64 + (((2 * (w & 1)) ^ ((p >> 1) & 3)) * 16);
  const uint32_t up = p < lane ? 2048 : 0;
  const uint32_t fa = reg + R_A5 + (lane >> 3) * 512 + w * 128 + (lane & 7) * 16;
  const uint32_t fc = reg + R_A3 + uoff(64 * (lane >> 4) + 16 * w + 2 * (lane & 7) + 1 - ((lane >> 3) & 1));
  wg_wait<0>();
  GATE(2)
  PROF(11, a_far);
  bar_sync(NB_WG + k4, 128);
#pragma unroll
  for (int z = 0; z < 4; ++z) {
    const uint32_t* a = yp + 8 * (z >> 1) + (z & 1);
    stsm4t((ya + (up ^ ((z >> 1) * 2048))) ^ ((z & 1) * 16), a[0], a[2], a[4], a[6]);
  }
  stsm4(fa, pack2(f1[0], f1[1]), pack2(f1[4], f1[5]), pack2(f1[8] + f1[2], f1[9] + f1[3]), pack2(f1[12] + f1[6], f1[13] + f1[7]));
  stsm2(fa + 2048, pack2(f1[16] + f1[10], f1[17] + f1[11]), pack2(f1[20] + f1[14], f1[21] + f1[15]));
  stsm4(fc, pack2(f3[0], f3[1]), pack2(f3[4], f3[5]), pack2(f3[8] + f3[2], f3[9] + f3[3]), pack2(f3[12] + f3[6], f3[13] + f3[7]));
  bar_sync(NB_WG + k4, 128);
  PROF(12, a_sts);
  {
    const int o = 32 * v + lane;
    const uint32_t a = reg + uoff(o), b = reg + R_A5 + o * 16;
    uint4 y[2];
    y[0] = hadd8(lds4(a + R_U), hadd8(lds4(o >= 36 ? a + R_B : reg), lds4(v >= 2 ? b - 1024 : reg)));
    uint4 h = lds4(a + R_A3);
    k1024 = prmt(k1024, k1024, 0x1010);
    h = make_uint4(hfma2(pv[0], k1024, h.x), hfma2(pv[1], k1024, h.y), hfma2(pv[2], k1024, h.z), hfma2(pv[3], k1024, h.w));
    y[1] = hadd8(lds4(a + R_U + 2048), hadd8(lds4(a + R_B + 2048), hadd8(lds4(b + 1024), h)));
    const int e0 = (o >> 3) * 8192 + (128 * k4 + c) * 16 + (((o & 4) + ((o >> 1) & 1)) ^ (c & 7)) * 2 + (o & 1);
    ANN(2, y[0].x & y[1].x & zero)
    const uint32_t me = (e0 & 3) == ((c >> 1) & 3), m0 = me & ~c, m1 = me & c, tag = 1 - layer;
#pragma unroll
    for (int z = 0; z < 2; ++z) {
      const uint4 r = hadd8(x[z], y[z]);
      str2((uint2*)P.S->XF + e0 + z * 131072, tagged(prmt(r.x, r.y, 0x5410), m0, tag), tagged(prmt(r.z, r.w, 0x5410), m1, tag));
      str2((uint2*)P.S->XF + (e0 ^ 4) + z * 131072, tagged(prmt(r.x, r.y, 0x7632), m0, tag), tagged(prmt(r.z, r.w, 0x7632), m1, tag));
    }
  }
  ANN(1, 0)
  GATE(3)
  PROF(13, a_out);
}

#define XORD 1
DEV void x_load(const Params& P, int c, int q, int layer) {
#pragma unroll
  for (int z = 0; z < 2; ++z) {
    const int e = z ^ (XORD && q == 3 && !(c & 4));
    mbar_expect1(B_X + 16 * q + 8 * e, 16384);
    bulk(xstage(q, e), P.S->XF + ((2 * (c >> 3) + 1 - e) * 4096 + q * 1024), 16384, B_X + 16 * q + 8 * e);
  }
}

DEV void means(uint32_t (&m)[4], int row, int lane, int layer, uint32_t zero) {
  mbar_wait(B_CS, 0);
  mbar_wait(B_ST, layer);
  const uint32_t a = SM_MISC + row * 4 + (lane & 28), k = (lane & 3) ? 0u : ~0u;
  m[0] = lds1(a) & k; m[1] = lds1(a + 32) & k; m[2] = m[0] & zero; m[3] = m[1] & zero;
}

DEV void attn_phase(const Params& P, int c, int e, int w, int lane, int layer) {
  PW(4 * e + w)
  const int cg = c & 7, J = 2 * (c >> 3) + 1 - e;
  float acc[96];
  zerov(acc);
  uint32_t m[4] = {0, 0, 0, 0};
#pragma unroll 1
  for (int q = 0;; ++q) {
    const uint64_t da = mkdesc(xstage(q, e), 16, 1024, 1), db = mkdesc(SM_S0 + (q & 1) * 49152, 8192, 1024, 1);
    bool all = mbar_test(B_W + 16 * q, layer) && mbar_test(B_W + 16 * q + 8, layer);
    mbar_wait(B_X + 16 * q + 8 * e, layer);
    for (int it = 0;; ++it) {
      const uint32_t a = xstage(q, e) + w * 4096 + lane * 132;
      const uint32_t ok = (lds1(a) ^ layer) & (lds1(a ^ 32) ^ layer) & (lds1(a ^ 64) ^ layer) & (lds1(a ^ 96) ^ layer);
      if (!bar_any(NB_WG + e, 128, !(ok & 1))) break;
      EVENT(8 * layer + 2 * q + e);
      refetch(xstage(q, e), P.S->XF + (J * 4096 + q * 1024), 8192, e, w);
      spin_guard(it);
    }
    if (q == 0 && e && w == 0) {
      bar_sync(NB_H, 160);
      cnt_wait(P, 2 + 5 * layer, c, lane);
      x_load(P, c, 1, layer);
      PROF(27, m_xi);
    }
    if (q == 3 && e) means(m, 16 * w, lane, layer, P.zero);
    if (!all) { mbar_wait(B_W + 16 * q, layer); all = mbar_test(B_W + 16 * q + 8, layer); }
    bar_sync(e ? NB_Q : q ? NB_T : NB_T + 4, 256);
    PROF(14 + q, m_q);
    wg_fence();
#pragma unroll
    for (int k = 0; k < 8; ++k) {
      if (k == 4) { if (!all) mbar_wait(B_W + 16 * q + 8, layer); wg_fence(); }
      wg_ss192(acc, da + k * 128, db + (k >> 2) * 1536 + (k & 3) * 128, 1);
    }
    wg_commit();
    if (q == 3) break;
    bar_arrive(e ? NB_T : NB_Q, 256);
    wg_wait<0>();
    mbar_arrive1(B_F + 8 * q);
  }
  const uint32_t ra = SM_STAT + 256 + (32 - 32 * e + 8 * w) * 16;
  float r0, r1;
  {
    if (!e) means(m, 64 + 16 * w, lane, layer, P.zero);
    PROF(28, m_sub);
    wg_fence();
    wg_rs192t(acc, m, mkdesc(SM_CS, 0, 32, 0));
    wg_commit();
    bar_arrive_if(NB_Q, 256, !e);
    r1 = lds1f(ra + 64 + (lane >> 3) * 16 + (lane & 4)); r0 = lds1f(ra + (lane >> 3) * 16 + (lane & 4));
    wg_wait<0>();
    mbar_arrive1(B_F + 24);
  }
  PROF(18, m_qkv);
  lane = opq(lane);
  const int g = lane >> 2, t = lane & 3;
  uint32_t Q[4][4], K[4][3][2], V[4][3][2];
  const int pos = 2 - 2 * e + (w >> 1);
  uint4 k0, k1, k2;
  {
    uint32_t pin = P.zero;
#pragma unroll
    for (int z = 0; z < 8; ++z) {
      K[z >> 1][2][z & 1] = pack2(acc[34 + 4 * z], acc[35 + 4 * z]);
      V[z >> 1][2][z & 1] = pack2(acc[66 + 4 * z], acc[67 + 4 * z]);
      K[z >> 1][1][z & 1] = pack2(acc[32 + 4 * z], acc[33 + 4 * z]);
      V[z >> 1][1][z & 1] = pack2(acc[64 + 4 * z], acc[65 + 4 * z]);
      pin &= K[z >> 1][1][z & 1] & V[z >> 1][1][z & 1];
    }
    if (pos == 3) {
      const uint32_t rk = pack2(r1, r1) | pin;
      uint4* h = P.S->H + ((c + 8) * 256 + (w & 1) * 128 + lane);
#pragma unroll
      for (int z = 0; z < 4; ++z) str4(h + z * 32, nz(hmul2(K[z][2][0], rk)), hmul2(K[z][2][1], rk), hmul2(V[z][2][0], rk), hmul2(V[z][2][1], rk));
      bar_arrive(NB_RL, 128);
    }
#pragma unroll
    for (int z = 0; z < 8; ++z) {
      V[z >> 1][2][z & 1] = movm(V[z >> 1][2][z & 1]);
    }
    const uint32_t kv = (w & 1) * 2048 + lane * 16;
    if (pos < 3) {
      mbar_wait(B_F + 16 + 8 * e, layer);
#pragma unroll
      for (int z = 0; z < 4; ++z) sts4(kvslot(cg, pos + 1) + kv + z * 512, K[z][2][0], K[z][2][1], V[z][2][0], V[z][2][1]);
      bar_arrive(NB_H + pos + 1, 128);
    }
    k0 = lds4(ra - 192 + 16 * t); k1 = lds4(ra + 16 * t); k2 = lds4(ra + 64 + 16 * t);
    PROF(19, m_kv);
#pragma unroll
    for (int z = 0; z < 8; ++z) {
      V[z >> 1][1][z & 1] = movm(V[z >> 1][1][z & 1]);
      Q[z >> 1][2 * (z & 1)] = pack2(acc[4 * z], acc[4 * z + 1]);
      Q[z >> 1][2 * (z & 1) + 1] = pack2(acc[4 * z + 2], acc[4 * z + 3]);
    }
    mbar_wait(B_F + 24, layer);
    bar_sync(NB_H + pos, 128);
#pragma unroll
    for (int z = 0; z < 4; ++z) {
      const uint4 hv = lds4(kvslot(cg, pos) + kv + z * 512);
      K[z][0][0] = hv.x; K[z][0][1] = hv.y; V[z][0][0] = hv.z; V[z][0][1] = hv.w;
    }
  }
  PROF(20, m_halo);
  const uint32_t ob = e ? SM_S1 : SM_XA;
  {
    const bool p0 = 2 * t > g, p1 = 2 * t + 1 > g, first = c < 8 && pos == 0;
    const uint32_t M = (p0 ? 0xFFFFu : 0u) | (p1 ? 0xFFFF0000u : 0u);
    const float sc0 = r0 * (0.25f * 1.4426950408889634f), sc1 = r1 * (0.25f * 1.4426950408889634f);
    const float sk[4] = {__uint_as_float(p0 ? k0.x : k1.x) * sc0, __uint_as_float(p1 ? k0.y : k1.y) * sc0,
                         __uint_as_float(p0 ? k1.x : k2.x) * sc1, __uint_as_float(p1 ? k1.y : k2.y) * sc1};
    const uint32_t rm[4] = {k0.z & M, k1.z & ~M, k1.z & M, k2.z & ~M}, s0 = k0.w | P.zero, s1 = k1.w | P.zero;
    const int oo = cg * 512 + (2 * (w & 2) + (w & 1)) * 64 + (lane ^ (g >> 1));
    uint4* O = P.S->O + (J * 4096 + oo);
#pragma unroll
    for (int h2 = 0; h2 < 2; ++h2) {
      uint32_t A[2], B[2], mx[2];
#pragma unroll
      for (int z = 0; z < 2; ++z) {
        const int h = 2 * h2 + z;
        float S[3][4];
#pragma unroll
        for (int n = 0; n < 3; ++n) mma16z(S[n], Q[h][0], Q[h][1], Q[h][2], Q[h][3], K[h][n][0], K[h][n][1]);
        if (first) { S[0][0] = __uint_as_float(0xFF800000u); S[0][1] = S[0][0]; }
        A[z] = pack2((p0 ? S[0][0] : S[1][0]) * sk[0], (p0 ? S[1][2] : S[2][2]) * sk[2]);
        B[z] = pack2((p1 ? S[0][1] : S[1][1]) * sk[1], (p1 ? S[1][3] : S[2][3]) * sk[3]);
      }
#pragma unroll
      for (int z = 0; z < 2; ++z) mx[z] = hmax2(A[z], B[z]);
#pragma unroll
      for (int z = 0; z < 2; ++z) mx[z] = hmax2(mx[z], __shfl_xor_sync(0xffffffffu, mx[z], 1));
#pragma unroll
      for (int z = 0; z < 2; ++z) mx[z] = hmax2(mx[z], __shfl_xor_sync(0xffffffffu, mx[z], 2));
      float Oa[2][3][4];
#pragma unroll
      for (int z = 0; z < 2; ++z) {
        const int h = 2 * h2 + z;
        const uint32_t a = hsub2(A[z], mx[z]), b = hsub2(B[z], mx[z]);
        const uint32_t w0 = pack2(ex2(bflo(a)), ex2(bflo(b))), w1 = pack2(ex2(bfhi(a)), ex2(bfhi(b)));
        const uint32_t u0 = hmul2(w0, rm[0]), u1 = hmul2(w0, rm[1]), u2 = hmul2(w1, rm[2]), u3 = hmul2(w1, rm[3]);
        const uint32_t z0 = w0 & P.zero, z1 = w1 & P.zero;
        mma16z(Oa[z][2], u0, z0, u1, u2, s0, s1);
#pragma unroll
        for (int d = 0; d < 2; ++d) mma16z(Oa[z][d], u0, z0, u1, u2, V[h][0][d], V[h][1][d]);
        mma8(Oa[z][2], z1, u3, k2.w);
#pragma unroll
        for (int d = 0; d < 2; ++d) mma8(Oa[z][d], z1, u3, V[h][2][d]);
      }
#pragma unroll
      for (int r = 0; r < 4; r += 2) {
        const float i0 = rcp(Oa[0][2][r]), i1 = rcp(Oa[1][2][r]);
        const uint32_t o0 = pack2(Oa[0][0][r] * i0, Oa[0][0][r + 1] * i0), o1 = pack2(Oa[0][1][r] * i0, Oa[0][1][r + 1] * i0);
        const uint32_t o2 = pack2(Oa[1][0][r] * i1, Oa[1][0][r + 1] * i1), o3 = pack2(Oa[1][1][r] * i1, Oa[1][1][r + 1] * i1);
        str4(O + h2 * 32 + r * 64, o0, o1, o2, o3);
        sts4(ob + oo * 16 + h2 * 512 + r * 1024, o0, o1, o2, o3);
      }
    }
  }
  bar_arrive(NB_T + 1 + e, 160);
  fence_async_smem();
  PROF(21, m_att);
  uint32_t res[8][2];
  mbar_wait(B_RES, layer);
  {
    const uint32_t a = SM_RES + e * 8192 + (lane >> 4) * 1024 + (lane & 7) * 128 + (((2 * (w & 2) + ((lane >> 2) & 2) + (w & 1)) ^ (lane & 7)) * 16);
#pragma unroll
    for (int j = 0; j < 8; j += 2) ldsm4t(res[j][0], res[j][1], res[j + 1][0], res[j + 1][1], a + j * 1024);
  }
  PROF(26, m_res);
  bar_sync(NB_WG + e, 128);
  XgAddr xa = xg_addr<true>(P.S->XG[1] + (64 * cg * 256 + 8 * J), ob, w, lane, P.zero);
  uint4* ps = &P.S->PS[((4 * J + w) * 8 + cg) * 8 + g];
  keep(ps, P.zero);
  if (layer) {
    xa.a = ob + w * 2048 + (lane & 15) * 128 + (((lane >> 4) ^ (lane & 7)) * 16);
    xa.b = ob + w * 2048 + (lane >> 3) * 128 + (((lane & 7) ^ (lane >> 3)) * 16);
    xa.dst = (uint4*)P.out + ((64 * J + 16 * w + 2 * (lane >> 3)) * 64 + 8 * cg + (lane & 7));
  }
  uint32_t y[8][2];
#pragma unroll 1
  for (int it = 0;; ++it) {
    float ac[32];
    zerov(ac);
#pragma unroll 1
    for (int n = 0; n < 8; ++n) {
      const int s = n == 0 ? cg : n - (n <= cg);
      mbar_wait(n ? B_O + 64 * e + 8 * s : B_WO, layer);
      if (n == 1) PROF(22, m_o1);
      if (n == 7) PROF(23, m_o7);
      const uint64_t da = mkdesc(ob + s * 8192, 16, 1024, 2), db = mkdesc(SM_R + s * 8192, 16, 1024, 1);
      wg_fence();
#pragma unroll
      for (int k = 0; k < 4; ++k) wg_ss64(ac, da + (k >> 1) * 32 + (k & 1) * 2, db + k * 128, 1);
      wg_commit();
    }
    wg_wait<0>();
    const bool bad = ac[0] != ac[0] || ac[2] != ac[2];
#pragma unroll
    for (int j = 0; j < 8; ++j) {
      y[j][0] = hadd2(res[j][0], pack2(ac[4 * j], ac[4 * j + 1]));
      y[j][1] = hadd2(res[j][1], pack2(ac[4 * j + 2], ac[4 * j + 3]));
    }
    if (!bar_any(NB_WG + e, 128, bad) || it == 16) break;
    EVENT(24 + 2 * layer + e);
    refetch(ob, P.S->O + J * 4096, 32768, e, w);
  }
  PROF(24, m_wo);
  if (layer == 0) {
    const float4 s = gram(y, g, P.zero);
    xg_put<true>(xa, y);
    str4_if(ps, nz(__float_as_uint(s.x)), __float_as_uint(s.y), __float_as_uint(s.z), __float_as_uint(s.w), t == (g >> 1));
    mbar_arrive1(B_ED + 8 * e);
    xg_store(xa, NB_WG + e);
    bar_arrive(NB_T + 3, 288);
  } else {
#pragma unroll
    for (int j = 0; j < 8; j += 2) stsm4(xa.a ^ (j * 16), y[j][0], y[j][1], y[j + 1][0], y[j + 1][1]);
    __syncwarp();
#pragma unroll
    for (int k = 0; k < 4; ++k) {
      const uint4 v = lds4((xa.b ^ ((k & 1) * 64)) + k * 512);
      stw4(xa.dst + ((k & 1) * 8 + (k >> 1)) * 64, v.x, v.y, v.z, v.w);
    }
  }
  PROF(25, m_epi);
}

#define HDELAY 300
#define ODELAY 200
#define PDELAY 500
#define FDELAY 200
#define WOQ 2
#define H5 1
#define SRDELAY 300
#define ZPACE 20

DEV void o_load(const Params& P, int c, int e, int lane, int layer) {
  PW(8 + e)
  const int J = 2 * (c >> 3) + 1 - e;
#pragma unroll 1
  for (int s = 0; s < 8; ++s) mbar_expect1(B_O + 64 * e + 8 * s, s == (c & 7) ? 0 : 8192);
  bar_sync(NB_T + 1 + e, 160);
  flag_set1(P.S->F + (J * 32 + 4 * (c & 7)));
  if (ODELAY) delay(ODELAY);
  PROF(26, a_go);
  poll(P.S->F + (J * 32 + (lane & 28)), 1);
  PROF(25, h_seen);
#pragma unroll 1
  for (int s = 0; s < 8; ++s)
    if (s != (c & 7)) bulk((e ? SM_S1 : SM_XA) + s * 8192, P.S->O + (J * 4096 + s * 512), 8192, B_O + 64 * e + 8 * s);
  PROF(28, a_o);
}

DEV void stats(const Params& P, int c, int w, int lane, int layer) {
  PW(12 + w)
  lane = opq(lane);
  const int r = (lane & 6) + ((lane >> 3) & 1), k = (2 * (c & 3) + (lane & 1)) ^ r, e = 1 - ((c >> 2) & 1);
  const uint32_t o = (32 * w + 8 * (lane >> 4) + r) * 128 + k * 16;
  const uint32_t mk = ((k & 1) == (r >> 2)) << (r & 3), tag = 1 - layer;
  float v[16];
#pragma unroll
  for (int z = 0; z < 16; ++z) v[z] = 0.f;
#pragma unroll 1
  for (int q = 0; q < 4; ++q) {
    mbar_wait(B_X + 16 * q + 8 * e, layer);
    PROF(19 + q, s_l);
    uint4 x, y;
    for (int it = 0;; ++it) {
      x = lds4v(xstage(q, e) + o); y = lds4v(xstage(q, e) + o + 2048);
      const uint32_t bad = (((x.x ^ tag) | (y.x ^ tag)) & mk) | (((x.y ^ tag) | (y.y ^ tag)) & (mk >> 1)) |
                           (((x.z ^ tag) | (y.z ^ tag)) & (mk >> 2)) | (((x.w ^ tag) | (y.w ^ tag)) & (mk >> 3));
      if (!__any_sync(0xffffffffu, bad & 1)) break;
      spin_guard(it);
    }
    mbar_arrive1(B_F + 8 * q);
    const uint32_t ws[8] = {x.x, x.y, x.z, x.w, y.x, y.y, y.z, y.w};
#pragma unroll
    for (int z = 0; z < 8; ++z) {
      const float lo = bflo(ws[z]), hi = bfhi(ws[z]);
      float* u = v + 4 * (z & 3);
      u[0] += lo; u[1] += lo * lo; u[2] += hi; u[3] += hi * hi;
    }
  }
  PROFD(14, s_part, __float_as_uint(v[0]));
  fold<8>(v, lane, 16); fold<4>(v, lane, 8); fold<2>(v, lane, 4); fold<1>(v, lane, 2);
  PROFD(16, s_fold, __float_as_uint(v[0]));
  if (w) {
    sts1(SM_MISC - 128 + w * 128 + lane * 4, __float_as_uint(v[0]));
    bar_arrive(NB_P, 128);
  } else {
    bar_sync(NB_P, 128);
    v[0] += lds1f(SM_MISC + lane * 4) + lds1f(SM_MISC + 128 + lane * 4) + lds1f(SM_MISC + 256 + lane * 4);
    float m;
    const float sd = ln_sd(v[0], __shfl_xor_sync(0xffffffffu, v[0], 2), m);
    if (!(lane & 2)) str1((uint32_t*)P.S->ST + (16 * c + 8 * (lane & 1) + (lane >> 2)), pack2(m, sd));
    sts4(SM_STAT + (lane & 15) * 16, 0x3F800000u, 0x3F800000u, 0x3F803F80u, 0x3F803F80u);
    fence_async_smem();
    PROF(17, s_pub);
    uint4 s;
    for (int it = 0;; ++it) {
      s = ldr4(P.S->ST + ((c >> 3) * 32 + lane));
      if (__all_sync(0xffffffffu, min4(s) != 0u)) break;
      spin_guard(it);
    }
    PROF(18, s_seen);
    const float r0 = rcp(bfhi(s.x)), r1 = rcp(bfhi(s.y)), r2 = rcp(bfhi(s.z)), r3 = rcp(bfhi(s.w));
    const uint32_t sg = 0x80008000u;
    sts4(SM_MISC + lane * 16, prmt(s.x, s.x, 0x1010) ^ sg, prmt(s.y, s.y, 0x1010) ^ sg, prmt(s.z, s.z, 0x1010) ^ sg, prmt(s.w, s.w, 0x1010) ^ sg);
    sts4(SM_STAT + 256 + lane * 32, __float_as_uint(r0), __float_as_uint(r1), pack2(r0, r1), prmt(s.x, s.y, 0x7632));
    sts4(SM_STAT + 272 + lane * 32, __float_as_uint(r2), __float_as_uint(r3), pack2(r2, r3), prmt(s.z, s.w, 0x7632));
    __syncwarp();
    mbar_arrive1(B_ST);
  }
  PROF(15, s_stat);
  if (w >= 2) {
    const uint4* h = P.S->H + (c * 256 + (w & 1) * 128 + lane);
    uint4 hv[4];
#pragma unroll
    for (int z = 0; z < 4; ++z) hv[z] = make_uint4(0, 0, 0, 0);
    bar_sync(NB_RL, 128);
    PROFD(26, s_hb, lds1v(SM_MISC));
    delay(HDELAY);
    for (int it = 0; c >= 8; ++it) {
#pragma unroll
      for (int z = 0; z < 4; ++z) hv[z] = ldr4(h + z * 32);
      if (__all_sync(0xffffffffu, min(min(hv[0].x, hv[1].x), min(hv[2].x, hv[3].x)) != 0u)) break;
      spin_guard(it);
    }
    mbar_wait(B_F + 24, layer);
#pragma unroll
    for (int z = 0; z < 4; ++z) sts4(kvslot(c & 7, 0) + (w & 1) * 2048 + lane * 16 + z * 512, hv[z].x, hv[z].y, movm(hv[z].z), movm(hv[z].w));
    bar_arrive(NB_H, 128);
    mbar_arrive1_if(B_ST + 8, w == 3);
    PROF(25, s_halo);
  }
}

DEV void finalize(const Params& P, int c, int lane, int layer) {
  PW(12)
  float z[4];
  if (layer == 0) {
    bar_sync(NB_P, 256);
    z[0] = z[1] = z[2] = z[3] = 0.f;
#pragma unroll
    for (int k = 0; k < 2; ++k) { const float4 a = lds4f(SM_RES + 8192 + k * 512 + lane * 16); z[0] += a.x; z[1] += a.y; z[2] += a.z; z[3] += a.w; }
  } else {
    mbar_wait(B_ED + 8 - 2 * (c & 4), 0);
    if (FDELAY) delay(FDELAY);
    const uint4* ps = &P.S->PS[c * 64 + lane];
    uint4 a, b;
    for (int it = 0;; ++it) {
      a = ldr4(ps); b = ldr4(ps + 32);
      if (__all_sync(0xffffffffu, min(a.x, b.x) != 0u)) break;
      spin_guard(it);
    }
    z[0] = __uint_as_float(a.x) + __uint_as_float(b.x); z[1] = __uint_as_float(a.y) + __uint_as_float(b.y);
    z[2] = __uint_as_float(a.z) + __uint_as_float(b.z); z[3] = __uint_as_float(a.w) + __uint_as_float(b.w);
  }
#pragma unroll
  for (int o = 8; o < 32; o <<= 1)
#pragma unroll
    for (int k = 0; k < 4; ++k) z[k] += __shfl_xor_sync(0xffffffffu, z[k], o);
  float m0, m1;
  const float r0 = rcp(ln_sd(z[0], z[1], m0)), r1 = rcp(ln_sd(z[2], z[3], m1));
  const uint32_t wr = nz(pack2(r0, r1)), wm = pack2(m0, m1);
  uint2* so = (uint2*)P.S->SR[layer] + ((lane >> 3) * 1024 + (lane & 2) * 256 + 4 * c + ((lane >> 1) & 2) + (lane & 1));
  str2(so, wr, wm); str2(so + 4096, wr, wm);
  if (!LATEF) bar_arrive_if(NB_Q, 448, !layer);
  PROF(23, s_sr);
}

DEV void announce(const Params& P, int c, int lane, int layer) {
  PW(13)
  bar_sync(NB_T + 3, 288);
  cnt_add(P, 5 * layer, c, lane);
  if (!LATEF) { bar_arrive_if(NB_Q, 448, !layer); fence_async_smem(); }
  PROF(24, s_own);
}

DEV void fetch(const Params& P, int c, int lane, int layer) {
  PW(13)
  mbar_expect1(B_E, 24576);
  cnt_wait(P, 5 * layer, c, lane);
#pragma unroll
  for (int k = 0; k < 4; ++k) bulk(SM_R + k * 16384 + R_B, P.S->XG[layer] + (128 * k + c) * 256, 4096, B_E);
  if (layer) delay(SRDELAY);
  bulk(SM_RES, P.S->SR[layer][c >> 4], 8192, B_E);
  if (!layer) { l2_prefetch(P.wqkv + c * 6144, 12288); l2_prefetch(P.wo + c * 2048, 4096); }
  PROF(25, s_all);
}

DEV void cs_part(const Params& P, int c, int w, int lane, int layer) {
  float cs[8];
#pragma unroll
  for (int k = 0; k < 8; ++k) cs[k] = 0.f;
  const int col = w * 512 + 64 * (c & 7) + 8 * (lane & 7);
#pragma unroll 1
  for (int r = 2 * layer; r < 2; ++r) {
    uint4 v[4];
#pragma unroll
    for (int k = 0; k < 4; ++k) v[k] = ldnc4(P.wqkv + ((32 * (c >> 3) + 16 * r + (lane >> 3)) * 1536 + col) + 4 * k * 1536);
#pragma unroll
    for (int k = 0; k < 4; ++k) {
      cs[0] += bflo(v[k].x); cs[1] += bfhi(v[k].x); cs[2] += bflo(v[k].y); cs[3] += bfhi(v[k].y);
      cs[4] += bflo(v[k].z); cs[5] += bfhi(v[k].z); cs[6] += bflo(v[k].w); cs[7] += bfhi(v[k].w);
    }
  }
  fold<4>(cs, lane, 16); fold<2>(cs, lane, 8);
  str2((float*)P.S->CS + ((c >> 3) * 1536 + col + 2 * (lane >> 3)), max(__float_as_uint(cs[0]), 1u - layer), __float_as_uint(cs[1]));
}

DEV void cs_sum(const Params& P, int c, int w, int lane) {
  float a, b;
  for (int it = 0;; ++it) {
    uint32_t m = ~0u;
    a = b = 0.f;
#pragma unroll
    for (int k = 0; k < 16; ++k) {
      const uint2 u = ldr2((const float*)P.S->CS + (w * 512 + 64 * (c & 7) + 2 * lane) + k * 1536);
      a += __uint_as_float(u.x); b += __uint_as_float(u.y); m = min(m, u.x);
    }
    if (__all_sync(0xffffffffu, m != 0u)) break;
    spin_guard(it);
  }
  const uint32_t hi = pack2(a, b), ad = SM_CS + w * 256 + (lane >> 2) * 32 + (lane & 3) * 4;
  sts1(ad, hi); sts1(ad + 16, pack2(a - bflo(hi), b - bfhi(hi)));
  fence_async_smem();
  __syncwarp();
  mbar_arrive1(B_CS);
}

DEV void x0_get(uint32_t (&x)[8][2], uint32_t a) {
  asm volatile("cp.async.wait_group 0;" ::: "memory");
#pragma unroll
  for (int z = 0; z < 4; ++z) {
    const uint4 v = lds4(a + z * 512);
    x[2 * (z & 2)][z & 1] = v.x; x[2 * (z & 2) + 1][z & 1] = v.y; x[2 * (z & 2) + 2][z & 1] = v.z; x[2 * (z & 2) + 3][z & 1] = v.w;
  }
}

DEV void par_load(const Params& P, int ch, int m, uint32_t (&pv)[8]) {
  const int mo = ch * 128 + m;
  pv[0] = ldnc16(P.Are + mo); pv[1] = ldnc16(P.Aim + mo); pv[2] = ldnc16(P.Bre + mo); pv[3] = ldnc16(P.Bim + mo);
  pv[4] = ldnc16(P.Cre + mo); pv[5] = ldnc16(P.Cim + mo); pv[6] = ldnc16(P.logdt + ch); pv[7] = ldnc16(P.dskip + ch);
}

__global__ void __launch_bounds__(NTHR, 1)
fused_kernel(const __grid_constant__ Params P, const __grid_constant__ CUtensorMap mapW,
             const __grid_constant__ CUtensorMap mapWo) {
  extern __shared__ __align__(1024) uint8_t smem_raw[];
  if (s2u(smem_raw) != SB) __trap();
  const int warp0 = __shfl_sync(0xffffffffu, threadIdx.x >> 5, 0), lane0 = threadIdx.x & 31;
  uint32_t smid; asm volatile("mov.u32 %0,%%smid;" : "=r"(smid));
  const int c = __shfl_sync(0xffffffffu, P.by_sm ? P.role[smid] : blockIdx.x, 0);
  if (c == 255) {
    if (threadIdx.x < NCOPY * NSUB)
#pragma unroll 1
      for (int it = 0; it < 256 && ldr1(P.S->C + 32 * threadIdx.x) < 128 / NSUB; ++it) __nanosleep(200);
    return;
  }
  const int cg = c & 7;
  PW(warp0)
  uint32_t dskip;
  {
    [[maybe_unused]] const int layer = 0;
    const int lane = lane0, g = lane >> 2, t = lane & 3, warp = warp0, k4 = warp >> 2, w = warp & 3;
    uint32_t pv[8];
    if (k4 < 2) par_load(P, 128 * k4 + c, 32 * w + lane, pv);
    else {
#pragma unroll
      for (int n = 0; n < 8; ++n) pv[n] = 0;
#pragma unroll
      for (int n = 0; n < 7; ++n) mbar_init1(SM_BAR + (n < 5 ? warp * 40 - 320 : 152 + warp * 16) + n * 8, n < 5 ? 1 : (CNT >> (4 * warp - 32)) & 15);
    }
    __syncthreads();
    const uint16_t* r = P.x0 + ((k4 < 2 ? 8192 * c + 64 * warp : (128 * (c >> 3) + 16 * (warp - 8)) * 512 + 64 * cg) + 1024 * g + 8 * t);
    const uint32_t xa = SM_R + k4 * 16384 + w * 2048 + lane * 16;
#pragma unroll
    for (int z = 0; z < 4; ++z) cp16(xa + z * 512, r + (z & 1) * 512 + (z & 2) * 16);
    asm volatile("cp.async.commit_group;" ::: "memory");
    sts4(SM_TAP + k4 * TAP_SZ + (32 * w + lane) * 16, 0, 0, 0, 0);
    sts4z_if(SM_TAP + k4 * TAP_SZ + 2048 + (32 * w + lane) * 16, w < 3);
    uint32_t x[8][2];
    if (k4 >= 2) {
      if (threadIdx.x == 448) {
        asm volatile("prefetch.tensormap [%0];" :: "l"(&mapW) : "memory");
        asm volatile("prefetch.tensormap [%0];" :: "l"(&mapWo) : "memory");
      }
      __syncwarp();
      if (PDELAY) delay(PDELAY);
      par_load(P, 128 * k4 + c, 32 * w + lane, pv);
      const XgAddr xd = xg_addr<false>(P.S->XG[0] + (64 * cg * 256 + 16 * (c >> 3) + 8 * (k4 - 2)), SM_R + k4 * 16384 + 8192, w, lane, P.zero);
      x0_get(x, xa);
      PROF(27, a_ld);
      xg_put<false>(xd, x);
      xg_store(xd, NB_WG + k4);
      bar_arrive(NB_T + 3, 288);
      bar_sync(NB_Q, 448 + 64 * LATEF);
    }
    tables(pv, k4, w, lane);
    if (k4 < 2) {
      x0_get(x, xa);
      const float4 s = gram(x, g, P.zero);
      if (t == (g >> 1)) sts4f(SM_RES + 8192 + (warp * 8 + g) * 16, s.x, s.y, s.z, s.w);
      __syncwarp();
      bar_arrive_if(NB_P, 256, warp != 7);
    }
    dskip = pv[7];
    PROF(1, a_x0);
  }
#pragma unroll 1
  for (int layer = 0; layer < 2; ++layer) {
    int lane = lane_here(P.zero);
    const int warp = warp0 | (layer & P.zero), k4 = warp >> 2, w = warp & 3;
    if (warp == (layer ? 12 : 7)) finalize(P, c, lane, layer);
    if (warp == (layer ? 13 : 6)) { announce(P, c, lane, layer); if (!LATEF) fetch(P, c, lane, layer); }
    if (layer == 0) {
      taps(dskip, k4, w, lane);
    }
    if (LATEF && warp == (layer ? 13 : 6)) fetch(P, c, lane, layer);
    conv(P, &mapW, c, k4, w, layer);
    lane = lane_here(P.zero);
    if (k4 < 2) {
      bar_arrive_if(NB_H, 160, !k4);
      if (warp == 0) {
        mbar_wait(B_K, 0);
        cnt_wait(P, 1 + 5 * layer, c, lane);
        x_load(P, c, 0, layer);
        PROF(27, m_xi);
      } else if (k4 == 0) cs_part(P, c, w - 1, lane, layer);
      attn_phase(P, c, k4, w, lane, layer);
    } else {
      bar_arrive_if(NB_RL, 256, warp >= 10);
      if (k4 == 3) {
        stats(P, c, w, lane, layer);
      } else if (w < 2) {
        bar_sync_if(NB_RL, 256, w);
        cnt_wait(P, 3 + 5 * layer + w, c, lane);
        bar_sync_if(NB_RL, 256, !w);
        if (w) mbar_wait(B_F, layer);
        x_load(P, c, 2 + w, layer);
        if (H5 && w) w_load(&mapW, cg, 5);
        PROF(14, h_xi);
        if (w == 1) str4(&P.S->SR[layer][lane >> 2][4 * c + (lane & 3)], 0, 0, 0, 0);
      } else if (w == 2) {
        mbar_expect1(B_WO, 65536);
        mbar_expect1(B_RES, 16384);
#pragma unroll 1
        for (int q = 0; q < 4; ++q) {
          mbar_wait(B_F + 8 * q, layer);
          if (q < 2) w_load(&mapW, cg, 4 + 2 * q);
          if (q == 1 || (q == 0 && !H5)) w_load(&mapW, cg, 5 + 2 * q);
          if (WOQ == 0 && ((q + 1) & 2)) tma5(SM_R + (q & 2) * 16384, &mapWo, 64 * cg, 4 * (q & 2), B_WO);
          if (WOQ && q == 2) {
            if (WOQ >= 2) mbar_wait(B_ST, layer);
            tma5(SM_R, &mapWo, 64 * cg, 0, B_WO);
            if (WOQ < 3) tma5(SM_R + 32768, &mapWo, 64 * cg, 8, B_WO);
          }
          if (WOQ == 3 && q == 2) { mbar_wait(B_ST + 8, layer); tma5(SM_R + 32768, &mapWo, 64 * cg, 8, B_WO); }
          if (q == 3) {
#pragma unroll
            for (int e = 0; e < 2; ++e) bulk(SM_RES + e * 8192, P.S->XF + ((2 * (c >> 3) + 1 - e) * 4096 + cg * 512), 8192, B_RES);
          }
          PROF(15 + q, h_w);
        }
      }
      if (k4 == 2 && w != 2) {
        if (layer == 0) cs_sum(P, c, w - (w >> 1), lane);
        if (w == 3) {
          uint4* xz = P.S->XG[layer] + (c * 256 + lane);
          mbar_wait(B_F, layer);
#pragma unroll 1
          for (int k = 0; k < 32; ++k) {
            str4(xz + ((k >> 3) * 32768 + (k & 7) * 32), 0, 0, 0, 0);
            if (ZPACE) __nanosleep(ZPACE);
          }
          PROF(19, h_z);
        }
      }
      if (warp < 10) o_load(P, c, w, lane, layer);
    }
    asm volatile("mov.b32 %0,0;" : "=r"(dskip));
  }
}

typedef CUresult (*EncodeFn)(CUtensorMap*, CUtensorMapDataType, cuuint32_t, void*, const cuuint64_t*, const cuuint64_t*,
                             const cuuint32_t*, const cuuint32_t*, CUtensorMapInterleave, CUtensorMapSwizzle,
                             CUtensorMapL2promotion, CUtensorMapFloatOOBfill);

static int place_roles(uint8_t* role) {
  int dev = 0, nsm = 0;
  cudaGetDevice(&dev);
  cudaDeviceGetAttribute(&nsm, cudaDevAttrMultiProcessorCount, dev);
  if (nsm < 128 || nsm > 144 || (nsm & 1)) return 0;
  cudaFuncSetAttribute(fused_kernel, cudaFuncAttributeNonPortableClusterSizeAllowed, 1);
  int occ[9] = {0};
  for (int k = 2; k <= 8; ++k) {
    cudaLaunchConfig_t cfg = {};
    cudaLaunchAttribute at[1];
    at[0].id = cudaLaunchAttributeClusterDimension;
    at[0].val.clusterDim.x = 2 * k; at[0].val.clusterDim.y = 1; at[0].val.clusterDim.z = 1;
    cfg.gridDim = dim3(2 * k); cfg.blockDim = dim3(NTHR); cfg.dynamicSmemBytes = SM_TOTAL; cfg.attrs = at; cfg.numAttrs = 1;
    if (cudaOccupancyMaxActiveClusters(&occ[k], fused_kernel, &cfg) != cudaSuccess) { cudaGetLastError(); occ[k] = 0; }
  }
  int n[10];
  n[7] = occ[8]; n[6] = occ[7]; n[5] = occ[6] - 0; n[4] = occ[5];
  n[3] = occ[4] - n[7]; n[1] = occ[2] - n[3] - n[5] - n[7]; n[0] = n[2] = n[1];
  n[8] = occ[3] - n[2] - n[5];
  const int ntpc = nsm / 2;
  int sum = 0;
  bool ok = n[0] > 0 && n[0] <= 8;
  for (int r = 0; r < 9; ++r) { ok = ok && n[r] >= 0 && (r == 0 || n[r] <= n[r - 1]); sum += n[r]; }
  if (!ok || sum > ntpc) { for (int r = 0; r < 9; ++r) n[r] = r < 8 ? 8 : 0; sum = 64; }
  int tp[8][9], cnt[8] = {0}, pool[72], np = 0, id = 0;
  for (int r = 0; r < 9; ++r)
    for (int g = n[0] - n[r]; g < n[0]; ++g) tp[g][cnt[g]++] = id++;
  for (; id < ntpc; ++id) pool[np++] = id;
  int order[72], no = 0;
  for (int g = 0; g < n[0]; ++g) {
    const int full = cnt[g] / 4 * 4;
    for (int k = 0; k < cnt[g]; ++k) { if (k < full) order[no++] = tp[g][k]; else pool[np++] = tp[g][k]; }
  }
  for (int k = 0; k < np; ++k) order[no++] = pool[k];
  for (int k = 0; k < 144; ++k) role[k] = 255;
  for (int k = 0; k < 64; ++k) { role[2 * order[k]] = 2 * k; role[2 * order[k] + 1] = 2 * k + 1; }
  return nsm;
}

extern "C" void kernel_launch(void* const* d_in, const int* in_sizes, int n_in, void* d_out, int out_size) {
  (void)in_sizes; (void)n_in; (void)out_size;
  static EncodeFn enc = nullptr;
  static uint8_t role[144];
  static int nsm = 0;
  static void* scratch = nullptr;
  if (!enc) {
    void* fn = nullptr;
    cudaDriverEntryPointQueryResult qr;
    cudaGetDriverEntryPoint("cuTensorMapEncodeTiled", &fn, cudaEnableDefault, &qr);
    enc = (EncodeFn)fn;
    cudaFuncSetAttribute(fused_kernel, cudaFuncAttributeMaxDynamicSharedMemorySize, SM_TOTAL);
    nsm = place_roles(role);
    cudaGetSymbolAddress(&scratch, g_S);
  }
  CUtensorMap mW, mWo;
  {
    cuuint64_t dim[3] = {512, 512, 3}, str[2] = {3072, 1024};
    cuuint32_t box[3] = {64, 64, 3}, es[3] = {1, 1, 1};
    enc(&mW, CU_TENSOR_MAP_DATA_TYPE_BFLOAT16, 3, d_in[10], dim, str, box, es, CU_TENSOR_MAP_INTERLEAVE_NONE,
        CU_TENSOR_MAP_SWIZZLE_128B, CU_TENSOR_MAP_L2_PROMOTION_NONE, CU_TENSOR_MAP_FLOAT_OOB_FILL_NONE);
  }
  {
    cuuint64_t dim[5] = {512, 2, 4, 4, 16}, str[4] = {1024, 8192, 2048, 32768};
    cuuint32_t box[5] = {64, 2, 4, 4, 8}, es[5] = {1, 1, 1, 1, 1};
    enc(&mWo, CU_TENSOR_MAP_DATA_TYPE_BFLOAT16, 5, d_in[11], dim, str, box, es, CU_TENSOR_MAP_INTERLEAVE_NONE,
        CU_TENSOR_MAP_SWIZZLE_128B, CU_TENSOR_MAP_L2_PROMOTION_NONE, CU_TENSOR_MAP_FLOAT_OOB_FILL_NONE);
  }
  Params P;
  P.x0 = (const uint16_t*)d_in[0]; P.Are = (const uint16_t*)d_in[1]; P.Aim = (const uint16_t*)d_in[2];
  P.Bre = (const uint16_t*)d_in[3]; P.Bim = (const uint16_t*)d_in[4]; P.Cre = (const uint16_t*)d_in[5];
  P.Cim = (const uint16_t*)d_in[6]; P.logdt = (const uint16_t*)d_in[7]; P.dskip = (const uint16_t*)d_in[8];
  P.wqkv = (const uint16_t*)d_in[10]; P.wo = (const uint16_t*)d_in[11]; P.out = (uint16_t*)d_out;
  for (int k = 0; k < 144; ++k) P.role[k] = role[k];
  P.by_sm = nsm > 0;
  P.zero = 0;
  P.S = (Scratch*)scratch;
  fused_kernel<<<nsm > 0 ? nsm : 128, NTHR, SM_TOTAL, cudaStreamPerThread>>>(P, mW, mWo);
}
```

```cpp
#include <cuda_runtime.h>
#include <cuda_bf16.h>
#include <cuda.h>
#include <stdint.h>

#define DEV __device__ __forceinline__

#define NCOPY 4
#define NSUB 1
#define EA 0x2221
constexpr int NTHR = 512;
constexpr int SPIN_LIMIT = 1 << 22;

constexpr uint32_t SB = 1024;
constexpr uint32_t SM_XA   = SB;
constexpr uint32_t SM_S0   = SM_XA + 16384;
constexpr uint32_t SM_S1   = SM_S0 + 49152;
constexpr uint32_t SM_XB   = SM_S1 + 49152;
constexpr uint32_t SM_R    = SM_XB + 16384;
constexpr uint32_t SM_RES  = SM_R + 65536;
constexpr uint32_t SM_TAP  = SM_RES + 16384;
constexpr int TAP_SZ = 3584;
constexpr uint32_t SM_CS   = SM_TAP + 4 * TAP_SZ;
constexpr uint32_t SM_STAT = SM_CS + 800;
constexpr uint32_t SM_MISC = SM_STAT + 1280;
constexpr uint32_t SM_BAR  = SM_MISC + 512;
constexpr int SM_TOTAL = SM_BAR + 448 - SB;
constexpr int R_U = 512, R_A5 = 5120, R_A3 = 8704, R_B = 11776;
constexpr int T_E = 1536, T_O = T_E + 1602, T_C = 3714;
constexpr uint32_t B_W = SM_BAR, B_X = SM_BAR + 64, B_O = SM_BAR + 128, B_WO = SM_BAR + 256, B_RES = SM_BAR + 264;
constexpr uint32_t B_ST = SM_BAR + 272, B_R = SM_BAR + 288, B_E = SM_BAR + 304;
constexpr uint32_t B_F = SM_BAR + 320, B_G = SM_BAR + 352, B_K = SM_BAR + 376, B_ED = SM_BAR + 384, B_CS = SM_BAR + 400, B_FH = SM_BAR + 416;
constexpr uint32_t CNT = 0x143444CC;
constexpr int NB_WG = 1, NB_T = 5, NB_Q = 10, NB_H = 11, NB_P = 14, NB_RL = 15;

struct Scratch {
  uint4    XG[2][512 * 256];
  uint4    XF[32 * 4096];
  uint4    O[32 * 8 * 512];
  uint32_t F[32 * 32];
  uint4    H[17 * 8 * 256];
  uint4    SR[2][8][512];
  uint4    ST[32 * 16];
  uint4    PS[128 * 64];
  float4   CS[16 * 1536 / 4];
  uint32_t C[10 * 32 * 32];
};
__device__ __align__(1024) Scratch g_S;

struct Params {
  int by_sm;
  uint32_t zero;
  Scratch* S;
  const uint16_t *x0, *Are, *Aim, *Bre, *Bim, *Cre, *Cim, *logdt, *dskip, *wqkv, *wo;
  uint16_t* out;
  uint8_t role[144];
};
#define EVENT(n) do {} while (0)
#define PROFD(slot, name, v) do {} while (0)
#define PROF(slot, name) do {} while (0)
#define PW(x)

DEV uint32_t s2u(const void* p) { return (uint32_t)__cvta_generic_to_shared(p); }
template <class T> DEV T opq(T x) { asm volatile("" : "+r"(x)); return x; }
DEV uint32_t pack2(float lo, float hi) { uint32_t d; asm("cvt.rn.bf16x2.f32 %0,%1,%2;" : "=r"(d) : "f"(hi), "f"(lo)); return d; }
DEV float bflo(uint32_t v) { return __uint_as_float(v << 16); }
DEV float bfhi(uint32_t v) { return __uint_as_float(v & 0xFFFF0000u); }
DEV float bfr(float x) { return bflo(pack2(x, 0.f)); }
DEV uint32_t hadd2(uint32_t a, uint32_t b) { uint32_t d; asm("add.rn.bf16x2 %0,%1,%2;" : "=r"(d) : "r"(a), "r"(b)); return d; }
DEV uint32_t hsub2(uint32_t a, uint32_t b) { uint32_t d; asm("sub.rn.bf16x2 %0,%1,%2;" : "=r"(d) : "r"(a), "r"(b)); return d; }
DEV uint32_t hmul2(uint32_t a, uint32_t b) { uint32_t d; asm("mul.rn.bf16x2 %0,%1,%2;" : "=r"(d) : "r"(a), "r"(b)); return d; }
DEV uint32_t hfma2(uint32_t a, uint32_t b, uint32_t c) { uint32_t d; asm("fma.rn.bf16x2 %0,%1,%2,%3;" : "=r"(d) : "r"(a), "r"(b), "r"(c)); return d; }
DEV uint32_t hmax2(uint32_t a, uint32_t b) { uint32_t d; asm("max.bf16x2 %0,%1,%2;" : "=r"(d) : "r"(a), "r"(b)); return d; }
DEV uint32_t prmt(uint32_t a, uint32_t b, uint32_t s) { uint32_t d; asm("prmt.b32 %0,%1,%2,%3;" : "=r"(d) : "r"(a), "r"(b), "r"(s)); return d; }
DEV uint32_t nz(uint32_t v) { uint32_t d; asm("max.u32 %0,%1,1;" : "=r"(d) : "r"(v)); return d; }
DEV uint32_t tagged(uint32_t v, uint32_t m, uint32_t tag) { return (v & ~m) | (tag & m); }
DEV uint32_t both(uint32_t a, uint32_t b, uint32_t x) { uint32_t d; asm("lop3.b32 %0,%1,%2,%3,0x42;" : "=r"(d) : "r"(a), "r"(b), "r"(x)); return d; }
DEV uint4 hadd8(const uint4& a, const uint4& b) { return make_uint4(hadd2(a.x, b.x), hadd2(a.y, b.y), hadd2(a.z, b.z), hadd2(a.w, b.w)); }
DEV uint32_t min4(const uint4& v) { return min(min(v.x, v.y), min(v.z, v.w)); }
DEV float rcp(float x) { float y; asm("rcp.approx.ftz.f32 %0,%1;" : "=f"(y) : "f"(x)); return y; }
DEV float sqrt_(float x) { float y; asm("sqrt.approx.ftz.f32 %0,%1;" : "=f"(y) : "f"(x)); return y; }
DEV float ex2(float x) { float y; asm("ex2.approx.ftz.f32 %0,%1;" : "=f"(y) : "f"(x)); return y; }

DEV uint4 ldr4(const void* p) { uint4 v; asm volatile("ld.relaxed.gpu.global.v4.u32 {%0,%1,%2,%3},[%4];" : "=r"(v.x), "=r"(v.y), "=r"(v.z), "=r"(v.w) : "l"(p) : "memory"); return v; }
DEV void ldr4_if(uint4& v, const void* p, bool c) {
  asm volatile("{.reg .pred q; setp.ne.u32 q,%5,0; @q ld.relaxed.gpu.global.v4.u32 {%0,%1,%2,%3},[%4];}"
    : "+r"(v.x), "+r"(v.y), "+r"(v.z), "+r"(v.w) : "l"(p), "r"((uint32_t)c) : "memory");
}
DEV uint2 ldr2(const void* p) { uint2 v; asm volatile("ld.relaxed.gpu.global.v2.u32 {%0,%1},[%2];" : "=r"(v.x), "=r"(v.y) : "l"(p) : "memory"); return v; }
DEV uint32_t ldr1(const void* p) { uint32_t v; asm volatile("ld.relaxed.gpu.global.u32 %0,[%1];" : "=r"(v) : "l"(p) : "memory"); return v; }
DEV void str4(void* p, uint32_t a, uint32_t b, uint32_t c, uint32_t d) { asm volatile("st.relaxed.gpu.global.v4.u32 [%0],{%1,%2,%3,%4};" :: "l"(p), "r"(a), "r"(b), "r"(c), "r"(d) : "memory"); }
DEV void str4_if(void* p, uint32_t a, uint32_t b, uint32_t c, uint32_t d, bool q) {
  asm volatile("{.reg .pred q; setp.ne.u32 q,%5,0; @q st.relaxed.gpu.global.v4.u32 [%0],{%1,%2,%3,%4};}" :: "l"(p), "r"(a), "r"(b), "r"(c), "r"(d), "r"((uint32_t)q) : "memory");
}
DEV void str2(void* p, uint32_t a, uint32_t b) { asm volatile("st.relaxed.gpu.global.v2.u32 [%0],{%1,%2};" :: "l"(p), "r"(a), "r"(b) : "memory"); }
DEV void str1(void* p, uint32_t a) { asm volatile("st.relaxed.gpu.global.u32 [%0],%1;" :: "l"(p), "r"(a) : "memory"); }
DEV void stw4(void* p, uint32_t a, uint32_t b, uint32_t c, uint32_t d) { asm volatile("st.global.v4.u32 [%0],{%1,%2,%3,%4};" :: "l"(p), "r"(a), "r"(b), "r"(c), "r"(d) : "memory"); }
DEV uint4 ldnc4(const void* p) { uint4 v; asm volatile("ld.global.nc.v4.u32 {%0,%1,%2,%3},[%4];" : "=r"(v.x), "=r"(v.y), "=r"(v.z), "=r"(v.w) : "l"(p)); return v; }
DEV uint4 ldw4(const void* p) { uint4 v; asm volatile("ld.global.v4.u32 {%0,%1,%2,%3},[%4];" : "=r"(v.x), "=r"(v.y), "=r"(v.z), "=r"(v.w) : "l"(p) : "memory"); return v; }
DEV void cp16(uint32_t d, const void* p) { asm volatile("cp.async.cg.shared.global [%0],[%1],16;" :: "r"(d), "l"(p) : "memory"); }
DEV uint32_t ldnc16(const void* p) { uint32_t v; asm volatile("ld.global.u16 %0,[%1];" : "=r"(v) : "l"(p) : "memory"); return v; }

DEV uint32_t lds1v(uint32_t a) { uint32_t v; asm volatile("ld.volatile.shared.u32 %0,[%1];" : "=r"(v) : "r"(a) : "memory"); return v; }
DEV uint4 lds4v(uint32_t a) { uint4 v; asm volatile("ld.volatile.shared.v4.u32 {%0,%1,%2,%3},[%4];" : "=r"(v.x), "=r"(v.y), "=r"(v.z), "=r"(v.w) : "r"(a) : "memory"); return v; }
DEV uint32_t lds1(uint32_t a) { uint32_t v; asm volatile("ld.shared.u32 %0,[%1];" : "=r"(v) : "r"(a)); return v; }
DEV uint2 lds2(uint32_t a) { uint2 v; asm volatile("ld.shared.v2.u32 {%0,%1},[%2];" : "=r"(v.x), "=r"(v.y) : "r"(a)); return v; }
DEV uint4 lds4(uint32_t a) { uint4 v; asm volatile("ld.shared.v4.u32 {%0,%1,%2,%3},[%4];" : "=r"(v.x), "=r"(v.y), "=r"(v.z), "=r"(v.w) : "r"(a)); return v; }
DEV uint32_t lds16(uint32_t a) { uint32_t v; asm volatile("ld.shared.u16 %0,[%1];" : "=r"(v) : "r"(a)); return v; }
DEV float lds1f(uint32_t a) { float v; asm volatile("ld.shared.f32 %0,[%1];" : "=f"(v) : "r"(a)); return v; }
DEV float2 lds2f(uint32_t a) { float2 v; asm volatile("ld.shared.v2.f32 {%0,%1},[%2];" : "=f"(v.x), "=f"(v.y) : "r"(a)); return v; }
DEV float4 lds4f(uint32_t a) { float4 v; asm volatile("ld.shared.v4.f32 {%0,%1,%2,%3},[%4];" : "=f"(v.x), "=f"(v.y), "=f"(v.z), "=f"(v.w) : "r"(a)); return v; }
DEV void sts1(uint32_t a, uint32_t v) { asm volatile("st.shared.u32 [%0],%1;" :: "r"(a), "r"(v) : "memory"); }
DEV void sts16(uint32_t a, uint32_t v) { asm volatile("{.reg .b16 h; cvt.u16.u32 h,%1; st.shared.u16 [%0],h;}" :: "r"(a), "r"(v) : "memory"); }
DEV void sts2f(uint32_t a, float x, float y) { asm volatile("st.shared.v2.f32 [%0],{%1,%2};" :: "r"(a), "f"(x), "f"(y) : "memory"); }
DEV void sts4f(uint32_t a, float x, float y, float z, float w) { asm volatile("st.shared.v4.f32 [%0],{%1,%2,%3,%4};" :: "r"(a), "f"(x), "f"(y), "f"(z), "f"(w) : "memory"); }
DEV void sts4(uint32_t a, uint32_t x, uint32_t y, uint32_t z, uint32_t w) { asm volatile("st.shared.v4.u32 [%0],{%1,%2,%3,%4};" :: "r"(a), "r"(x), "r"(y), "r"(z), "r"(w) : "memory"); }
DEV void sts4z_if(uint32_t a, bool c) { asm volatile("{.reg .pred q; setp.ne.u32 q,%1,0; @q st.shared.v4.u32 [%0],{%2,%2,%2,%2};}" :: "r"(a), "r"((uint32_t)c), "r"(0) : "memory"); }

DEV void ldsm4t(uint32_t& r0, uint32_t& r1, uint32_t& r2, uint32_t& r3, uint32_t a) { asm volatile("ldmatrix.sync.aligned.m8n8.x4.trans.shared.b16 {%0,%1,%2,%3},[%4];" : "=r"(r0), "=r"(r1), "=r"(r2), "=r"(r3) : "r"(a) : "memory"); }
DEV void stsm4(uint32_t a, uint32_t r0, uint32_t r1, uint32_t r2, uint32_t r3) { asm volatile("stmatrix.sync.aligned.m8n8.x4.shared.b16 [%0],{%1,%2,%3,%4};" :: "r"(a), "r"(r0), "r"(r1), "r"(r2), "r"(r3) : "memory"); }
DEV void stsm2(uint32_t a, uint32_t r0, uint32_t r1) { asm volatile("stmatrix.sync.aligned.m8n8.x2.shared.b16 [%0],{%1,%2};" :: "r"(a), "r"(r0), "r"(r1) : "memory"); }
DEV void stsm4t(uint32_t a, uint32_t r0, uint32_t r1, uint32_t r2, uint32_t r3) { asm volatile("stmatrix.sync.aligned.m8n8.x4.trans.shared.b16 [%0],{%1,%2,%3,%4};" :: "r"(a), "r"(r0), "r"(r1), "r"(r2), "r"(r3) : "memory"); }
DEV uint32_t movm(uint32_t a) { uint32_t d; asm volatile("movmatrix.sync.aligned.m8n8.trans.b16 %0,%1;" : "=r"(d) : "r"(a)); return d; }
DEV void mma16(float (&d)[4], uint32_t a0, uint32_t a1, uint32_t a2, uint32_t a3, uint32_t b0, uint32_t b1) {
  asm volatile("mma.sync.aligned.m16n8k16.row.col.f32.bf16.bf16.f32 {%0,%1,%2,%3},{%4,%5,%6,%7},{%8,%9},{%0,%1,%2,%3};"
    : "+f"(d[0]), "+f"(d[1]), "+f"(d[2]), "+f"(d[3]) : "r"(a0), "r"(a1), "r"(a2), "r"(a3), "r"(b0), "r"(b1));
}
DEV void mma16z(float (&d)[4], uint32_t a0, uint32_t a1, uint32_t a2, uint32_t a3, uint32_t b0, uint32_t b1) {
  asm volatile("mma.sync.aligned.m16n8k16.row.col.f32.bf16.bf16.f32 {%0,%1,%2,%3},{%4,%5,%6,%7},{%8,%9},{%10,%10,%10,%10};"
    : "=f"(d[0]), "=f"(d[1]), "=f"(d[2]), "=f"(d[3]) : "r"(a0), "r"(a1), "r"(a2), "r"(a3), "r"(b0), "r"(b1), "f"(0.f));
}
DEV void mma8z(float (&d)[4], uint32_t a0, uint32_t a1, uint32_t b0) {
  asm volatile("mma.sync.aligned.m16n8k8.row.col.f32.bf16.bf16.f32 {%0,%1,%2,%3},{%4,%5},{%6},{%7,%7,%7,%7};"
    : "=f"(d[0]), "=f"(d[1]), "=f"(d[2]), "=f"(d[3]) : "r"(a0), "r"(a1), "r"(b0), "f"(0.f));
}
DEV void mma8(float (&d)[4], uint32_t a0, uint32_t a1, uint32_t b0) {
  asm volatile("mma.sync.aligned.m16n8k8.row.col.f32.bf16.bf16.f32 {%0,%1,%2,%3},{%4,%5},{%6},{%0,%1,%2,%3};"
    : "+f"(d[0]), "+f"(d[1]), "+f"(d[2]), "+f"(d[3]) : "r"(a0), "r"(a1), "r"(b0));
}

DEV void bar_sync(int id, int n) { asm volatile("bar.sync %0,%1;" :: "r"(id), "r"(n) : "memory"); }
DEV void bar_arrive(int id, int n) { asm volatile("bar.arrive %0,%1;" :: "r"(id), "r"(n) : "memory"); }
DEV void bar_sync_if(int id, int n, int c) { asm volatile("{.reg .pred q; setp.ne.s32 q,%2,0; @q bar.sync %0,%1;}" :: "r"(id), "r"(n), "r"(c) : "memory"); }
DEV void bar_arrive_if(int id, int n, int c) { asm volatile("{.reg .pred q; setp.ne.s32 q,%2,0; @q bar.arrive %0,%1;}" :: "r"(id), "r"(n), "r"(c) : "memory"); }
DEV bool bar_any(int id, int n, bool c) {
  uint32_t r; asm volatile("{.reg .pred p,q; setp.ne.u32 q,%3,0; bar.red.or.pred p,%1,%2,q; selp.u32 %0,1,0,p;}" : "=r"(r) : "r"(id), "r"(n), "r"((uint32_t)c) : "memory");
  return __any_sync(0xffffffffu, r);
}
DEV void fence_async_glob() { asm volatile("fence.proxy.async.global;" ::: "memory"); }
DEV void fence_async_smem() { asm volatile("fence.proxy.async.shared::cta;" ::: "memory"); }
DEV void fence_gpu() { asm volatile("fence.acq_rel.gpu;" ::: "memory"); }
DEV void mbar_wait(uint32_t b, uint32_t ph) {
  asm volatile("{\n.reg .pred p;\nW: mbarrier.try_wait.parity.shared::cta.b64 p,[%0],%1;\n@!p bra W;\n}" :: "r"(b), "r"(ph) : "memory");
}
DEV bool mbar_test(uint32_t b, uint32_t ph) {
  uint32_t r; asm volatile("{.reg .pred p; mbarrier.test_wait.parity.shared::cta.b64 p,[%1],%2; selp.u32 %0,1,0,p;}" : "=r"(r) : "r"(b), "r"(ph) : "memory");
  return __all_sync(0xffffffffu, r);
}
DEV uint32_t mbar_test2(uint32_t b, uint32_t ph) {
  uint32_t r; asm volatile("{.reg .pred p,q; mbarrier.test_wait.parity.shared::cta.b64 p,[%1],%2; mbarrier.test_wait.parity.shared::cta.b64 q,[%1+8],%2;\n"
                           "and.pred p,p,q; selp.u32 %0,1,0,p;}" : "=r"(r) : "r"(b), "r"(ph) : "memory");
  return r;
}
DEV void spin_guard(int it) { asm volatile("{.reg .pred p; setp.gt.s32 p,%0,%1; @p trap;}" :: "r"(it), "n"(SPIN_LIMIT)); }
DEV uint32_t here(uint32_t zero) {
  uint32_t d; asm volatile("mov.u32 %0,%%clock;" : "=r"(d) :: "memory"); return d & zero;
}
DEV int lane_here(uint32_t zero) {
  uint32_t d; asm volatile("mov.u32 %0,%%laneid;" : "=r"(d)); return d | here(zero);
}
DEV void delay(uint32_t n) { const uint32_t t0 = clock(); while ((uint32_t)clock() - t0 < n); __syncwarp(); }
DEV void poll(const uint32_t* p, uint32_t n) {
  for (int it = 0; !__all_sync(0xffffffffu, ldr1(p) >= n); ++it) spin_guard(it);
}
DEV void cnt_add(const Params& P, int n, int c, int lane) { asm volatile("{.reg .pred p; setp.lt.s32 p,%1,%2; @p red.relaxed.gpu.global.add.u32 [%0],1;}" :: "l"(P.S->C + (32 * (NSUB * lane + c % NSUB) + n * 1024)), "r"(lane), "n"(NCOPY) : "memory"); }
DEV void cnt_wait(const Params& P, int n, int c, int lane) { poll(P.S->C + (32 * (NSUB * (c / (128 / NCOPY)) + lane % NSUB) + n * 1024), 128 / NSUB); }
DEV void mbar_init1(uint32_t b, int n) { asm volatile("{.reg .pred p; elect.sync _|p,0xffffffff; @p mbarrier.init.shared::cta.b64 [%0],%1;}" :: "r"(b), "r"(n) : "memory"); }
DEV void mbar_arrive1(uint32_t b) { asm volatile("{.reg .pred p; elect.sync _|p,0xffffffff; @p mbarrier.arrive.shared::cta.b64 _,[%0];}" :: "r"(b) : "memory"); }
DEV void mbar_arrive1_if(uint32_t b, int c) {
  asm volatile("{.reg .pred p,q; setp.ne.s32 q,%1,0; elect.sync _|p,0xffffffff; and.pred p,p,q; @p mbarrier.arrive.shared::cta.b64 _,[%0];}" :: "r"(b), "r"(c) : "memory");
}
DEV void mbar_expect1(uint32_t b, int bytes) { asm volatile("{.reg .pred p; elect.sync _|p,0xffffffff; @p mbarrier.arrive.expect_tx.shared::cta.b64 _,[%0],%1;}" :: "r"(b), "r"(bytes) : "memory"); }
DEV void flag_set1(uint32_t* q) { asm volatile("{.reg .pred p; elect.sync _|p,0xffffffff; @p st.relaxed.gpu.global.u32 [%0],1;}" :: "l"(q) : "memory"); }
DEV void tma3(uint32_t dst, const CUtensorMap* m, int c0, int c1, uint32_t bar) {
  asm volatile("{.reg .pred p; elect.sync _|p,0xffffffff;\n"
    "@p cp.async.bulk.tensor.3d.shared::cluster.global.mbarrier::complete_tx::bytes [%0],[%1,{%2,%3,%5}],[%4];}"
    :: "r"(dst), "l"(m), "r"(c0), "r"(c1), "r"(bar), "r"(0) : "memory");
}
DEV void tma5(uint32_t dst, const CUtensorMap* m, int c0, int c4, uint32_t bar) {
  asm volatile("{.reg .pred p; elect.sync _|p,0xffffffff;\n"
    "@p cp.async.bulk.tensor.5d.shared::cluster.global.mbarrier::complete_tx::bytes [%0],[%1,{%2,%5,%5,%5,%3}],[%4];}"
    :: "r"(dst), "l"(m), "r"(c0), "r"(c4), "r"(bar), "r"(0) : "memory");
}
DEV void bulk(uint32_t dst, const void* src, int bytes, uint32_t bar) {
  asm volatile("{.reg .pred p; elect.sync _|p,0xffffffff;\n@p cp.async.bulk.shared::cluster.global.mbarrier::complete_tx::bytes [%0],[%1],%2,[%3];}" :: "r"(dst), "l"(src), "r"(bytes), "r"(bar) : "memory");
}
DEV void bulk_store(void* dst, uint32_t src, int bytes) {
  asm volatile("{.reg .pred p; elect.sync _|p,0xffffffff;\n@p cp.async.bulk.global.shared::cta.bulk_group [%0],[%1],%2;}" :: "l"(dst), "r"(src), "r"(bytes) : "memory");
}
DEV void l2_prefetch(const void* src, int bytes) {
  asm volatile("{.reg .pred p; elect.sync _|p,0xffffffff;\n@p cp.async.bulk.prefetch.L2.global [%0],%1;}" :: "l"(src), "r"(bytes) : "memory");
}

DEV uint64_t mkdesc(uint32_t addr, uint32_t lbo, uint32_t sbo, uint32_t swz) {
  return (uint64_t)((addr >> 4) | ((lbo >> 4) << 16)) | ((uint64_t)((sbo >> 4) | (swz << 30)) << 32);
}
DEV void wg_fence() { asm volatile("wgmma.fence.sync.aligned;" ::: "memory"); }
DEV void wg_commit() { asm volatile("wgmma.commit_group.sync.aligned;" ::: "memory"); }
template <int N> DEV void wg_wait() { asm volatile("wgmma.wait_group.sync.aligned %0;" :: "n"(N) : "memory"); }
template <int N> DEV void zerov(float (&d)[N]) {
#pragma unroll
  for (int i = 0; i < N; ++i) asm volatile("mov.b32 %0,0;" : "=f"(d[i]));
}
template <int N> DEV void undef(float (&d)[N]) {
#pragma unroll
  for (int i = 0; i < N; ++i) asm volatile("" : "=f"(d[i]));
}
#define R4(d, o) "+f"(d[o]), "+f"(d[o + 1]), "+f"(d[o + 2]), "+f"(d[o + 3])
#define R8(d, o) R4(d, o), R4(d, o + 4)
#define R16(d, o) R8(d, o), R8(d, o + 8)
#define R32(d, o) R16(d, o), R16(d, o + 16)
#define L0 "%0,%1,%2,%3,%4,%5,%6,%7,%8,%9,"
#define L10(a) "%" #a "0,%" #a "1,%" #a "2,%" #a "3,%" #a "4,%" #a "5,%" #a "6,%" #a "7,%" #a "8,%" #a "9,"
#define WG_HEAD(pr, n) "{.reg .pred p; setp.ne.s32 p,%" #pr ",0;\nwgmma.mma_async.sync.aligned.m64n" #n "k16.f32.bf16.bf16 {"
DEV void wg_rs64k(float (&d)[32], const uint32_t (&a)[4], uint64_t db, int acc) {
  asm volatile(WG_HEAD(37, 64) L0 L10(1) L10(2) "%30,%31},{%32,%33,%34,%35},%36,p,1,1,0;}"
    : R32(d, 0) : "r"(a[0]), "r"(a[1]), "r"(a[2]), "r"(a[3]), "l"(db), "r"(acc));
}
DEV void wg_rs48t(float (&d)[24], const uint32_t (&a)[4], uint64_t db, int acc) {
  asm volatile(WG_HEAD(29, 48) L0 L10(1) "%20,%21,%22,%23},{%24,%25,%26,%27},%28,p,1,1,1;}"
    : R16(d, 0), R8(d, 16) : "r"(a[0]), "r"(a[1]), "r"(a[2]), "r"(a[3]), "l"(db), "r"(acc));
}
DEV void wg_rs32t(float (&d)[16], const uint32_t (&a)[4], uint64_t db, int acc) {
  asm volatile(WG_HEAD(21, 32) L0 "%10,%11,%12,%13,%14,%15},{%16,%17,%18,%19},%20,p,1,1,1;}"
    : R16(d, 0) : "r"(a[0]), "r"(a[1]), "r"(a[2]), "r"(a[3]), "l"(db), "r"(acc));
}
DEV void wg_ss48(float (&d)[24], uint64_t da, uint64_t db, int acc) {
  asm volatile(WG_HEAD(26, 48) L0 L10(1) "%20,%21,%22,%23},%24,%25,p,1,1,1,1;}" : R16(d, 0), R8(d, 16) : "l"(da), "l"(db), "r"(acc));
}
DEV void wg_ss64(float (&d)[32], uint64_t da, uint64_t db, int acc) {
  asm volatile(WG_HEAD(34, 64) L0 L10(1) L10(2) "%30,%31},%32,%33,p,1,1,0,1;}" : R32(d, 0) : "l"(da), "l"(db), "r"(acc));
}
DEV void wg_ss192(float (&d)[96], uint64_t da, uint64_t db, int acc) {
  asm volatile(WG_HEAD(98, 192) L0 L10(1) L10(2) L10(3) L10(4) L10(5) L10(6) L10(7) L10(8) "%90,%91,%92,%93,%94,%95},%96,%97,p,1,1,1,1;}"
    : R32(d, 0), R32(d, 32), R32(d, 64) : "l"(da), "l"(db), "r"(acc));
}

DEV void wg_rs192t(float (&d)[96], const uint32_t (&a)[4], uint64_t db) {
  asm volatile("wgmma.mma_async.sync.aligned.m64n192k16.f32.bf16.bf16 {" L0 L10(1) L10(2) L10(3) L10(4) L10(5) L10(6) L10(7) L10(8) "%90,%91,%92,%93,%94,%95},{%96,%97,%98,%99},%100,1,1,1,1;"
    : R32(d, 0), R32(d, 32), R32(d, 64) : "r"(a[0]), "r"(a[1]), "r"(a[2]), "r"(a[3]), "l"(db));
}

DEV float ln_sd(float s, float q, float& m) {
  m = s * (1.f / 512.f);
  return bfr(sqrt_(bfr(bfr(fmaxf(q * (1.f / 512.f) - m * m, 0.f)) + 1e-5f)));
}
DEV float4 gram(const uint32_t (&w)[8][2], int g, uint32_t zero) {
  float s[4], q[4][4];
  const uint32_t o0 = 0x3F803F80u | zero, o1 = 0x3F803F80u ^ zero;
#pragma unroll
  for (int j = 0; j < 8; ++j) {
#pragma unroll
    for (int h = 0; h < 2; ++h) { if (j < 2) mma8z(q[2 * j + h], w[j][0], w[j][1], w[j][h]); else mma8(q[2 * (j & 1) + h], w[j][0], w[j][1], w[j][h]); }
    if (j == 1) mma16z(s, w[0][0], w[0][1], w[1][0], w[1][1], o0, o1);
    else if (j & 1) mma16(s, w[j - 1][0], w[j - 1][1], w[j][0], w[j][1], o0, o1);
  }
  const bool od = g & 1;
  return make_float4(s[0], od ? q[0][1] + q[2][1] : q[0][0] + q[2][0], s[2], od ? q[1][3] + q[3][3] : q[1][2] + q[3][2]);
}
DEV void keep(uint32_t v, uint32_t zero) {
  asm volatile("{.reg .pred p; setp.ne.u32 p,%1,0; @p st.shared.u32 [%0],%0;}" :: "r"(v), "r"(zero) : "memory");
}
DEV void keep(const void* v, uint32_t zero) { asm volatile("{.reg .pred p; setp.ne.u32 p,%1,0; @p st.global.u32 [%0],%1;}" :: "l"(v), "r"(zero) : "memory"); }
struct XgAddr { uint32_t a, b; uint4* dst; };
template <bool FRAG> DEV XgAddr xg_addr(uint4* dst, uint32_t stg, int wp, int lane, uint32_t zero) {
  const int t = lane & 3, r = 4 * wp + (lane >> 3);
  XgAddr x = {stg + t * (FRAG ? 256 : 1024) + ((wp ^ t) * 32) + (lane >> 2) * 4,
              stg + r * 128 + (((lane & 7) ^ (2 * (((r >> 1) ^ (r >> 3)) & 3))) * 16), dst + (r * 256 + (lane & 7))};
  keep(x.a, zero); keep(x.b, zero); keep(x.dst, zero);
  return x;
}
template <bool FRAG> DEV void xg_put(const XgAddr& x, const uint32_t (&w)[8][2]) {
#pragma unroll
  for (int n = 0; n < 8; ++n) {
    const uint32_t b = (x.a ^ ((n & 3) * 32)) + (FRAG ? n * 1024 : (n >> 2) * 4096 + (n & 3) * 256);
    sts1(b, prmt(w[n][0], w[n][1], 0x5410)); sts1(b + 128, prmt(w[n][0], w[n][1], 0x7632));
  }
}
DEV void xg_store(const XgAddr& x, int nb) {
  bar_sync(nb, 128);
#pragma unroll
  for (int k = 0; k < 4; ++k) {
    const uint4 v = lds4((x.b ^ ((k & 1) * 64)) + k * 2048);
    str4(x.dst + k * 4096, nz(v.x), v.y, v.z, v.w);
  }
}
template <int N, int M> DEV void fold(float (&v)[M], int lane, int bit) {
  const bool b = lane & bit;
#pragma unroll
  for (int k = 0; k < N; ++k) { const float sn = b ? v[k] : v[k + N], kp = b ? v[k + N] : v[k]; v[k] = kp + __shfl_xor_sync(0xffffffffu, sn, bit); }
}
DEV void refetch(uint32_t dst, const uint4* src, int half, int e, int w) {
#pragma unroll 1
  for (int r = 0; r < 2; ++r) {
    if (w == 0) { mbar_expect1(B_R + 8 * e, half); bulk(dst + r * half, src + r * (half >> 4), half, B_R + 8 * e); }
    mbar_wait(B_R + 8 * e, r);
    bar_sync(NB_WG + e, 128);
  }
}
DEV uint32_t kvslot(int cg, int pos) { return (pos & 2 ? SM_XA : SM_S1) + (cg < 4 ? 5 : 2) * 8192 + (pos & 1) * 4096; }
DEV uint32_t xstage(int q, int e) { return ((q + 1) & 2) ? SM_R + ((q & 2) + e) * 16384 : e ? SM_XB : SM_XA; }
DEV void cmul(float& orr, float& oi, float ar, float ai, float br, float bi) {
  float r = ar * br - ai * bi, i = ar * bi + ai * br; orr = r; oi = i;
}
DEV void cexp_(float al, float bt, float s, float& er, float& ei) {
  float mag = ex2(al * s), ph = bt * s;
  ph -= rintf(ph);
  float ang = ph * 6.283185307179586f;
  er = mag * __cosf(ang); ei = mag * __sinf(ang);
}

#define KS 2048
#define LATEF 0
DEV void put8(uint32_t a, const float (&r)[8], const float (&i)[8]) {
  sts4(a, pack2(r[0], r[1]), pack2(r[2], r[3]), pack2(r[4], r[5]), pack2(r[6], r[7]));
  sts4(a + 1024, pack2(i[0], i[1]), pack2(i[2], i[3]), pack2(i[4], i[5]), pack2(i[6], i[7]));
}
DEV void tables(const uint32_t (&pv)[8], int k4, int w, int lane) {
  PW(4 * k4 + w)
  [[maybe_unused]] const int layer = 0;
  const float dt = bfr(__expf(bflo(pv[6])));
  const float al = dt * bflo(pv[0]) * 1.4426950408889634f, bt = dt * bflo(pv[1]) * 0.15915494309189535f;
  float qr[8], qi[8], yr[8], yi[8];
  cmul(qr[0], qi[0], bflo(pv[4]), bflo(pv[5]), dt * bflo(pv[2]), dt * bflo(pv[3]));
  PROFD(2, a_par, __float_as_uint(qr[0] + al + bt));
  float e1r, e1i, eMr, eMi, eLr, eLi;
  cexp_(al, bt, 1.f, e1r, e1i); cexp_(al, -bt, 8.f, yr[1], yi[1]); cexp_(al, -bt, 64.f, eMr, eMi); cexp_(al, bt, 256.f, eLr, eLi);
  const uint32_t ad = SB + k4 * 32768 + (w & 1) * 512 + lane * 16, am = ad + (w >> 1) * KS, an = ad + (8 + 3 * (w >> 1)) * KS;
  yr[0] = 1.f; yi[0] = 0.f;
#pragma unroll
  for (int k = 1; k < 8; ++k) {
    cmul(qr[k], qi[k], qr[k - 1], qi[k - 1], e1r, e1i);
    if (k > 1) cmul(yr[k], yi[k], yr[k - 1], yi[k - 1], yr[1], yi[1]);
  }
  put8(an, qr, qi);
#pragma unroll
  for (int j = 0; j < 4; ++j) {
    put8(am + j * 2 * KS, yr, yi);
#pragma unroll
    for (int k = 0; k < 8; ++k) {
      if (j == 0 && k == 0) { yr[0] = eMr; yi[0] = eMi; } else if (j < 3) cmul(yr[k], yi[k], yr[k], yi[k], eMr, eMi);
    }
    if (j == 0) {
#pragma unroll
      for (int k = 0; k < 8; ++k) { const int o = k < 4 ? 2 * k : k < 6 ? 2 * k - 8 : k - 2; cmul(qr[k], qi[k], qr[o], qi[o], eLr, eLi); }
      put8(an + KS, qr, qi);
    } else if (j == 1) {
#pragma unroll
      for (int k = 0; k < 5; ++k) cmul(qr[k], qi[k], qr[k ? k - 1 : 6], qi[k ? k - 1 : 6], eLr, eLi);
      put8(an + 2 * KS, qr, qi);
    }
  }
  PROF(3, a_tab);
}

DEV void sts16_if(uint32_t a, uint32_t v, bool c) { asm volatile("{.reg .pred q; .reg .b16 h; setp.ne.u32 q,%2,0; cvt.u16.u32 h,%1; @q st.shared.u16 [%0],h;}" :: "r"(a), "r"(v), "r"((uint32_t)c) : "memory"); }
DEV void sts1_if(uint32_t a, uint32_t v, bool c) { asm volatile("{.reg .pred q; setp.ne.u32 q,%2,0; @q st.shared.u32 [%0],%1;}" :: "r"(a), "r"(v), "r"((uint32_t)c) : "memory"); }
DEV void taps(uint32_t dskip, int k4, int w, int lane) {
  PW(4 * k4 + w)
  [[maybe_unused]] const int layer = 0;
  fence_async_smem();
  bar_sync(k4 > LATEF ? NB_WG + k4 : NB_Q, k4 > LATEF ? 128 : 448 + 64 * LATEF);
  float d[24];
  undef(d);
  const uint64_t da = mkdesc(SB + k4 * 32768, 1024, KS, 0);
  wg_fence();
#pragma unroll
  for (int j = 0; j < 8; ++j) wg_ss48(d, da + j * 8, da + KS / 2 + j * 8, j);
  wg_commit();
  const int b = 8 * w + (lane >> 2), t = lane & 3, id = 32 * w + lane;
  constexpr int DO = T_O - T_E;
  const uint32_t te = SM_TAP + k4 * TAP_SZ + T_E, a0 = te - 16 * b - 4 * t;
  const uint32_t a1 = a0 - 512 - 4 * t, a2 = te - 2 * (511 + b) - 64 * t, a3 = te + (T_C - T_E) - 2 * (127 + b) - 128 * t;
  wg_wait<0>();
  PROF(4, a_mma);
  {
    const uint32_t v = pack2(d[1] + d[15], d[0] + d[14] + (id ? 0.f : bflo(dskip)));
    sts1(a0 + DO - 2, v); sts16(a0 - 2, v); sts16(a0, v >> 16);
  }
  {
    const uint32_t v = pack2(d[5] + d[19], d[4] + d[18]), u = prmt(v, v, 0x3232);
    const bool lo = t < 2, k512 = id == 2;
    sts1_if(k512 ? te - 2 * 512 : a1, u, (lo && id) || k512);
    sts1_if(k512 ? te - 2 * 514 : a1 - 4, k512 ? u : v, lo || k512);
    sts1_if(k512 ? te + DO - 2 * 513 : a1 + DO - 2, u, lo || k512);
    sts16(lo ? a1 + DO - 4 : a2 + DO - 194, v);
    sts16(lo ? (id ? a1 + DO + 2 : a1) : k512 ? te + DO - 2 * 511 : a2 + DO, u);
    sts16_if(a2 - 194, v, !lo);
    sts16_if(k512 ? te + DO - 2 * 514 : a2, u, !lo);
  }
  {
    const uint32_t v = pack2(d[8] + d[22], d[9] + d[23]);
    sts16_if(id ? a3 : te - 2 * 639, v, t < 2 || id == 2);
    sts16_if(a3 - 64, v >> 16, t < 2);
    sts16_if(te + DO - 2 * 639, v, id == 0);
  }
  bar_sync(NB_WG + k4, 128);
  mbar_arrive1_if(B_K, w == 0);
}

DEV uint32_t cpy(uint32_t v, uint32_t id) {
  uint32_t d; asm volatile("prmt.b32 %0,%1,%1,%2;" : "=r"(d) : "r"(v), "r"(id)); return d;
}
DEV uint32_t uoff(int s) { return (s ^ ((s >> 3) & 3)) * 16; }
template <bool FULL> DEV void boxes(const uint32_t (&u)[10], uint32_t a, uint32_t a9, uint32_t a7, uint32_t (&pv)[4]) {
  uint32_t v[8], p[8], x[4], y[4];
#pragma unroll
  for (int j = 0; j < 8; ++j) { v[j] = prmt(u[j], u[j + 1], 0x5432); p[j] = hadd2(u[j], v[j]); }
#pragma unroll
  for (int j = 0; j < 4; ++j) { x[j] = hadd2(hadd2(p[j + 1], p[j + 2]), u[j + 3]); y[j] = hadd2(v[j + 3], p[j + 4]); }
  sts4(a + R_A5, x[0], x[1], x[2], x[3]);
  sts4(a + R_A3, y[0], y[1], y[2], y[3]);
  if (FULL) {
#pragma unroll
    for (int j = 0; j < 4; ++j) { x[j] = hadd2(x[j], hadd2(v[j], v[j + 3])); y[j] = hadd2(x[j], hadd2(u[j], u[j + 4])); pv[j] = p[j + 4]; }
    sts4(a7, x[0], x[1], x[2], x[3]);
    sts4(a9, y[0], y[1], y[2], y[3]);
  }
}
DEV void halo(uint32_t (&u)[10], uint32_t a, int lane) {
  asm volatile("{.reg .pred p,q; setp.eq.s32 p,%8,0; setp.lt.s32 q,%8,2;\n@p ld.shared.v4.u32 {%2,%3,%4,%5},[%6];\n@q ld.shared.v2.u32 {%0,%1},[%7];}"
    : "+r"(u[0]), "+r"(u[1]), "+r"(u[2]), "+r"(u[3]), "+r"(u[4]), "+r"(u[5]) : "r"(a), "r"(a + 24 - 16 * lane), "r"(lane));
}
#define ROT 2
#define G1 -1
#define G2 0
#define G3 1
#define TPS 0x6135
#define GMASK ((G1 >= 0 ? 2 : 0) | (G2 >= 0 ? 4 : 0) | (G3 >= 0 ? 8 : 0))
#define GATE1(g, n, p) if (g >= 0 && (g & 3) == p) mbar_arrive1_if(B_G + 8 * n, k4 == (g >> 2));
#define GATE(p) GATE1(G1, 0, p) GATE1(G2, 1, p) GATE1(G3, 2, p)
#define TMASK(p) (((TPS & 15) == p) | ((((TPS >> 4) & 15) == p) << 1) | ((((TPS >> 8) & 15) == p) << 2) | ((((TPS >> 12) & 15) == p) << 3))
#define TURN(p) if (TMASK(p) == 15) bar_arrive(NB_T + 1 + k4, 256); else if (TMASK(p)) { if ((TMASK(p) >> k4) & 1) bar_arrive(NB_T + 1 + k4, 256); }
#define ANN(p, dep) if (EA & (0x1111 * p)) cnt_add(P, 1 + 5 * layer + k4, c, (32 * (v ^ 3) + lane) | (dep) | ((~(EA >> (4 * k4)) & p) << 8));
DEV void w_load(const CUtensorMap* mW, int cg, int h) {
  mbar_expect1(B_W + 8 * h, 24576);
  tma3(SM_S0 + (h & 3) * 24576, mW, 64 * cg, 64 * h, B_W + 8 * h);
}

DEV void conv(const Params& P, const CUtensorMap* mW, int c, int k4, int w, int layer) {
  const uint32_t zero = P.zero;
  PW(4 * k4 + w)
  int lane = lane_here(zero);
  const int g = lane >> 2, t = lane & 3, v = w ^ (ROT * (k4 & 1)), tid = 32 * v + lane;
  const uint32_t reg = SM_R + k4 * 16384, tp = SM_TAP + k4 * TAP_SZ;
  const uint32_t g0 = tp + ((g & 1) ? T_O : T_E) + 2 * (2 * t - g);
  uint32_t F[18][4], U[12];
  {
    const uint32_t ga = g0 - 32 * (w & 1) - 576 * (w >> 1);
    F[0][2] = lds1(ga + 48);
#pragma unroll
    for (int j = 0; j < 12; ++j) { F[j][0] = lds1(ga + 32 - 32 * j); F[j][1] = lds1(ga + 16 - 32 * j); }
#pragma unroll
    for (int j = 0; j < 12; ++j) U[j] = lds1(ga - 352 - 16 * j);
  }
  PROF(5, a_pre);
  if (k4 == 3 && w == 3) {
    mbar_wait(B_E, layer);
    mbar_wait(B_K, 0);
#pragma unroll
    for (int h = 0; h < 4; ++h) w_load(mW, c & 7, h);
  }
  mbar_wait(k4 && ((GMASK >> k4) & 1) ? B_G - 8 + 8 * k4 : B_E, layer);
  PROF(6, a_x);
  const uint32_t ua = reg + R_U + uoff(tid);
  uint4 x[2];
  uint32_t pv[4];
  {
    uint4 s[4];
#pragma unroll
    for (int z = 0; z < 2; ++z) x[z] = lds4(reg + R_B + tid * 16 + z * 2048);
#pragma unroll
    for (int z = 0; z < 4; ++z) s[z] = lds4(SM_RES + tid * 16 + (z >> 1) * 2048 + (z & 1) * 4096);
    sts4z_if(reg + lane * 16 + (w ? w * 3584 + 1024 : 0), w < 3);
    for (int it = 0;; ++it) {
      uint32_t m = min(x[0].x, x[1].x);
#pragma unroll
      for (int z = 0; z < 4; ++z) m = min(m, min(s[z].x, s[z].z));
      if (m) break;
#pragma unroll
      for (int z = 0; z < 2; ++z) x[z] = ldr4(&P.S->XG[layer][(128 * k4 + c) * 256 + opq(tid) + z * 128]);
#pragma unroll
      for (int z = 0; z < 4; ++z) s[z] = ldr4(&P.S->SR[layer][c >> 4][opq(tid) + (z >> 1) * 128 + (z & 1) * 256]);
#pragma unroll
      for (int z = 0; z < 4; ++z) sts4(SM_RES + tid * 16 + (z >> 1) * 2048 + (z & 1) * 4096, s[z].x, s[z].y, s[z].z, s[z].w);
      spin_guard(it);
    }
    __syncwarp();
    uint32_t u[2][10];
#pragma unroll
    for (int z = 0; z < 2; ++z) {
      u[z][6] = hmul2(hsub2(x[z].x, s[2 * z].y), s[2 * z].x); u[z][7] = hmul2(hsub2(x[z].y, s[2 * z].w), s[2 * z].z);
      u[z][8] = hmul2(hsub2(x[z].z, s[2 * z + 1].y), s[2 * z + 1].x); u[z][9] = hmul2(hsub2(x[z].w, s[2 * z + 1].w), s[2 * z + 1].z);
      sts4(ua + z * 2048, u[z][6], u[z][7], u[z][8], u[z][9]);
    }
#pragma unroll
    for (int j = 0; j < 6; ++j) u[0][j] = __shfl_up_sync(0xffffffffu, u[0][j < 2 ? 8 + j : 4 + j], j < 2 ? 2 : 1);
    bar_sync(NB_WG + k4, 128);
    GATE(0)
    PROF(7, a_u);
    const uint32_t h1 = reg + R_U + v * 512 - 64;
    halo(u[0], h1, lane);
    if (v < 2) {
      u[1][0] = 0;
#pragma unroll
      for (int j = 1; j < 6; ++j) u[1][j] = __shfl_up_sync(0xffffffffu, u[1][j < 2 ? 8 + j : 4 + j], j < 2 ? 2 : 1);
      halo(u[1], h1 + 2048, lane);
      boxes<false>(u[1], reg + tid * 16 + 2048, 0, 0, pv);
    }
    const uint32_t bo = reg + R_B + tid * 16 + (v >> 1) * 1056;
    const uint32_t be = tid == 127 ? reg + R_B + 1024 : bo + (tid == 63 ? 2112 : 1056);
    boxes<true>(u[0], reg + tid * 16, (lane & 1) ? be : bo, (lane & 1) ? bo : be, pv);
    sts4z_if(reg + R_B + 1040, tid == 0);
  }
  GATE(1)
  fence_async_smem();
  if (k4 == 3 && w < 3) {
    const uint32_t src = SM_RES + 8192 + w * 2048, f = (w >> 1) - 1;
#pragma unroll
    for (int z = 0; z < 4; ++z) sts4(src + lane * 16 + z * 512, f, f, f, f);
    fence_async_smem();
    __syncwarp();
    if (w < 2) {
#pragma unroll
      for (int z = 0; z < 4; ++z) bulk_store(&P.S->O[((c >> 3) * 16 + w * 8 + (c & 7)) * 512] + z * 128, src, 2048);
    } else {
#pragma unroll
      for (int z = 0; z < 2; ++z) {
        bulk_store(&P.S->H[(c + 8) * 256] + z * 128, src, 2048);
        bulk_store(P.S->F + ((c >> 3) * 64 + 4 * (c & 7)) + z * 32, src, 16);
      }
      bulk_store(&P.S->PS[c * 64], src, 1024);
      bulk_store(&P.S->ST[c * 4], src, 64);
      if (c < 5) bulk_store(P.S->C + (c + 5 - 5 * layer) * 1024, src, 128 * NCOPY * NSUB);
    }
    asm volatile("cp.async.bulk.commit_group;" ::: "memory");
  }
  const uint32_t id = opq(0x3210u);
#pragma unroll
  for (int j = 0; j < 12; ++j) { F[j][3] = cpy(F[j][0], id); if (j) F[j][2] = cpy(F[j - 1][1], id); }
  const uint32_t g2 = tp + T_C - 258 - 32 * w + 4 * (t - g);
  PROF(8, a_box);
  bar_sync(NB_T + k4, k4 ? 256 : 128);
  PROF(9, a_turn);
  float acc[32], f1[24], f3[16];
  uint32_t qa[4][4], qb[4][4], qc[4][4], fp[4];
  const uint64_t db = mkdesc(reg + R_U, 16, 512, 2) + 2;
#define STEP(mm) wg_fence(); mm; wg_commit(); wg_wait<2>();
#define D(j) STEP(wg_rs64k(acc, F[j], db - 2 * j, j))
#define C(j) STEP(wg_rs32t(f3, qc[j], mkdesc(reg + R_B, 128, 1040, 0) + 16 * j, j))
#define T(q, j, o) STEP(wg_rs48t(f1, q[j], d1 + o + 16 * (j & 1) - 32 * (j >> 1), o | j))
#define LO(q, a) q[0] = lds1(a); q[2] = lds1(a + 16);
#define HI(q, a) q[1] = lds1(a - 128); q[3] = lds1(a - 112);
#define NIL(q) { const uint32_t z = here(zero); q[2][1] = cpy(z, 0); q[2][3] = cpy(z, 1); q[3][1] = cpy(z, 2); q[3][3] = cpy(z, 3); }
#define X(j) F[12 + j][0] = cpy(U[2 * j], ix); F[12 + j][1] = cpy(U[2 * j + 1], ix); F[12 + j][3] = cpy(F[12 + j][0], ix); F[12 + j][2] = cpy(F[11 + j][1], ix);
#define PIN ix = 0x3210u | here(zero);
  const uint32_t g1 = g0 - 2 * 576 - 16 * w;
  const uint64_t d1 = mkdesc(reg + R_A5, 128, 512, 0);
  constexpr int O3 = (R_A3 - R_A5) / 16;
  uint32_t ix;
  undef(acc);
  D(0) TURN(0) D(1) D(2) LO(qc[0], g2) D(3) HI(qc[0], g2) D(4) LO(qc[1], g2 + 32) D(5) HI(qc[1], g2 + 32)
  D(6) TURN(1) LO(qc[2], g2 + 64) D(7) HI(qc[2], g2 + 64) D(8) LO(qc[3], g2 + 96) D(9) HI(qc[3], g2 + 96) D(10) PIN X(0)
  undef(f3);
  C(0) C(1) LO(qa[0], g1) C(2) X(1) C(3) TURN(2) HI(qa[0], g1)
  D(11) LO(qa[1], g1 + 32) PIN X(2) D(12) HI(qa[1], g1 + 32) X(3)
  fp[0] = pack2(f3[0], f3[1]); fp[1] = pack2(f3[4], f3[5]); fp[2] = pack2(f3[8] + f3[2], f3[9] + f3[3]); fp[3] = pack2(f3[12] + f3[6], f3[13] + f3[7]);
  D(13) LO(qa[2], g1 - 64) PIN ix |= fp[0] & fp[1] & fp[2] & fp[3] & zero; X(4) D(14) TURN(3) LO(qa[3], g1 - 32) X(5)
  D(15) LO(qb[0], g1 - 192) NIL(qa) D(16) HI(qb[0], g1 - 192) D(17) TURN(4) LO(qb[1], g1 - 160)
  PROF(10, a_den);
  undef(f1);
  T(qa, 0, 0) HI(qb[1], g1 - 160) T(qa, 1, 0) LO(qb[2], g1 - 256) T(qa, 2, 0) LO(qb[3], g1 - 224) NIL(qb) T(qa, 3, 0) TURN(5)
  wg_fence();
#pragma unroll
  for (int j = 0; j < 4; ++j) wg_rs48t(f1, qb[j], d1 + O3 + 16 * (j & 1) - 32 * (j >> 1), 1);
  wg_commit();
  TURN(6)
  asm volatile("cp.async.bulk.wait_group 0;" ::: "memory");
  uint32_t k1024 = lds16(tp + T_E - 2 * 639);
  lane = lane_here(zero);
  uint32_t yp[16];
#pragma unroll
  for (int z = 0; z < 16; ++z) yp[z] = pack2(acc[2 * z], acc[2 * z + 1]);
  const int p = (lane + 9 * (w >> 1)) & 31;
  const uint32_t ya = reg + ((w >> 1) ? R_B : R_U) + p * 64 + (((2 * (w & 1)) ^ ((p >> 1) & 3)) * 16);
  const uint32_t up = p < lane ? 2048 : 0;
  const uint32_t fa = reg + R_A5 + (lane >> 3) * 512 + w * 128 + (lane & 7) * 16;
  const uint32_t fc = reg + R_A3 + uoff(64 * (lane >> 4) + 16 * w + 2 * (lane & 7) + 1 - ((lane >> 3) & 1));
  wg_wait<0>();
  GATE(2)
  PROF(11, a_far);
  bar_sync(NB_WG + k4, 128);
#pragma unroll
  for (int z = 0; z < 4; ++z) {
    const uint32_t* a = yp + 8 * (z >> 1) + (z & 1);
    stsm4t((ya + (up ^ ((z >> 1) * 2048))) ^ ((z & 1) * 16), a[0], a[2], a[4], a[6]);
  }
  stsm4(fa, pack2(f1[0], f1[1]), pack2(f1[4], f1[5]), pack2(f1[8] + f1[2], f1[9] + f1[3]), pack2(f1[12] + f1[6], f1[13] + f1[7]));
  stsm2(fa + 2048, pack2(f1[16] + f1[10], f1[17] + f1[11]), pack2(f1[20] + f1[14], f1[21] + f1[15]));
  stsm4(fc, fp[0], fp[1], fp[2], fp[3]);
  bar_sync(NB_WG + k4, 128);
  PROF(12, a_sts);
  {
    const int o = 32 * v + lane;
    const uint32_t a = reg + uoff(o), b = reg + R_A5 + o * 16;
    uint4 y[2];
    y[0] = hadd8(lds4(a + R_U), hadd8(lds4(o >= 36 ? a + R_B : reg), lds4(v >= 2 ? b - 1024 : reg)));
    uint4 h = lds4(a + R_A3);
    k1024 = prmt(k1024, k1024, 0x1010);
    h = make_uint4(hfma2(pv[0], k1024, h.x), hfma2(pv[1], k1024, h.y), hfma2(pv[2], k1024, h.z), hfma2(pv[3], k1024, h.w));
    y[1] = hadd8(lds4(a + R_U + 2048), hadd8(lds4(a + R_B + 2048), hadd8(lds4(b + 1024), h)));
    const int e0 = (o >> 3) * 8192 + (128 * k4 + c) * 16 + (((o & 4) + ((o >> 1) & 1)) ^ (c & 7)) * 2 + (o & 1);
    ANN(2, y[0].x & y[1].x & zero)
    const uint32_t me = (e0 & 3) == ((c >> 1) & 3), m0 = me & ~c, m1 = me & c, tag = 1 - layer;
#pragma unroll
    for (int z = 0; z < 2; ++z) {
      const uint4 r = hadd8(x[z], y[z]);
      str2((uint2*)P.S->XF + e0 + z * 131072, tagged(prmt(r.x, r.y, 0x5410), m0, tag), tagged(prmt(r.z, r.w, 0x5410), m1, tag));
      str2((uint2*)P.S->XF + (e0 ^ 4) + z * 131072, tagged(prmt(r.x, r.y, 0x7632), m0, tag), tagged(prmt(r.z, r.w, 0x7632), m1, tag));
    }
  }
  ANN(1, 0)
  GATE(3)
  PROF(13, a_out);
}

#define WGATE 1
#define FH 1
#define QPIN 1
#define XORD 1
DEV void x_load(const Params& P, int c, int q, int layer) {
#pragma unroll
  for (int z = 0; z < 2; ++z) {
    const int e = z ^ (XORD && q == 3 && !(c & 4));
    mbar_expect1(B_X + 16 * q + 8 * e, 16384);
    bulk(xstage(q, e), P.S->XF + ((2 * (c >> 3) + 1 - e) * 4096 + q * 1024), 16384, B_X + 16 * q + 8 * e);
  }
}

DEV void means(uint32_t (&m)[4], int row, int lane, int layer, uint32_t zero) {
  mbar_wait(B_CS, 0);
  mbar_wait(B_ST, layer);
  const uint32_t a = SM_MISC + row * 4 + (lane & 28), k = (lane & 3) ? 0u : ~0u;
  m[0] = lds1(a) & k; m[1] = lds1(a + 32) & k; m[2] = m[0] & zero; m[3] = m[1] & zero;
}

DEV void attn_phase(const Params& P, int c, int e, int w, int lane, int layer) {
  PW(4 * e + w)
  const int cg = c & 7, J = 2 * (c >> 3) + 1 - e;
  float acc[96];
  zerov(acc);
  uint32_t m[4] = {0, 0, 0, 0};
#pragma unroll 1
  for (int q = 0;; ++q) {
    const uint64_t da = mkdesc(xstage(q, e), 16, 1024, 1), db = mkdesc(SM_S0 + (q & 1) * 49152, 8192, 1024, 1);
    const uint32_t wr = mbar_test2(B_W + 16 * q, layer), xa = xstage(q, e) + w * 4096 + lane * 132;
    mbar_wait(B_X + 16 * q + 8 * e, layer);
    for (int it = 0;; ++it) {
      const uint32_t ok = both(lds1(xa), lds1(xa ^ 32), layer) & both(lds1(xa ^ 64), lds1(xa ^ 96), layer);
      if (__all_sync(0xffffffffu, ok & 1)) break;
      EVENT(8 * layer + 2 * q + e);
#pragma unroll 1
      for (int j = 0; j < 8; ++j) cp16(xstage(q, e) + w * 4096 + j * 512 + lane * 16, P.S->XF + (J * 4096 + q * 1024 + w * 256 + j * 32 + lane));
      asm volatile("cp.async.wait_all;" ::: "memory");
      fence_async_smem();
      __syncwarp();
      spin_guard(it);
    }
    bool all = __all_sync(0xffffffffu, wr);
    if (q == 0 && e && w == 0) {
      bar_sync(NB_H, 256);
      cnt_wait(P, 2 + 5 * layer, c, lane);
      x_load(P, c, 1, layer);
      PROF(27, m_xi);
    }
    if (q == 3 && e) means(m, 16 * w, lane, layer, P.zero);
    if (!all) { mbar_wait(B_W + 16 * q, layer); all = mbar_test(B_W + 16 * q + 8, layer); }
    bar_sync(e ? NB_Q : q ? NB_T : NB_T + 4, 256);
    PROF(14 + q, m_q);
    wg_fence();
#pragma unroll
    for (int k = 0; k < 8; ++k) {
      if (k == 4) { wg_commit(); if (!all) mbar_wait(B_W + 16 * q + 8, layer); wg_fence(); }
      wg_ss192(acc, da + k * 128, db + (k >> 2) * 1536 + (k & 3) * 128, 1);
    }
    wg_commit();
    if (q == 3) break;
    bar_arrive(e ? NB_T : NB_Q, 256);
    if (FH) { wg_wait<1>(); mbar_arrive1_if(B_FH + 8 * q, e && q < 2); }
    wg_wait<0>();
    mbar_arrive1(B_F + 8 * q);
  }
  const int pos = 2 - 2 * e + (w >> 1);
  uint4* h = P.S->H + ((c + 8) * 256 + (w & 1) * 128 + lane);
  {
    if (!e) means(m, 64 + 16 * w, lane, layer, P.zero);
    PROF(28, m_sub);
    wg_fence();
    wg_rs192t(acc, m, mkdesc(SM_CS, 0, 32, 0));
    wg_commit();
    bar_arrive_if(NB_Q, 256, !e);
    keep(h, P.zero);
    wg_wait<0>();
    mbar_arrive1(B_F + 24);
  }
  PROF(18, m_qkv);
  lane = opq(lane);
  const int g = lane >> 2, t = lane & 3;
  uint32_t Q[4][4], K[4][3][2], V[4][3][2];
  const uint32_t ra = SM_STAT + 256 + (32 - 32 * e + 8 * w) * 16;
  float r0, r1;
  uint4 k0, k1, k2;
  {
#pragma unroll
    for (int z = 0; z < 4; ++z) {
      K[z][2][0] = nz(pack2(acc[34 + 8 * z], acc[35 + 8 * z])); K[z][2][1] = pack2(acc[38 + 8 * z], acc[39 + 8 * z]);
      V[z][2][0] = pack2(acc[66 + 8 * z], acc[67 + 8 * z]); V[z][2][1] = pack2(acc[70 + 8 * z], acc[71 + 8 * z]);
      str4_if(h + z * 32, K[z][2][0], K[z][2][1], V[z][2][0], V[z][2][1], pos == 3);
    }
    bar_arrive_if(NB_RL, 128, pos == 3);
#pragma unroll
    for (int z = 0; z < 8; ++z) {
      V[z >> 1][2][z & 1] = movm(V[z >> 1][2][z & 1]);
      K[z >> 1][1][z & 1] = pack2(acc[32 + 4 * z], acc[33 + 4 * z]);
      V[z >> 1][1][z & 1] = pack2(acc[64 + 4 * z], acc[65 + 4 * z]);
    }
    const uint32_t kv = (w & 1) * 2048 + lane * 16;
    if (pos < 3) {
      mbar_wait(B_F + 16 + 8 * e, layer);
#pragma unroll
      for (int z = 0; z < 4; ++z) sts4(kvslot(cg, pos + 1) + kv + z * 512, K[z][2][0], K[z][2][1], V[z][2][0], V[z][2][1]);
      bar_arrive(NB_H + pos + 1, 128);
    }
    r0 = lds1f(ra + (g >> 1) * 16 + (g & 1) * 4); r1 = lds1f(ra + 64 + (g >> 1) * 16 + (g & 1) * 4);
    k1 = lds4(ra + 16 * t); k2 = lds4(ra + 64 + 16 * t);
    PROF(19, m_kv);
    uint32_t pin = QPIN ? P.zero : 0;
#pragma unroll
    for (int z = 0; z < 8; ++z) {
      V[z >> 1][1][z & 1] = movm(V[z >> 1][1][z & 1]);
      Q[z >> 1][2 * (z & 1)] = pack2(acc[4 * z], acc[4 * z + 1]);
      Q[z >> 1][2 * (z & 1) + 1] = pack2(acc[4 * z + 2], acc[4 * z + 3]);
      if (QPIN) pin &= Q[z >> 1][2 * (z & 1)] & Q[z >> 1][2 * (z & 1) + 1];
    }
    mbar_wait(B_F + 24, layer);
    bar_sync(NB_H + pos + pin, pos ? 128 : 160);
    k0 = lds4(ra - 192 + 16 * t);
#pragma unroll
    for (int z = 0; z < 4; ++z) {
      const uint4 hv = lds4(kvslot(cg, pos) + kv + z * 512);
      K[z][0][0] = hv.x; K[z][0][1] = hv.y; V[z][0][0] = hv.z; V[z][0][1] = hv.w;
    }
  }
  PROF(20, m_halo);
  const uint32_t ob = e ? SM_S1 : SM_XA;
  {
    const bool p0 = 2 * t > g, p1 = 2 * t + 1 > g, first = c < 8 && pos == 0;
    const uint32_t M = (p0 ? 0xFFFFu : 0u) | (p1 ? 0xFFFF0000u : 0u);
    const float sc0 = r0 * (0.25f * 1.4426950408889634f), sc1 = r1 * (0.25f * 1.4426950408889634f);
    const float sk[4] = {__uint_as_float(p0 ? k0.x : k1.x) * sc0, __uint_as_float(p1 ? k0.y : k1.y) * sc0,
                         __uint_as_float(p0 ? k1.x : k2.x) * sc1, __uint_as_float(p1 ? k1.y : k2.y) * sc1};
    const uint32_t rm[4] = {k0.z & M, k1.z & ~M, k1.z & M, k2.z & ~M}, s0 = k0.w | P.zero, s1 = k1.w | P.zero;
    const int oo = cg * 512 + (2 * (w & 2) + (w & 1)) * 64 + (lane ^ (g >> 1));
    uint4* O = P.S->O + (J * 4096 + oo);
#pragma unroll
    for (int h2 = 0; h2 < 2; ++h2) {
      uint32_t A[2], B[2], mx[2];
#pragma unroll
      for (int z = 0; z < 2; ++z) {
        const int h = 2 * h2 + z;
        float S[3][4];
#pragma unroll
        for (int n = 0; n < 3; ++n) mma16z(S[n], Q[h][0], Q[h][1], Q[h][2], Q[h][3], K[h][n][0], K[h][n][1]);
        if (first) { S[0][0] = __uint_as_float(0xFF800000u); S[0][1] = S[0][0]; }
        A[z] = pack2((p0 ? S[0][0] : S[1][0]) * sk[0], (p0 ? S[1][2] : S[2][2]) * sk[2]);
        B[z] = pack2((p1 ? S[0][1] : S[1][1]) * sk[1], (p1 ? S[1][3] : S[2][3]) * sk[3]);
      }
#pragma unroll
      for (int z = 0; z < 2; ++z) mx[z] = hmax2(A[z], B[z]);
#pragma unroll
      for (int z = 0; z < 2; ++z) mx[z] = hmax2(mx[z], __shfl_xor_sync(0xffffffffu, mx[z], 1));
#pragma unroll
      for (int z = 0; z < 2; ++z) mx[z] = hmax2(mx[z], __shfl_xor_sync(0xffffffffu, mx[z], 2));
      float Oa[2][3][4];
#pragma unroll
      for (int z = 0; z < 2; ++z) {
        const int h = 2 * h2 + z;
        const uint32_t a = hsub2(A[z], mx[z]), b = hsub2(B[z], mx[z]);
        const uint32_t w0 = pack2(ex2(bflo(a)), ex2(bflo(b))), w1 = pack2(ex2(bfhi(a)), ex2(bfhi(b)));
        const uint32_t u0 = hmul2(w0, rm[0]), u1 = hmul2(w0, rm[1]), u2 = hmul2(w1, rm[2]), u3 = hmul2(w1, rm[3]);
        const uint32_t z0 = w0 & P.zero, z1 = w1 & P.zero;
        mma16z(Oa[z][2], u0, z0, u1, u2, s0, s1);
#pragma unroll
        for (int d = 0; d < 2; ++d) mma16z(Oa[z][d], u0, z0, u1, u2, V[h][0][d], V[h][1][d]);
        mma8(Oa[z][2], z1, u3, k2.w);
#pragma unroll
        for (int d = 0; d < 2; ++d) mma8(Oa[z][d], z1, u3, V[h][2][d]);
      }
#pragma unroll
      for (int r = 0; r < 4; r += 2) {
        const float i0 = rcp(Oa[0][2][r]), i1 = rcp(Oa[1][2][r]);
        const uint32_t o0 = pack2(Oa[0][0][r] * i0, Oa[0][0][r + 1] * i0), o1 = pack2(Oa[0][1][r] * i0, Oa[0][1][r + 1] * i0);
        const uint32_t o2 = pack2(Oa[1][0][r] * i1, Oa[1][0][r + 1] * i1), o3 = pack2(Oa[1][1][r] * i1, Oa[1][1][r + 1] * i1);
        str4(O + h2 * 32 + r * 64, o0, o1, o2, o3);
        sts4(ob + oo * 16 + h2 * 512 + r * 1024, o0, o1, o2, o3);
      }
    }
  }
  bar_arrive(NB_T + 1 + e, 160);
  fence_async_smem();
  PROF(21, m_att);
  uint32_t res[8][2];
  mbar_wait(B_RES, layer);
  {
    const uint32_t a = SM_RES + e * 8192 + (lane >> 4) * 1024 + (lane & 7) * 128 + (((2 * (w & 2) + ((lane >> 2) & 2) + (w & 1)) ^ (lane & 7)) * 16);
#pragma unroll
    for (int j = 0; j < 8; j += 2) ldsm4t(res[j][0], res[j][1], res[j + 1][0], res[j + 1][1], a + j * 1024);
  }
  PROF(26, m_res);
  if (WGATE) bar_sync(NB_T, 256); else bar_sync(NB_WG + e, 128);
  XgAddr xa = xg_addr<true>(P.S->XG[1] + (64 * cg * 256 + 8 * J), ob, w, lane, P.zero);
  uint4* ps = &P.S->PS[((4 * J + w) * 8 + cg) * 8 + g];
  keep(ps, P.zero);
  if (layer) {
    xa.a = ob + w * 2048 + (lane & 15) * 128 + (((lane >> 4) ^ (lane & 7)) * 16);
    xa.b = ob + w * 2048 + (lane >> 3) * 128 + (((lane & 7) ^ (lane >> 3)) * 16);
    xa.dst = (uint4*)P.out + ((64 * J + 16 * w + 2 * (lane >> 3)) * 64 + 8 * cg + (lane & 7));
  }
  uint32_t y[8][2];
#pragma unroll 1
  for (int it = 0;; ++it) {
    float ac[32];
    zerov(ac);
#pragma unroll 1
    for (int n = 0; n < 8; ++n) {
      const int s = n == 0 ? cg : n - (n <= cg);
      mbar_wait(n ? B_O + 64 * e + 8 * s : B_WO, layer);
      if (n == 1) PROF(22, m_o1);
      if (n == 7) PROF(23, m_o7);
      const uint64_t da = mkdesc(ob + s * 8192, 16, 1024, 2), db = mkdesc(SM_R + s * 8192, 16, 1024, 1);
      wg_fence();
#pragma unroll
      for (int k = 0; k < 4; ++k) wg_ss64(ac, da + (k >> 1) * 32 + (k & 1) * 2, db + k * 128, 1);
      wg_commit();
    }
    wg_wait<0>();
    const bool bad = ac[0] != ac[0] || ac[2] != ac[2];
#pragma unroll
    for (int j = 0; j < 8; ++j) {
      y[j][0] = hadd2(res[j][0], pack2(ac[4 * j], ac[4 * j + 1]));
      y[j][1] = hadd2(res[j][1], pack2(ac[4 * j + 2], ac[4 * j + 3]));
    }
    if (!bar_any(NB_WG + e, 128, bad) || it == 16) break;
    EVENT(24 + 2 * layer + e);
    refetch(ob, P.S->O + J * 4096, 32768, e, w);
  }
  PROF(24, m_wo);
  if (layer == 0) {
    const float4 s = gram(y, g, P.zero);
    xg_put<true>(xa, y);
    str4_if(ps, nz(__float_as_uint(s.x)), __float_as_uint(s.y), __float_as_uint(s.z), __float_as_uint(s.w), t == (g >> 1));
    mbar_arrive1(B_ED + 8 * e);
    xg_store(xa, NB_WG + e);
    bar_arrive(NB_T + 3, 288);
  } else {
#pragma unroll
    for (int j = 0; j < 8; j += 2) stsm4(xa.a ^ (j * 16), y[j][0], y[j][1], y[j + 1][0], y[j + 1][1]);
    __syncwarp();
#pragma unroll
    for (int k = 0; k < 4; ++k) {
      const uint4 v = lds4((xa.b ^ ((k & 1) * 64)) + k * 512);
      stw4(xa.dst + ((k & 1) * 8 + (k >> 1)) * 64, v.x, v.y, v.z, v.w);
    }
  }
  PROF(25, m_epi);
}

#define HDELAY 300
#define ODELAY 200
#define PDELAY 500
#define FDELAY 200
#define CSP 0
#define CSU 4
#define WOQ 2
#define H5 1
#define SRDELAY 300
#define ZPACE 20

DEV void o_load(const Params& P, int c, int e, int lane, int layer) {
  PW(8 + e)
  const int J = 2 * (c >> 3) + 1 - e;
#pragma unroll 1
  for (int s = 0; s < 8; ++s) mbar_expect1(B_O + 64 * e + 8 * s, s == (c & 7) ? 0 : 8192);
  bar_sync(NB_T + 1 + e, 160);
  flag_set1(P.S->F + (J * 32 + 4 * (c & 7)));
  if (ODELAY) delay(ODELAY);
  PROF(26, a_go);
  poll(P.S->F + (J * 32 + (lane & 28)), 1);
  PROF(25, h_seen);
  bar_sync_if(NB_Q, 64, e);
#pragma unroll 1
  for (int s = 0; s < 8; ++s)
    if (s != (c & 7)) bulk((e ? SM_S1 : SM_XA) + s * 8192, P.S->O + (J * 4096 + s * 512), 8192, B_O + 64 * e + 8 * s);
  bar_arrive_if(NB_Q, 64, !e);
  PROF(28, a_o);
}

DEV void stats(const Params& P, int c, int w, int lane, int layer) {
  PW(12 + w)
  lane = opq(lane);
  const int r = (lane & 6) + ((lane >> 3) & 1), k = (2 * (c & 3) + (lane & 1)) ^ r, e = 1 - ((c >> 2) & 1);
  const uint32_t o = (32 * w + 8 * (lane >> 4) + r) * 128 + k * 16;
  const uint32_t mk = ((k & 1) == (r >> 2)) << (r & 3), tag = 1 - layer;
  float v[16];
#pragma unroll
  for (int z = 0; z < 16; ++z) v[z] = 0.f;
#pragma unroll 1
  for (int q = 0; q < 4; ++q) {
    mbar_wait(B_X + 16 * q + 8 * e, layer);
    PROF(19 + q, s_l);
    uint4 x, y;
    for (int it = 0;; ++it) {
      x = lds4v(xstage(q, e) + o); y = lds4v(xstage(q, e) + o + 2048);
      const uint32_t bad = (((x.x ^ tag) | (y.x ^ tag)) & mk) | (((x.y ^ tag) | (y.y ^ tag)) & (mk >> 1)) |
                           (((x.z ^ tag) | (y.z ^ tag)) & (mk >> 2)) | (((x.w ^ tag) | (y.w ^ tag)) & (mk >> 3));
      if (!__any_sync(0xffffffffu, bad & 1)) break;
      spin_guard(it);
    }
    mbar_arrive1(B_F + 8 * q);
    const uint32_t ws[8] = {x.x, x.y, x.z, x.w, y.x, y.y, y.z, y.w};
#pragma unroll
    for (int z = 0; z < 8; ++z) {
      const float lo = bflo(ws[z]), hi = bfhi(ws[z]);
      float* u = v + 4 * (z & 3);
      u[0] += lo; u[1] += lo * lo; u[2] += hi; u[3] += hi * hi;
    }
  }
  PROFD(14, s_part, __float_as_uint(v[0]));
  fold<8>(v, lane, 16); fold<4>(v, lane, 8); fold<2>(v, lane, 4); fold<1>(v, lane, 2);
  PROFD(16, s_fold, __float_as_uint(v[0]));
  if (w) {
    sts1(SM_MISC - 128 + w * 128 + lane * 4, __float_as_uint(v[0]));
    bar_arrive(NB_P, 128);
  } else {
    bar_sync(NB_P, 128);
    v[0] += lds1f(SM_MISC + lane * 4) + lds1f(SM_MISC + 128 + lane * 4) + lds1f(SM_MISC + 256 + lane * 4);
    float m;
    const float sd = ln_sd(v[0], __shfl_xor_sync(0xffffffffu, v[0], 2), m);
    if (!(lane & 2)) str1((uint32_t*)P.S->ST + (16 * c + 8 * (lane & 1) + (lane >> 2)), pack2(m, sd));
    sts4(SM_STAT - 32 + min(lane, 17) * 16, 0x3F800000u, 0x3F800000u, 0x3F803F80u, 0x3F803F80u);
    fence_async_smem();
    PROF(17, s_pub);
    uint4 s;
    for (int it = 0;; ++it) {
      s = ldr4(P.S->ST + ((c >> 3) * 32 + lane));
      if (__all_sync(0xffffffffu, min4(s) != 0u)) break;
      spin_guard(it);
    }
    PROF(18, s_seen);
    const float r0 = rcp(bfhi(s.x)), r1 = rcp(bfhi(s.y)), r2 = rcp(bfhi(s.z)), r3 = rcp(bfhi(s.w));
    const uint32_t sg = 0x80008000u;
    sts4(SM_MISC + lane * 16, prmt(s.x, s.x, 0x1010) ^ sg, prmt(s.y, s.y, 0x1010) ^ sg, prmt(s.z, s.z, 0x1010) ^ sg, prmt(s.w, s.w, 0x1010) ^ sg);
    sts4(SM_STAT + 256 + lane * 32, __float_as_uint(r0), __float_as_uint(r1), pack2(r0, r1), prmt(s.x, s.y, 0x7632));
    sts4(SM_STAT + 272 + lane * 32, __float_as_uint(r2), __float_as_uint(r3), pack2(r2, r3), prmt(s.z, s.w, 0x7632));
    __syncwarp();
    mbar_arrive1(B_ST);
  }
  PROF(15, s_stat);
  if (w == 1) {
    mbar_wait(B_ST, layer);
    if (c >= 8) {
      uint2 s;
      for (int it = 0;; ++it) {
        s = ldr2((const uint2*)P.S->ST + ((c >> 3) * 64 - 12 + (lane & 11)));
        if (__all_sync(0xffffffffu, min(s.x, s.y) != 0u)) break;
        spin_guard(it);
      }
      const float r0 = rcp(bfhi(s.x)), r1 = rcp(bfhi(s.y));
      sts4(SM_STAT + 64 + (lane & 11) * 16, __float_as_uint(r0), __float_as_uint(r1), pack2(r0, r1), prmt(s.x, s.y, 0x7632));
    }
    bar_arrive(NB_H, 160);
  }
  if (w >= 2) {
    const uint4* h = P.S->H + (c * 256 + (w & 1) * 128 + lane);
    uint4 hv[4];
#pragma unroll
    for (int z = 0; z < 4; ++z) hv[z] = make_uint4(0, 0, 0, 0);
    bar_sync(NB_RL, 128);
    PROFD(26, s_hb, lds1v(SM_MISC));
    delay(HDELAY);
    for (int it = 0; c >= 8; ++it) {
#pragma unroll
      for (int z = 0; z < 4; ++z) hv[z] = ldr4(h + z * 32);
      if (__all_sync(0xffffffffu, min(min(hv[0].x, hv[1].x), min(hv[2].x, hv[3].x)) != 0u)) break;
      spin_guard(it);
    }
    mbar_wait(B_F + 24, layer);
#pragma unroll
    for (int z = 0; z < 4; ++z) sts4(kvslot(c & 7, 0) + (w & 1) * 2048 + lane * 16 + z * 512, hv[z].x, hv[z].y, movm(hv[z].z), movm(hv[z].w));
    bar_arrive(NB_H, 160);
    mbar_arrive1_if(B_ST + 8, w == 3);
    PROF(25, s_halo);
  }
}

DEV void finalize(const Params& P, int c, int lane, int layer) {
  PW(12)
  float z[4];
  if (layer == 0) {
    bar_sync(NB_P, 256);
    z[0] = z[1] = z[2] = z[3] = 0.f;
#pragma unroll
    for (int k = 0; k < 2; ++k) { const float4 a = lds4f(SM_RES + 8192 + k * 512 + lane * 16); z[0] += a.x; z[1] += a.y; z[2] += a.z; z[3] += a.w; }
  } else {
    mbar_wait(B_ED + 8 - 2 * (c & 4), 0);
    if (FDELAY) delay(FDELAY);
    const uint4* ps = &P.S->PS[c * 64 + lane];
    uint4 a, b;
    for (int it = 0;; ++it) {
      a = ldr4(ps); b = ldr4(ps + 32);
      if (__all_sync(0xffffffffu, min(a.x, b.x) != 0u)) break;
      spin_guard(it);
    }
    z[0] = __uint_as_float(a.x) + __uint_as_float(b.x); z[1] = __uint_as_float(a.y) + __uint_as_float(b.y);
    z[2] = __uint_as_float(a.z) + __uint_as_float(b.z); z[3] = __uint_as_float(a.w) + __uint_as_float(b.w);
  }
#pragma unroll
  for (int o = 8; o < 32; o <<= 1)
#pragma unroll
    for (int k = 0; k < 4; ++k) z[k] += __shfl_xor_sync(0xffffffffu, z[k], o);
  float m0, m1;
  const float r0 = rcp(ln_sd(z[0], z[1], m0)), r1 = rcp(ln_sd(z[2], z[3], m1));
  const uint32_t wr = nz(pack2(r0, r1)), wm = pack2(m0, m1);
  uint2* so = (uint2*)P.S->SR[layer] + ((lane >> 3) * 1024 + (lane & 2) * 256 + 4 * c + ((lane >> 1) & 2) + (lane & 1));
  str2(so, wr, wm); str2(so + 4096, wr, wm);
  if (!LATEF) bar_arrive_if(NB_Q, 448, !layer);
  PROF(23, s_sr);
}

DEV void announce(const Params& P, int c, int lane, int layer) {
  PW(13)
  bar_sync(NB_T + 3, 288);
  cnt_add(P, 5 * layer, c, lane);
  if (!LATEF) { bar_arrive_if(NB_Q, 448, !layer); fence_async_smem(); }
  PROF(24, s_own);
}

DEV void fetch(const Params& P, int c, int lane, int layer) {
  PW(13)
  mbar_expect1(B_E, 24576);
  cnt_wait(P, 5 * layer, c, lane);
#pragma unroll
  for (int k = 0; k < 4; ++k) bulk(SM_R + k * 16384 + R_B, P.S->XG[layer] + (128 * k + c) * 256, 4096, B_E);
  if (layer) delay(SRDELAY);
  bulk(SM_RES, P.S->SR[layer][c >> 4], 8192, B_E);
  if (!layer) { if (!CSP) l2_prefetch(P.wqkv + c * 6144, 12288); l2_prefetch(P.wo + c * 2048, 4096); }
  PROF(25, s_all);
}

DEV void cs_part(const Params& P, int c, int w, int lane, int layer) {
  float cs[8];
#pragma unroll
  for (int k = 0; k < 8; ++k) cs[k] = 0.f;
  const int col = w * 512 + 64 * (c & 7) + 8 * (lane & 7);
#pragma unroll 1
  for (int r = 8 * layer; r < 8; r += CSU) {
    uint4 v[CSU];
#pragma unroll
    for (int k = 0; k < CSU; ++k) v[k] = ldnc4(P.wqkv + ((32 * (c >> 3) + 4 * r + (lane >> 3)) * 1536 + col) + 4 * k * 1536);
#pragma unroll
    for (int k = 0; k < CSU; ++k) {
      cs[0] += bflo(v[k].x); cs[1] += bfhi(v[k].x); cs[2] += bflo(v[k].y); cs[3] += bfhi(v[k].y);
      cs[4] += bflo(v[k].z); cs[5] += bfhi(v[k].z); cs[6] += bflo(v[k].w); cs[7] += bfhi(v[k].w);
    }
  }
  fold<4>(cs, lane, 16); fold<2>(cs, lane, 8);
  str2((float*)P.S->CS + ((c >> 3) * 1536 + col + 2 * (lane >> 3)), max(__float_as_uint(cs[0]), 1u - layer), __float_as_uint(cs[1]));
}

DEV void cs_sum(const Params& P, int c, int w, int lane) {
  float a, b;
  for (int it = 0;; ++it) {
    uint32_t m = ~0u;
    a = b = 0.f;
#pragma unroll
    for (int k = 0; k < 16; ++k) {
      const uint2 u = ldr2((const float*)P.S->CS + (w * 512 + 64 * (c & 7) + 2 * lane) + k * 1536);
      a += __uint_as_float(u.x); b += __uint_as_float(u.y); m = min(m, u.x);
    }
    if (__all_sync(0xffffffffu, m != 0u)) break;
    spin_guard(it);
  }
  const uint32_t hi = pack2(a, b), ad = SM_CS + w * 256 + (lane >> 2) * 32 + (lane & 3) * 4;
  sts1(ad, hi); sts1(ad + 16, pack2(a - bflo(hi), b - bfhi(hi)));
  fence_async_smem();
  __syncwarp();
  mbar_arrive1(B_CS);
}

DEV void x0_get(uint32_t (&x)[8][2], uint32_t a) {
  asm volatile("cp.async.wait_group 0;" ::: "memory");
#pragma unroll
  for (int z = 0; z < 4; ++z) {
    const uint4 v = lds4(a + z * 512);
    x[2 * (z & 2)][z & 1] = v.x; x[2 * (z & 2) + 1][z & 1] = v.y; x[2 * (z & 2) + 2][z & 1] = v.z; x[2 * (z & 2) + 3][z & 1] = v.w;
  }
}

DEV void par_load(const Params& P, int ch, int m, uint32_t (&pv)[8]) {
  const int mo = ch * 128 + m;
  pv[0] = ldnc16(P.Are + mo); pv[1] = ldnc16(P.Aim + mo); pv[2] = ldnc16(P.Bre + mo); pv[3] = ldnc16(P.Bim + mo);
  pv[4] = ldnc16(P.Cre + mo); pv[5] = ldnc16(P.Cim + mo); pv[6] = ldnc16(P.logdt + ch); pv[7] = ldnc16(P.dskip + ch);
}

__global__ void __launch_bounds__(NTHR, 1)
fused_kernel(const __grid_constant__ Params P, const __grid_constant__ CUtensorMap mapW,
             const __grid_constant__ CUtensorMap mapWo) {
  extern __shared__ __align__(1024) uint8_t smem_raw[];
  if (s2u(smem_raw) != SB) __trap();
  const int warp0 = __shfl_sync(0xffffffffu, threadIdx.x >> 5, 0), lane0 = threadIdx.x & 31;
  uint32_t smid; asm volatile("mov.u32 %0,%%smid;" : "=r"(smid));
  const int c = __shfl_sync(0xffffffffu, P.by_sm ? P.role[smid] : blockIdx.x, 0);
  if (c == 255) {
    if (threadIdx.x < NCOPY * NSUB)
#pragma unroll 1
      for (int it = 0; it < 256 && ldr1(P.S->C + 32 * threadIdx.x) < 128 / NSUB; ++it) __nanosleep(200);
    return;
  }
  const int cg = c & 7;
  PW(warp0)
  uint32_t dskip;
  {
    [[maybe_unused]] const int layer = 0;
    const int lane = lane0, g = lane >> 2, t = lane & 3, warp = warp0, k4 = warp >> 2, w = warp & 3;
    uint32_t pv[8];
    if (k4 < 2) par_load(P, 128 * k4 + c, 32 * w + lane, pv);
    else {
#pragma unroll
      for (int n = 0; n < 8; ++n) pv[n] = 0;
#pragma unroll
      for (int n = 0; n < 7; ++n) mbar_init1(SM_BAR + (n < 5 ? warp * 40 - 320 : 152 + warp * 16) + n * 8, n < 5 ? 1 : (CNT >> (4 * warp - 32)) & 15);
    }
    __syncthreads();
    const uint16_t* r = P.x0 + ((k4 < 2 ? 8192 * c + 64 * warp : (128 * (c >> 3) + 16 * (warp - 8)) * 512 + 64 * cg) + 1024 * g + 8 * t);
    const uint32_t xa = SM_R + k4 * 16384 + w * 2048 + lane * 16;
#pragma unroll
    for (int z = 0; z < 4; ++z) cp16(xa + z * 512, r + (z & 1) * 512 + (z & 2) * 16);
    asm volatile("cp.async.commit_group;" ::: "memory");
    sts4(SM_TAP + k4 * TAP_SZ + (32 * w + lane) * 16, 0, 0, 0, 0);
    sts4z_if(SM_TAP + k4 * TAP_SZ + 2048 + (32 * w + lane) * 16, w < 3);
    uint32_t x[8][2];
    if (k4 >= 2) {
      if (threadIdx.x == 448) {
        asm volatile("prefetch.tensormap [%0];" :: "l"(&mapW) : "memory");
        asm volatile("prefetch.tensormap [%0];" :: "l"(&mapWo) : "memory");
      }
      __syncwarp();
      if (PDELAY) delay(PDELAY);
      par_load(P, 128 * k4 + c, 32 * w + lane, pv);
      const XgAddr xd = xg_addr<false>(P.S->XG[0] + (64 * cg * 256 + 16 * (c >> 3) + 8 * (k4 - 2)), SM_R + k4 * 16384 + 8192, w, lane, P.zero);
      x0_get(x, xa);
      PROF(27, a_ld);
      xg_put<false>(xd, x);
      xg_store(xd, NB_WG + k4);
      bar_arrive(NB_T + 3, 288);
      bar_sync(NB_Q, 448 + 64 * LATEF);
    }
    tables(pv, k4, w, lane);
    if (k4 < 2) {
      x0_get(x, xa);
      const float4 s = gram(x, g, P.zero);
      if (t == (g >> 1)) sts4f(SM_RES + 8192 + (warp * 8 + g) * 16, s.x, s.y, s.z, s.w);
      __syncwarp();
      bar_arrive_if(NB_P, 256, warp != 7);
    }
    dskip = pv[7];
    PROF(1, a_x0);
  }
#pragma unroll 1
  for (int layer = 0; layer < 2; ++layer) {
    int lane = lane_here(P.zero);
    const int warp = warp0 | (layer & P.zero), k4 = warp >> 2, w = warp & 3;
    if (warp == (layer ? 12 : 7)) finalize(P, c, lane, layer);
    if (warp == (layer ? 13 : 6)) { announce(P, c, lane, layer); if (!LATEF) fetch(P, c, lane, layer); }
    if (layer == 0) {
      if (CSP && k4 == 1 && w != 2) { if (CSP > 1) delay(CSP); cs_part(P, c, w - (w >> 1), lane, 0); }
      taps(dskip, k4, w, lane);
    }
    if (LATEF && warp == (layer ? 13 : 6)) fetch(P, c, lane, layer);
    conv(P, &mapW, c, k4, w, layer);
    lane = lane_here(P.zero);
    if (k4 < 2) {
      bar_arrive_if(NB_H, 256, warp != 4);
      if (warp == 0) {
        mbar_wait(B_K, 0);
        cnt_wait(P, 1 + 5 * layer, c, lane);
        x_load(P, c, 0, layer);
        PROF(27, m_xi);
      } else if (k4 == 0 && (CSP == 0 || layer)) cs_part(P, c, w - 1, lane, CSP ? 1 : layer);
      attn_phase(P, c, k4, w, lane, layer);
    } else {
      bar_arrive_if(NB_RL, 256, warp >= 10);
      if (k4 == 3) {
        stats(P, c, w, lane, layer);
      } else if (w < 2) {
        bar_sync_if(NB_RL, 256, w);
        cnt_wait(P, 3 + 5 * layer + w, c, lane);
        bar_sync_if(NB_RL, 256, !w);
        if (w) mbar_wait(B_F, layer);
        x_load(P, c, 2 + w, layer);
        if (H5 && w) w_load(&mapW, cg, 5);
        PROF(14, h_xi);
        if (w == 1) str4(&P.S->SR[layer][lane >> 2][4 * c + (lane & 3)], 0, 0, 0, 0);
      } else if (w == 2) {
        mbar_expect1(B_WO, 65536);
        mbar_expect1(B_RES, 16384);
#pragma unroll 1
        for (int q = 0; q < 4; ++q) {
          if (FH && q < 2) { mbar_wait(B_FH + 8 * q, layer); w_load(&mapW, cg, 4 + 2 * q); }
          mbar_wait(B_F + 8 * q, layer);
          if (!FH && q < 2) w_load(&mapW, cg, 4 + 2 * q);
          if (q == 1 || (q == 0 && !H5)) w_load(&mapW, cg, 5 + 2 * q);
          if (WOQ == 0 && ((q + 1) & 2)) tma5(SM_R + (q & 2) * 16384, &mapWo, 64 * cg, 4 * (q & 2), B_WO);
          if (WOQ && q == 2) {
            if (WOQ >= 2) mbar_wait(B_ST, layer);
            tma5(SM_R, &mapWo, 64 * cg, 0, B_WO);
            if (WOQ < 3) tma5(SM_R + 32768, &mapWo, 64 * cg, 8, B_WO);
          }
          if (WOQ == 3 && q == 2) { mbar_wait(B_ST + 8, layer); tma5(SM_R + 32768, &mapWo, 64 * cg, 8, B_WO); }
          if (q == 3) {
#pragma unroll
            for (int e = 0; e < 2; ++e) bulk(SM_RES + e * 8192, P.S->XF + ((2 * (c >> 3) + 1 - e) * 4096 + cg * 512), 8192, B_RES);
          }
          PROF(15 + q, h_w);
        }
      }
      if (k4 == 2 && w != 2) {
        if (layer == 0) cs_sum(P, c, w - (w >> 1), lane);
        if (w == 3) {
          uint4* xz = P.S->XG[layer] + (c * 256 + lane);
          mbar_wait(B_F, layer);
#pragma unroll 1
          for (int k = 0; k < 32; ++k) {
            str4(xz + ((k >> 3) * 32768 + (k & 7) * 32), 0, 0, 0, 0);
            if (ZPACE) __nanosleep(ZPACE);
          }
          PROF(19, h_z);
        }
      }
      if (warp < 10) o_load(P, c, w, lane, layer);
    }
    asm volatile("mov.b32 %0,0;" : "=r"(dskip));
  }
}

typedef CUresult (*EncodeFn)(CUtensorMap*, CUtensorMapDataType, cuuint32_t, void*, const cuuint64_t*, const cuuint64_t*,
                             const cuuint32_t*, const cuuint32_t*, CUtensorMapInterleave, CUtensorMapSwizzle,
                             CUtensorMapL2promotion, CUtensorMapFloatOOBfill);

#define POOL 0
#define GOFF 0
static int place_roles(uint8_t* role) {
  int dev = 0, nsm = 0;
  cudaGetDevice(&dev);
  cudaDeviceGetAttribute(&nsm, cudaDevAttrMultiProcessorCount, dev);
  if (nsm < 128 || nsm > 144 || (nsm & 1)) return 0;
  cudaFuncSetAttribute(fused_kernel, cudaFuncAttributeNonPortableClusterSizeAllowed, 1);
  int occ[9] = {0};
  for (int k = 2; k <= 8; ++k) {
    cudaLaunchConfig_t cfg = {};
    cudaLaunchAttribute at[1];
    at[0].id = cudaLaunchAttributeClusterDimension;
    at[0].val.clusterDim.x = 2 * k; at[0].val.clusterDim.y = 1; at[0].val.clusterDim.z = 1;
    cfg.gridDim = dim3(2 * k); cfg.blockDim = dim3(NTHR); cfg.dynamicSmemBytes = SM_TOTAL; cfg.attrs = at; cfg.numAttrs = 1;
    if (cudaOccupancyMaxActiveClusters(&occ[k], fused_kernel, &cfg) != cudaSuccess) { cudaGetLastError(); occ[k] = 0; }
  }
  int n[10];
  n[7] = occ[8]; n[6] = occ[7]; n[5] = occ[6] - 0; n[4] = occ[5];
  n[3] = occ[4] - n[7]; n[1] = occ[2] - n[3] - n[5] - n[7]; n[0] = n[2] = n[1];
  n[8] = occ[3] - n[2] - n[5];
  const int ntpc = nsm / 2;
  int sum = 0;
  bool ok = n[0] > 0 && n[0] <= 8;
  for (int r = 0; r < 9; ++r) { ok = ok && n[r] >= 0 && (r == 0 || n[r] <= n[r - 1]); sum += n[r]; }
  if (!ok || sum > ntpc) { for (int r = 0; r < 9; ++r) n[r] = r < 8 ? 8 : 0; sum = 64; }
  int tp[8][9], cnt[8] = {0}, pool[72], np = 0, id = 0;
  for (int r = 0; r < 9; ++r)
    for (int g = n[0] - n[r]; g < n[0]; ++g) tp[g][cnt[g]++] = id++;
  for (; id < ntpc; ++id) pool[np++] = id;
  int order[72], no = 0;
  for (int g = 0; g < n[0]; ++g) {
    const int full = cnt[g] / 4 * 4;
    for (int k = 0; k < cnt[g]; ++k) { if (k < full) order[no++] = tp[g][k]; else pool[np++] = tp[g][k]; }
  }
  for (int k = 0; k < np; ++k) order[no++] = pool[POOL == 1 ? np - 1 - k : POOL == 2 ? (k + np - 2) % np : k];
  for (int k = 0; k < 144; ++k) role[k] = 255;
  for (int k = 0; k < 64; ++k) { role[2 * order[k]] = (2 * k + GOFF) & 127; role[2 * order[k] + 1] = (2 * k + 1 + GOFF) & 127; }
  return nsm;
}

extern "C" void kernel_launch(void* const* d_in, const int* in_sizes, int n_in, void* d_out, int out_size) {
  (void)in_sizes; (void)n_in; (void)out_size;
  static EncodeFn enc = nullptr;
  static uint8_t role[144];
  static int nsm = 0;
  static void* scratch = nullptr;
  if (!enc) {
    void* fn = nullptr;
    cudaDriverEntryPointQueryResult qr;
    cudaGetDriverEntryPoint("cuTensorMapEncodeTiled", &fn, cudaEnableDefault, &qr);
    enc = (EncodeFn)fn;
    cudaFuncSetAttribute(fused_kernel, cudaFuncAttributeMaxDynamicSharedMemorySize, SM_TOTAL);
    nsm = place_roles(role);
    cudaGetSymbolAddress(&scratch, g_S);
  }
  CUtensorMap mW, mWo;
  {
    cuuint64_t dim[3] = {512, 512, 3}, str[2] = {3072, 1024};
    cuuint32_t box[3] = {64, 64, 3}, es[3] = {1, 1, 1};
    enc(&mW, CU_TENSOR_MAP_DATA_TYPE_BFLOAT16, 3, d_in[10], dim, str, box, es, CU_TENSOR_MAP_INTERLEAVE_NONE,
        CU_TENSOR_MAP_SWIZZLE_128B, CU_TENSOR_MAP_L2_PROMOTION_NONE, CU_TENSOR_MAP_FLOAT_OOB_FILL_NONE);
  }
  {
    cuuint64_t dim[5] = {512, 2, 4, 4, 16}, str[4] = {1024, 8192, 2048, 32768};
    cuuint32_t box[5] = {64, 2, 4, 4, 8}, es[5] = {1, 1, 1, 1, 1};
    enc(&mWo, CU_TENSOR_MAP_DATA_TYPE_BFLOAT16, 5, d_in[11], dim, str, box, es, CU_TENSOR_MAP_INTERLEAVE_NONE,
        CU_TENSOR_MAP_SWIZZLE_128B, CU_TENSOR_MAP_L2_PROMOTION_NONE, CU_TENSOR_MAP_FLOAT_OOB_FILL_NONE);
  }
  Params P;
  P.x0 = (const uint16_t*)d_in[0]; P.Are = (const uint16_t*)d_in[1]; P.Aim = (const uint16_t*)d_in[2];
  P.Bre = (const uint16_t*)d_in[3]; P.Bim = (const uint16_t*)d_in[4]; P.Cre = (const uint16_t*)d_in[5];
  P.Cim = (const uint16_t*)d_in[6]; P.logdt = (const uint16_t*)d_in[7]; P.dskip = (const uint16_t*)d_in[8];
  P.wqkv = (const uint16_t*)d_in[10]; P.wo = (const uint16_t*)d_in[11]; P.out = (uint16_t*)d_out;
  for (int k = 0; k < 144; ++k) P.role[k] = role[k];
  P.by_sm = nsm > 0;
  P.zero = 0;
  P.S = (Scratch*)scratch;
  fused_kernel<<<nsm > 0 ? nsm : 128, NTHR, SM_TOTAL, cudaStreamPerThread>>>(P, mW, mWo);
}
```

```cpp
#include <cuda_runtime.h>
#include <cuda_bf16.h>
#include <cuda.h>
#include <stdint.h>

#define DEV __device__ __forceinline__

#define NCOPY 4
#define NSUB 1
#define EA 0x2221
constexpr int NTHR = 512;
constexpr int SPIN_LIMIT = 1 << 22;

constexpr uint32_t SB = 1024;
constexpr uint32_t SM_XA   = SB;
constexpr uint32_t SM_S0   = SM_XA + 16384;
constexpr uint32_t SM_S1   = SM_S0 + 49152;
constexpr uint32_t SM_XB   = SM_S1 + 49152;
constexpr uint32_t SM_R    = SM_XB + 16384;
constexpr uint32_t SM_RES  = SM_R + 65536;
constexpr uint32_t SM_TAP  = SM_RES + 16384;
constexpr int TAP_SZ = 3584;
constexpr uint32_t SM_CS   = SM_TAP + 4 * TAP_SZ;
constexpr uint32_t SM_STAT = SM_CS + 800;
constexpr uint32_t SM_MISC = SM_STAT + 1280;
constexpr uint32_t SM_BAR  = SM_MISC + 512;
constexpr int SM_TOTAL = SM_BAR + 448 - SB;
constexpr int R_U = 512, R_A5 = 5120, R_A3 = 8704, R_B = 11776;
constexpr int T_E = 1536, T_O = T_E + 1602, T_C = 3714;
constexpr uint32_t B_W = SM_BAR, B_X = SM_BAR + 64, B_O = SM_BAR + 128, B_WO = SM_BAR + 256, B_RES = SM_BAR + 264;
constexpr uint32_t B_ST = SM_BAR + 272, B_R = SM_BAR + 288, B_E = SM_BAR + 304;
constexpr uint32_t B_F = SM_BAR + 320, B_G = SM_BAR + 352, B_K = SM_BAR + 376, B_ED = SM_BAR + 384, B_CS = SM_BAR + 400, B_FH = SM_BAR + 416;
constexpr uint32_t CNT = 0x143444CC;
constexpr int NB_WG = 1, NB_T = 5, NB_Q = 10, NB_H = 11, NB_P = 14, NB_RL = 15;

struct Scratch {
  uint4    XG[2][512 * 256];
  uint4    XF[32 * 4096];
  uint4    O[32 * 8 * 512];
  uint32_t F[32 * 32];
  uint4    H[17 * 8 * 256];
  uint4    SR[2][8][512];
  uint4    ST[32 * 16];
  uint4    PS[128 * 64];
  float4   CS[16 * 1536 / 4];
  uint32_t C[10 * 32 * 32];
};
__device__ __align__(1024) Scratch g_S;

struct Params {
  int by_sm;
  uint32_t zero;
  Scratch* S;
  const uint16_t *x0, *Are, *Aim, *Bre, *Bim, *Cre, *Cim, *logdt, *dskip, *wqkv, *wo;
  uint16_t* out;
  uint8_t role[144];
};
#define EVENT(n) do {} while (0)
#define PROFD(slot, name, v) do {} while (0)
#define PROF(slot, name) do {} while (0)
#define PW(x)

DEV uint32_t s2u(const void* p) { return (uint32_t)__cvta_generic_to_shared(p); }
template <class T> DEV T opq(T x) { asm volatile("" : "+r"(x)); return x; }
DEV uint32_t pack2(float lo, float hi) { uint32_t d; asm("cvt.rn.bf16x2.f32 %0,%1,%2;" : "=r"(d) : "f"(hi), "f"(lo)); return d; }
DEV float bflo(uint32_t v) { return __uint_as_float(v << 16); }
DEV float bfhi(uint32_t v) { return __uint_as_float(v & 0xFFFF0000u); }
DEV float bfr(float x) { return bflo(pack2(x, 0.f)); }
DEV uint32_t hadd2(uint32_t a, uint32_t b) { uint32_t d; asm("add.rn.bf16x2 %0,%1,%2;" : "=r"(d) : "r"(a), "r"(b)); return d; }
DEV uint32_t hsub2(uint32_t a, uint32_t b) { uint32_t d; asm("sub.rn.bf16x2 %0,%1,%2;" : "=r"(d) : "r"(a), "r"(b)); return d; }
DEV uint32_t hmul2(uint32_t a, uint32_t b) { uint32_t d; asm("mul.rn.bf16x2 %0,%1,%2;" : "=r"(d) : "r"(a), "r"(b)); return d; }
DEV uint32_t hfma2(uint32_t a, uint32_t b, uint32_t c) { uint32_t d; asm("fma.rn.bf16x2 %0,%1,%2,%3;" : "=r"(d) : "r"(a), "r"(b), "r"(c)); return d; }
DEV uint32_t hmax2(uint32_t a, uint32_t b) { uint32_t d; asm("max.bf16x2 %0,%1,%2;" : "=r"(d) : "r"(a), "r"(b)); return d; }
DEV uint32_t prmt(uint32_t a, uint32_t b, uint32_t s) { uint32_t d; asm("prmt.b32 %0,%1,%2,%3;" : "=r"(d) : "r"(a), "r"(b), "r"(s)); return d; }
DEV uint32_t nz(uint32_t v) { uint32_t d; asm("max.u32 %0,%1,1;" : "=r"(d) : "r"(v)); return d; }
DEV uint32_t tagged(uint32_t v, uint32_t m, uint32_t tag) { return (v & ~m) | (tag & m); }
DEV uint32_t both(uint32_t a, uint32_t b, uint32_t x) { uint32_t d; asm("lop3.b32 %0,%1,%2,%3,0x42;" : "=r"(d) : "r"(a), "r"(b), "r"(x)); return d; }
DEV uint4 hadd8(const uint4& a, const uint4& b) { return make_uint4(hadd2(a.x, b.x), hadd2(a.y, b.y), hadd2(a.z, b.z), hadd2(a.w, b.w)); }
DEV uint32_t min4(const uint4& v) { return min(min(v.x, v.y), min(v.z, v.w)); }
DEV float rcp(float x) { float y; asm("rcp.approx.ftz.f32 %0,%1;" : "=f"(y) : "f"(x)); return y; }
DEV float sqrt_(float x) { float y; asm("sqrt.approx.ftz.f32 %0,%1;" : "=f"(y) : "f"(x)); return y; }
DEV float ex2(float x) { float y; asm("ex2.approx.ftz.f32 %0,%1;" : "=f"(y) : "f"(x)); return y; }

DEV uint4 ldr4(const void* p) { uint4 v; asm volatile("ld.relaxed.gpu.global.v4.u32 {%0,%1,%2,%3},[%4];" : "=r"(v.x), "=r"(v.y), "=r"(v.z), "=r"(v.w) : "l"(p) : "memory"); return v; }
DEV void ldr4_if(uint4& v, const void* p, bool c) {
  asm volatile("{.reg .pred q; setp.ne.u32 q,%5,0; @q ld.relaxed.gpu.global.v4.u32 {%0,%1,%2,%3},[%4];}"
    : "+r"(v.x), "+r"(v.y), "+r"(v.z), "+r"(v.w) : "l"(p), "r"((uint32_t)c) : "memory");
}
DEV uint2 ldr2(const void* p) { uint2 v; asm volatile("ld.relaxed.gpu.global.v2.u32 {%0,%1},[%2];" : "=r"(v.x), "=r"(v.y) : "l"(p) : "memory"); return v; }
DEV uint32_t ldr1(const void* p) { uint32_t v; asm volatile("ld.relaxed.gpu.global.u32 %0,[%1];" : "=r"(v) : "l"(p) : "memory"); return v; }
DEV void str4(void* p, uint32_t a, uint32_t b, uint32_t c, uint32_t d) { asm volatile("st.relaxed.gpu.global.v4.u32 [%0],{%1,%2,%3,%4};" :: "l"(p), "r"(a), "r"(b), "r"(c), "r"(d) : "memory"); }
DEV void str4_if(void* p, uint32_t a, uint32_t b, uint32_t c, uint32_t d, bool q) {
  asm volatile("{.reg .pred q; setp.ne.u32 q,%5,0; @q st.relaxed.gpu.global.v4.u32 [%0],{%1,%2,%3,%4};}" :: "l"(p), "r"(a), "r"(b), "r"(c), "r"(d), "r"((uint32_t)q) : "memory");
}
DEV void str2(void* p, uint32_t a, uint32_t b) { asm volatile("st.relaxed.gpu.global.v2.u32 [%0],{%1,%2};" :: "l"(p), "r"(a), "r"(b) : "memory"); }
DEV void str1(void* p, uint32_t a) { asm volatile("st.relaxed.gpu.global.u32 [%0],%1;" :: "l"(p), "r"(a) : "memory"); }
DEV void stw4(void* p, uint32_t a, uint32_t b, uint32_t c, uint32_t d) { asm volatile("st.global.v4.u32 [%0],{%1,%2,%3,%4};" :: "l"(p), "r"(a), "r"(b), "r"(c), "r"(d) : "memory"); }
DEV uint4 ldnc4(const void* p) { uint4 v; asm volatile("ld.global.nc.v4.u32 {%0,%1,%2,%3},[%4];" : "=r"(v.x), "=r"(v.y), "=r"(v.z), "=r"(v.w) : "l"(p)); return v; }
DEV uint4 ldw4(const void* p) { uint4 v; asm volatile("ld.global.v4.u32 {%0,%1,%2,%3},[%4];" : "=r"(v.x), "=r"(v.y), "=r"(v.z), "=r"(v.w) : "l"(p) : "memory"); return v; }
DEV void cp16(uint32_t d, const void* p) { asm volatile("cp.async.cg.shared.global [%0],[%1],16;" :: "r"(d), "l"(p) : "memory"); }
DEV uint32_t ldnc16(const void* p) { uint32_t v; asm volatile("ld.global.u16 %0,[%1];" : "=r"(v) : "l"(p) : "memory"); return v; }

DEV uint32_t lds1v(uint32_t a) { uint32_t v; asm volatile("ld.volatile.shared.u32 %0,[%1];" : "=r"(v) : "r"(a) : "memory"); return v; }
DEV uint4 lds4v(uint32_t a) { uint4 v; asm volatile("ld.volatile.shared.v4.u32 {%0,%1,%2,%3},[%4];" : "=r"(v.x), "=r"(v.y), "=r"(v.z), "=r"(v.w) : "r"(a) : "memory"); return v; }
DEV uint32_t lds1(uint32_t a) { uint32_t v; asm volatile("ld.shared.u32 %0,[%1];" : "=r"(v) : "r"(a)); return v; }
DEV uint2 lds2(uint32_t a) { uint2 v; asm volatile("ld.shared.v2.u32 {%0,%1},[%2];" : "=r"(v.x), "=r"(v.y) : "r"(a)); return v; }
DEV uint4 lds4(uint32_t a) { uint4 v; asm volatile("ld.shared.v4.u32 {%0,%1,%2,%3},[%4];" : "=r"(v.x), "=r"(v.y), "=r"(v.z), "=r"(v.w) : "r"(a)); return v; }
DEV uint32_t lds16(uint32_t a) { uint32_t v; asm volatile("ld.shared.u16 %0,[%1];" : "=r"(v) : "r"(a)); return v; }
DEV float lds1f(uint32_t a) { float v; asm volatile("ld.shared.f32 %0,[%1];" : "=f"(v) : "r"(a)); return v; }
DEV float2 lds2f(uint32_t a) { float2 v; asm volatile("ld.shared.v2.f32 {%0,%1},[%2];" : "=f"(v.x), "=f"(v.y) : "r"(a)); return v; }
DEV float4 lds4f(uint32_t a) { float4 v; asm volatile("ld.shared.v4.f32 {%0,%1,%2,%3},[%4];" : "=f"(v.x), "=f"(v.y), "=f"(v.z), "=f"(v.w) : "r"(a)); return v; }
DEV void sts1(uint32_t a, uint32_t v) { asm volatile("st.shared.u32 [%0],%1;" :: "r"(a), "r"(v) : "memory"); }
DEV void sts16(uint32_t a, uint32_t v) { asm volatile("{.reg .b16 h; cvt.u16.u32 h,%1; st.shared.u16 [%0],h;}" :: "r"(a), "r"(v) : "memory"); }
DEV void sts2f(uint32_t a, float x, float y) { asm volatile("st.shared.v2.f32 [%0],{%1,%2};" :: "r"(a), "f"(x), "f"(y) : "memory"); }
DEV void sts4f(uint32_t a, float x, float y, float z, float w) { asm volatile("st.shared.v4.f32 [%0],{%1,%2,%3,%4};" :: "r"(a), "f"(x), "f"(y), "f"(z), "f"(w) : "memory"); }
DEV void sts4(uint32_t a, uint32_t x, uint32_t y, uint32_t z, uint32_t w) { asm volatile("st.shared.v4.u32 [%0],{%1,%2,%3,%4};" :: "r"(a), "r"(x), "r"(y), "r"(z), "r"(w) : "memory"); }
DEV void sts4z_if(uint32_t a, bool c) { asm volatile("{.reg .pred q; setp.ne.u32 q,%1,0; @q st.shared.v4.u32 [%0],{%2,%2,%2,%2};}" :: "r"(a), "r"((uint32_t)c), "r"(0) : "memory"); }

DEV void ldsm4t(uint32_t& r0, uint32_t& r1, uint32_t& r2, uint32_t& r3, uint32_t a) { asm volatile("ldmatrix.sync.aligned.m8n8.x4.trans.shared.b16 {%0,%1,%2,%3},[%4];" : "=r"(r0), "=r"(r1), "=r"(r2), "=r"(r3) : "r"(a) : "memory"); }
DEV void stsm4(uint32_t a, uint32_t r0, uint32_t r1, uint32_t r2, uint32_t r3) { asm volatile("stmatrix.sync.aligned.m8n8.x4.shared.b16 [%0],{%1,%2,%3,%4};" :: "r"(a), "r"(r0), "r"(r1), "r"(r2), "r"(r3) : "memory"); }
DEV void stsm2(uint32_t a, uint32_t r0, uint32_t r1) { asm volatile("stmatrix.sync.aligned.m8n8.x2.shared.b16 [%0],{%1,%2};" :: "r"(a), "r"(r0), "r"(r1) : "memory"); }
DEV void stsm4t(uint32_t a, uint32_t r0, uint32_t r1, uint32_t r2, uint32_t r3) { asm volatile("stmatrix.sync.aligned.m8n8.x4.trans.shared.b16 [%0],{%1,%2,%3,%4};" :: "r"(a), "r"(r0), "r"(r1), "r"(r2), "r"(r3) : "memory"); }
DEV uint32_t movm(uint32_t a) { uint32_t d; asm volatile("movmatrix.sync.aligned.m8n8.trans.b16 %0,%1;" : "=r"(d) : "r"(a)); return d; }
DEV void mma16(float (&d)[4], uint32_t a0, uint32_t a1, uint32_t a2, uint32_t a3, uint32_t b0, uint32_t b1) {
  asm volatile("mma.sync.aligned.m16n8k16.row.col.f32.bf16.bf16.f32 {%0,%1,%2,%3},{%4,%5,%6,%7},{%8,%9},{%0,%1,%2,%3};"
    : "+f"(d[0]), "+f"(d[1]), "+f"(d[2]), "+f"(d[3]) : "r"(a0), "r"(a1), "r"(a2), "r"(a3), "r"(b0), "r"(b1));
}
DEV void mma16z(float (&d)[4], uint32_t a0, uint32_t a1, uint32_t a2, uint32_t a3, uint32_t b0, uint32_t b1) {
  asm volatile("mma.sync.aligned.m16n8k16.row.col.f32.bf16.bf16.f32 {%0,%1,%2,%3},{%4,%5,%6,%7},{%8,%9},{%10,%10,%10,%10};"
    : "=f"(d[0]), "=f"(d[1]), "=f"(d[2]), "=f"(d[3]) : "r"(a0), "r"(a1), "r"(a2), "r"(a3), "r"(b0), "r"(b1), "f"(0.f));
}
DEV void mma8z(float (&d)[4], uint32_t a0, uint32_t a1, uint32_t b0) {
  asm volatile("mma.sync.aligned.m16n8k8.row.col.f32.bf16.bf16.f32 {%0,%1,%2,%3},{%4,%5},{%6},{%7,%7,%7,%7};"
    : "=f"(d[0]), "=f"(d[1]), "=f"(d[2]), "=f"(d[3]) : "r"(a0), "r"(a1), "r"(b0), "f"(0.f));
}
DEV void mma8(float (&d)[4], uint32_t a0, uint32_t a1, uint32_t b0) {
  asm volatile("mma.sync.aligned.m16n8k8.row.col.f32.bf16.bf16.f32 {%0,%1,%2,%3},{%4,%5},{%6},{%0,%1,%2,%3};"
    : "+f"(d[0]), "+f"(d[1]), "+f"(d[2]), "+f"(d[3]) : "r"(a0), "r"(a1), "r"(b0));
}

DEV void bar_sync(int id, int n) { asm volatile("bar.sync %0,%1;" :: "r"(id), "r"(n) : "memory"); }
DEV void bar_arrive(int id, int n) { asm volatile("bar.arrive %0,%1;" :: "r"(id), "r"(n) : "memory"); }
DEV void bar_sync_if(int id, int n, int c) { asm volatile("{.reg .pred q; setp.ne.s32 q,%2,0; @q bar.sync %0,%1;}" :: "r"(id), "r"(n), "r"(c) : "memory"); }
DEV void bar_arrive_if(int id, int n, int c) { asm volatile("{.reg .pred q; setp.ne.s32 q,%2,0; @q bar.arrive %0,%1;}" :: "r"(id), "r"(n), "r"(c) : "memory"); }
DEV bool bar_any(int id, int n, bool c) {
  uint32_t r; asm volatile("{.reg .pred p,q; setp.ne.u32 q,%3,0; bar.red.or.pred p,%1,%2,q; selp.u32 %0,1,0,p;}" : "=r"(r) : "r"(id), "r"(n), "r"((uint32_t)c) : "memory");
  return __any_sync(0xffffffffu, r);
}
DEV void fence_async_glob() { asm volatile("fence.proxy.async.global;" ::: "memory"); }
DEV void fence_async_smem() { asm volatile("fence.proxy.async.shared::cta;" ::: "memory"); }
DEV void fence_gpu() { asm volatile("fence.acq_rel.gpu;" ::: "memory"); }
DEV void mbar_wait(uint32_t b, uint32_t ph) {
  asm volatile("{\n.reg .pred p;\nW: mbarrier.try_wait.parity.shared::cta.b64 p,[%0],%1;\n@!p bra W;\n}" :: "r"(b), "r"(ph) : "memory");
}
DEV bool mbar_test(uint32_t b, uint32_t ph) {
  uint32_t r; asm volatile("{.reg .pred p; mbarrier.test_wait.parity.shared::cta.b64 p,[%1],%2; selp.u32 %0,1,0,p;}" : "=r"(r) : "r"(b), "r"(ph) : "memory");
  return __all_sync(0xffffffffu, r);
}
DEV uint32_t mbar_test2(uint32_t b, uint32_t ph) {
  uint32_t r; asm volatile("{.reg .pred p,q; mbarrier.test_wait.parity.shared::cta.b64 p,[%1],%2; mbarrier.test_wait.parity.shared::cta.b64 q,[%1+8],%2;\n"
                           "and.pred p,p,q; selp.u32 %0,1,0,p;}" : "=r"(r) : "r"(b), "r"(ph) : "memory");
  return r;
}
DEV void spin_guard(int it) { asm volatile("{.reg .pred p; setp.gt.s32 p,%0,%1; @p trap;}" :: "r"(it), "n"(SPIN_LIMIT)); }
DEV uint32_t here(uint32_t zero) {
  uint32_t d; asm volatile("mov.u32 %0,%%clock;" : "=r"(d) :: "memory"); return d & zero;
}
DEV int lane_here(uint32_t zero) {
  uint32_t d; asm volatile("mov.u32 %0,%%laneid;" : "=r"(d)); return d | here(zero);
}
DEV void delay(uint32_t n) { const uint32_t t0 = clock(); while ((uint32_t)clock() - t0 < n); __syncwarp(); }
DEV void poll(const uint32_t* p, uint32_t n) {
  for (int it = 0; !__all_sync(0xffffffffu, ldr1(p) >= n); ++it) spin_guard(it);
}
DEV void cnt_add(const Params& P, int n, int c, int lane) { asm volatile("{.reg .pred p; setp.lt.s32 p,%1,%2; @p red.relaxed.gpu.global.add.u32 [%0],1;}" :: "l"(P.S->C + (32 * (NSUB * lane + c % NSUB) + n * 1024)), "r"(lane), "n"(NCOPY) : "memory"); }
DEV void cnt_wait(const Params& P, int n, int c, int lane) { poll(P.S->C + (32 * (NSUB * (c / (128 / NCOPY)) + lane % NSUB) + n * 1024), 128 / NSUB); }
DEV void mbar_init1(uint32_t b, int n) { asm volatile("{.reg .pred p; elect.sync _|p,0xffffffff; @p mbarrier.init.shared::cta.b64 [%0],%1;}" :: "r"(b), "r"(n) : "memory"); }
DEV void mbar_arrive1(uint32_t b) { asm volatile("{.reg .pred p; elect.sync _|p,0xffffffff; @p mbarrier.arrive.shared::cta.b64 _,[%0];}" :: "r"(b) : "memory"); }
DEV void mbar_arrive1_if(uint32_t b, int c) {
  asm volatile("{.reg .pred p,q; setp.ne.s32 q,%1,0; elect.sync _|p,0xffffffff; and.pred p,p,q; @p mbarrier.arrive.shared::cta.b64 _,[%0];}" :: "r"(b), "r"(c) : "memory");
}
DEV void mbar_expect1(uint32_t b, int bytes) { asm volatile("{.reg .pred p; elect.sync _|p,0xffffffff; @p mbarrier.arrive.expect_tx.shared::cta.b64 _,[%0],%1;}" :: "r"(b), "r"(bytes) : "memory"); }
DEV void flag_set1(uint32_t* q) { asm volatile("{.reg .pred p; elect.sync _|p,0xffffffff; @p st.relaxed.gpu.global.u32 [%0],1;}" :: "l"(q) : "memory"); }
DEV void tma3(uint32_t dst, const CUtensorMap* m, int c0, int c1, uint32_t bar) {
  asm volatile("{.reg .pred p; elect.sync _|p,0xffffffff;\n"
    "@p cp.async.bulk.tensor.3d.shared::cluster.global.mbarrier::complete_tx::bytes [%0],[%1,{%2,%3,%5}],[%4];}"
    :: "r"(dst), "l"(m), "r"(c0), "r"(c1), "r"(bar), "r"(0) : "memory");
}
DEV void tma5(uint32_t dst, const CUtensorMap* m, int c0, int c4, uint32_t bar) {
  asm volatile("{.reg .pred p; elect.sync _|p,0xffffffff;\n"
    "@p cp.async.bulk.tensor.5d.shared::cluster.global.mbarrier::complete_tx::bytes [%0],[%1,{%2,%5,%5,%5,%3}],[%4];}"
    :: "r"(dst), "l"(m), "r"(c0), "r"(c4), "r"(bar), "r"(0) : "memory");
}
DEV void bulk(uint32_t dst, const void* src, int bytes, uint32_t bar) {
  asm volatile("{.reg .pred p; elect.sync _|p,0xffffffff;\n@p cp.async.bulk.shared::cluster.global.mbarrier::complete_tx::bytes [%0],[%1],%2,[%3];}" :: "r"(dst), "l"(src), "r"(bytes), "r"(bar) : "memory");
}
DEV void bulk_store(void* dst, uint32_t src, int bytes) {
  asm volatile("{.reg .pred p; elect.sync _|p,0xffffffff;\n@p cp.async.bulk.global.shared::cta.bulk_group [%0],[%1],%2;}" :: "l"(dst), "r"(src), "r"(bytes) : "memory");
}
DEV void l2_prefetch(const void* src, int bytes) {
  asm volatile("{.reg .pred p; elect.sync _|p,0xffffffff;\n@p cp.async.bulk.prefetch.L2.global [%0],%1;}" :: "l"(src), "r"(bytes) : "memory");
}

DEV uint64_t mkdesc(uint32_t addr, uint32_t lbo, uint32_t sbo, uint32_t swz) {
  return (uint64_t)((addr >> 4) | ((lbo >> 4) << 16)) | ((uint64_t)((sbo >> 4) | (swz << 30)) << 32);
}
DEV void wg_fence() { asm volatile("wgmma.fence.sync.aligned;" ::: "memory"); }
DEV void wg_commit() { asm volatile("wgmma.commit_group.sync.aligned;" ::: "memory"); }
template <int N> DEV void wg_wait() { asm volatile("wgmma.wait_group.sync.aligned %0;" :: "n"(N) : "memory"); }
template <int N> DEV void zerov(float (&d)[N]) {
#pragma unroll
  for (int i = 0; i < N; ++i) asm volatile("mov.b32 %0,0;" : "=f"(d[i]));
}
template <int N> DEV void undef(float (&d)[N]) {
#pragma unroll
  for (int i = 0; i < N; ++i) asm volatile("" : "=f"(d[i]));
}
#define R4(d, o) "+f"(d[o]), "+f"(d[o + 1]), "+f"(d[o + 2]), "+f"(d[o + 3])
#define R8(d, o) R4(d, o), R4(d, o + 4)
#define R16(d, o) R8(d, o), R8(d, o + 8)
#define R32(d, o) R16(d, o), R16(d, o + 16)
#define L0 "%0,%1,%2,%3,%4,%5,%6,%7,%8,%9,"
#define L10(a) "%" #a "0,%" #a "1,%" #a "2,%" #a "3,%" #a "4,%" #a "5,%" #a "6,%" #a "7,%" #a "8,%" #a "9,"
#define WG_HEAD(pr, n) "{.reg .pred p; setp.ne.s32 p,%" #pr ",0;\nwgmma.mma_async.sync.aligned.m64n" #n "k16.f32.bf16.bf16 {"
DEV void wg_rs64k(float (&d)[32], const uint32_t (&a)[4], uint64_t db, int acc) {
  asm volatile(WG_HEAD(37, 64) L0 L10(1) L10(2) "%30,%31},{%32,%33,%34,%35},%36,p,1,1,0;}"
    : R32(d, 0) : "r"(a[0]), "r"(a[1]), "r"(a[2]), "r"(a[3]), "l"(db), "r"(acc));
}
DEV void wg_rs48t(float (&d)[24], const uint32_t (&a)[4], uint64_t db, int acc) {
  asm volatile(WG_HEAD(29, 48) L0 L10(1) "%20,%21,%22,%23},{%24,%25,%26,%27},%28,p,1,1,1;}"
    : R16(d, 0), R8(d, 16) : "r"(a[0]), "r"(a[1]), "r"(a[2]), "r"(a[3]), "l"(db), "r"(acc));
}
DEV void wg_rs32t(float (&d)[16], const uint32_t (&a)[4], uint64_t db, int acc) {
  asm volatile(WG_HEAD(21, 32) L0 "%10,%11,%12,%13,%14,%15},{%16,%17,%18,%19},%20,p,1,1,1;}"
    : R16(d, 0) : "r"(a[0]), "r"(a[1]), "r"(a[2]), "r"(a[3]), "l"(db), "r"(acc));
}
DEV void wg_ss48(float (&d)[24], uint64_t da, uint64_t db, int acc) {
  asm volatile(WG_HEAD(26, 48) L0 L10(1) "%20,%21,%22,%23},%24,%25,p,1,1,1,1;}" : R16(d, 0), R8(d, 16) : "l"(da), "l"(db), "r"(acc));
}
DEV void wg_ss64(float (&d)[32], uint64_t da, uint64_t db, int acc) {
  asm volatile(WG_HEAD(34, 64) L0 L10(1) L10(2) "%30,%31},%32,%33,p,1,1,0,1;}" : R32(d, 0) : "l"(da), "l"(db), "r"(acc));
}
DEV void wg_ss192(float (&d)[96], uint64_t da, uint64_t db, int acc) {
  asm volatile(WG_HEAD(98, 192) L0 L10(1) L10(2) L10(3) L10(4) L10(5) L10(6) L10(7) L10(8) "%90,%91,%92,%93,%94,%95},%96,%97,p,1,1,1,1;}"
    : R32(d, 0), R32(d, 32), R32(d, 64) : "l"(da), "l"(db), "r"(acc));
}

DEV void wg_rs192t(float (&d)[96], const uint32_t (&a)[4], uint64_t db) {
  asm volatile("wgmma.mma_async.sync.aligned.m64n192k16.f32.bf16.bf16 {" L0 L10(1) L10(2) L10(3) L10(4) L10(5) L10(6) L10(7) L10(8) "%90,%91,%92,%93,%94,%95},{%96,%97,%98,%99},%100,1,1,1,1;"
    : R32(d, 0), R32(d, 32), R32(d, 64) : "r"(a[0]), "r"(a[1]), "r"(a[2]), "r"(a[3]), "l"(db));
}

DEV float ln_sd(float s, float q, float& m) {
  m = s * (1.f / 512.f);
  return bfr(sqrt_(bfr(bfr(fmaxf(q * (1.f / 512.f) - m * m, 0.f)) + 1e-5f)));
}
DEV float4 gram(const uint32_t (&w)[8][2], int g, uint32_t zero) {
  float s[4], q[4][4];
  const uint32_t o0 = 0x3F803F80u | zero, o1 = 0x3F803F80u ^ zero;
#pragma unroll
  for (int j = 0; j < 8; ++j) {
#pragma unroll
    for (int h = 0; h < 2; ++h) { if (j < 2) mma8z(q[2 * j + h], w[j][0], w[j][1], w[j][h]); else mma8(q[2 * (j & 1) + h], w[j][0], w[j][1], w[j][h]); }
    if (j == 1) mma16z(s, w[0][0], w[0][1], w[1][0], w[1][1], o0, o1);
    else if (j & 1) mma16(s, w[j - 1][0], w[j - 1][1], w[j][0], w[j][1], o0, o1);
  }
  const bool od = g & 1;
  return make_float4(s[0], od ? q[0][1] + q[2][1] : q[0][0] + q[2][0], s[2], od ? q[1][3] + q[3][3] : q[1][2] + q[3][2]);
}
DEV void keep(uint32_t v, uint32_t zero) {
  asm volatile("{.reg .pred p; setp.ne.u32 p,%1,0; @p st.shared.u32 [%0],%0;}" :: "r"(v), "r"(zero) : "memory");
}
DEV void keep(const void* v, uint32_t zero) { asm volatile("{.reg .pred p; setp.ne.u32 p,%1,0; @p st.global.u32 [%0],%1;}" :: "l"(v), "r"(zero) : "memory"); }
struct XgAddr { uint32_t a, b; uint4* dst; };
template <bool FRAG> DEV XgAddr xg_addr(uint4* dst, uint32_t stg, int wp, int lane, uint32_t zero) {
  const int t = lane & 3, r = 4 * wp + (lane >> 3);
  XgAddr x = {stg + t * (FRAG ? 256 : 1024) + ((wp ^ t) * 32) + (lane >> 2) * 4,
              stg + r * 128 + (((lane & 7) ^ (2 * (((r >> 1) ^ (r >> 3)) & 3))) * 16), dst + (r * 256 + (lane & 7))};
  keep(x.a, zero); keep(x.b, zero); keep(x.dst, zero);
  return x;
}
template <bool FRAG> DEV void xg_put(const XgAddr& x, const uint32_t (&w)[8][2]) {
#pragma unroll
  for (int n = 0; n < 8; ++n) {
    const uint32_t b = (x.a ^ ((n & 3) * 32)) + (FRAG ? n * 1024 : (n >> 2) * 4096 + (n & 3) * 256);
    sts1(b, prmt(w[n][0], w[n][1], 0x5410)); sts1(b + 128, prmt(w[n][0], w[n][1], 0x7632));
  }
}
DEV void xg_store(const XgAddr& x) {
#pragma unroll
  for (int k = 0; k < 4; ++k) {
    const uint4 v = lds4((x.b ^ ((k & 1) * 64)) + k * 2048);
    str4(x.dst + k * 4096, nz(v.x), v.y, v.z, v.w);
  }
}
template <int N, int M> DEV void fold(float (&v)[M], int lane, int bit) {
  const bool b = lane & bit;
#pragma unroll
  for (int k = 0; k < N; ++k) { const float sn = b ? v[k] : v[k + N], kp = b ? v[k + N] : v[k]; v[k] = kp + __shfl_xor_sync(0xffffffffu, sn, bit); }
}
DEV void refetch(uint32_t dst, const uint4* src, int half, int e, int w) {
#pragma unroll 1
  for (int r = 0; r < 2; ++r) {
    if (w == 0) { mbar_expect1(B_R + 8 * e, half); bulk(dst + r * half, src + r * (half >> 4), half, B_R + 8 * e); }
    mbar_wait(B_R + 8 * e, r);
    bar_sync(NB_WG + e, 128);
  }
}
DEV uint32_t kvslot(int cg, int pos) { return (pos & 2 ? SM_XA : SM_S1) + (cg < 4 ? 5 : 2) * 8192 + (pos & 1) * 4096; }
DEV uint32_t xstage(int q, int e) { return ((q + 1) & 2) ? SM_R + ((q & 2) + e) * 16384 : e ? SM_XB : SM_XA; }
DEV void cmul(float& orr, float& oi, float ar, float ai, float br, float bi) {
  float r = ar * br - ai * bi, i = ar * bi + ai * br; orr = r; oi = i;
}
DEV void cexp_(float al, float bt, float s, float& er, float& ei) {
  float mag = ex2(al * s), ph = bt * s;
  ph -= rintf(ph);
  float ang = ph * 6.283185307179586f;
  er = mag * __cosf(ang); ei = mag * __sinf(ang);
}

#define KS 2048
DEV void put8(uint32_t a, const float (&r)[8], const float (&i)[8]) {
  sts4(a, pack2(r[0], r[1]), pack2(r[2], r[3]), pack2(r[4], r[5]), pack2(r[6], r[7]));
  sts4(a + 1024, pack2(i[0], i[1]), pack2(i[2], i[3]), pack2(i[4], i[5]), pack2(i[6], i[7]));
}
DEV void tables(const uint32_t (&pv)[8], int k4, int w, int lane) {
  PW(4 * k4 + w)
  [[maybe_unused]] const int layer = 0;
  const float dt = bfr(__expf(bflo(pv[6])));
  const float al = dt * bflo(pv[0]) * 1.4426950408889634f, bt = dt * bflo(pv[1]) * 0.15915494309189535f;
  float qr[8], qi[8], yr[8], yi[8];
  cmul(qr[0], qi[0], bflo(pv[4]), bflo(pv[5]), dt * bflo(pv[2]), dt * bflo(pv[3]));
  PROFD(2, a_par, __float_as_uint(qr[0] + al + bt));
  float e1r, e1i, eMr, eMi, eLr, eLi;
  cexp_(al, bt, 1.f, e1r, e1i); cexp_(al, -bt, 8.f, yr[1], yi[1]); cexp_(al, -bt, 64.f, eMr, eMi); cexp_(al, bt, 256.f, eLr, eLi);
  const uint32_t ad = SB + k4 * 32768 + (w & 1) * 512 + lane * 16, am = ad + (w >> 1) * KS, an = ad + (8 + 3 * (w >> 1)) * KS;
  yr[0] = 1.f; yi[0] = 0.f;
#pragma unroll
  for (int k = 1; k < 8; ++k) {
    cmul(qr[k], qi[k], qr[k - 1], qi[k - 1], e1r, e1i);
    if (k > 1) cmul(yr[k], yi[k], yr[k - 1], yi[k - 1], yr[1], yi[1]);
  }
  put8(an, qr, qi);
#pragma unroll
  for (int j = 0; j < 4; ++j) {
    put8(am + j * 2 * KS, yr, yi);
#pragma unroll
    for (int k = 0; k < 8; ++k) {
      if (j == 0 && k == 0) { yr[0] = eMr; yi[0] = eMi; } else if (j < 3) cmul(yr[k], yi[k], yr[k], yi[k], eMr, eMi);
    }
    if (j == 0) {
#pragma unroll
      for (int k = 0; k < 8; ++k) { const int o = k < 4 ? 2 * k : k < 6 ? 2 * k - 8 : k - 2; cmul(qr[k], qi[k], qr[o], qi[o], eLr, eLi); }
      put8(an + KS, qr, qi);
    } else if (j == 1) {
#pragma unroll
      for (int k = 0; k < 5; ++k) cmul(qr[k], qi[k], qr[k ? k - 1 : 6], qi[k ? k - 1 : 6], eLr, eLi);
      put8(an + 2 * KS, qr, qi);
    }
  }
  PROF(3, a_tab);
}

DEV void sts16_if(uint32_t a, uint32_t v, bool c) { asm volatile("{.reg .pred q; .reg .b16 h; setp.ne.u32 q,%2,0; cvt.u16.u32 h,%1; @q st.shared.u16 [%0],h;}" :: "r"(a), "r"(v), "r"((uint32_t)c) : "memory"); }
DEV void sts1_if(uint32_t a, uint32_t v, bool c) { asm volatile("{.reg .pred q; setp.ne.u32 q,%2,0; @q st.shared.u32 [%0],%1;}" :: "r"(a), "r"(v), "r"((uint32_t)c) : "memory"); }
DEV void taps(uint32_t dskip, int k4, int w, int lane) {
  PW(4 * k4 + w)
  [[maybe_unused]] const int layer = 0;
  fence_async_smem();
  bar_sync((k4 & 1) ? NB_WG + k4 : NB_Q, (k4 & 1) ? 128 : 448);
  float d[24];
  undef(d);
  const uint64_t da = mkdesc(SB + k4 * 32768, 1024, KS, 0);
  wg_fence();
#pragma unroll
  for (int j = 0; j < 8; ++j) wg_ss48(d, da + j * 8, da + KS / 2 + j * 8, j);
  wg_commit();
  const int b = 8 * w + (lane >> 2), t = lane & 3, id = 32 * w + lane;
  constexpr int DO = T_O - T_E;
  const uint32_t te = SM_TAP + k4 * TAP_SZ + T_E, a0 = te - 16 * b - 4 * t;
  const uint32_t a1 = a0 - 512 - 4 * t, a2 = te - 2 * (511 + b) - 64 * t, a3 = te + (T_C - T_E) - 2 * (127 + b) - 128 * t;
  wg_wait<0>();
  PROF(4, a_mma);
  {
    const uint32_t v = pack2(d[1] + d[15], d[0] + d[14] + (id ? 0.f : bflo(dskip)));
    sts1(a0 + DO - 2, v); sts16(a0 - 2, v); sts16(a0, v >> 16);
  }
  {
    const uint32_t v = pack2(d[5] + d[19], d[4] + d[18]), u = prmt(v, v, 0x3232);
    const bool lo = t < 2, k512 = id == 2;
    sts1_if(k512 ? te - 2 * 512 : a1, u, (lo && id) || k512);
    sts1_if(k512 ? te - 2 * 514 : a1 - 4, k512 ? u : v, lo || k512);
    sts1_if(k512 ? te + DO - 2 * 513 : a1 + DO - 2, u, lo || k512);
    sts16(lo ? a1 + DO - 4 : a2 + DO - 194, v);
    sts16(lo ? (id ? a1 + DO + 2 : a1) : k512 ? te + DO - 2 * 511 : a2 + DO, u);
    sts16_if(a2 - 194, v, !lo);
    sts16_if(k512 ? te + DO - 2 * 514 : a2, u, !lo);
  }
  {
    const uint32_t v = pack2(d[8] + d[22], d[9] + d[23]);
    sts16_if(id ? a3 : te - 2 * 639, v, t < 2 || id == 2);
    sts16_if(a3 - 64, v >> 16, t < 2);
    sts16_if(te + DO - 2 * 639, v, id == 0);
  }
  bar_sync(NB_WG + k4, 128);
  mbar_arrive1_if(B_K, w == 0);
}

DEV uint32_t cpy(uint32_t v, uint32_t id) {
  uint32_t d; asm volatile("prmt.b32 %0,%1,%1,%2;" : "=r"(d) : "r"(v), "r"(id)); return d;
}
DEV uint32_t uoff(int s) { return (s ^ ((s >> 3) & 3)) * 16; }
template <bool FULL> DEV void boxes(const uint32_t (&u)[10], uint32_t a, uint32_t a9, uint32_t a7, uint32_t (&pv)[4]) {
  uint32_t v[8], p[8], x[4], y[4];
#pragma unroll
  for (int j = 0; j < 8; ++j) { v[j] = prmt(u[j], u[j + 1], 0x5432); p[j] = hadd2(u[j], v[j]); }
#pragma unroll
  for (int j = 0; j < 4; ++j) { x[j] = hadd2(hadd2(p[j + 1], p[j + 2]), u[j + 3]); y[j] = hadd2(v[j + 3], p[j + 4]); }
  sts4(a + R_A5, x[0], x[1], x[2], x[3]);
  sts4(a + R_A3, y[0], y[1], y[2], y[3]);
  if (FULL) {
#pragma unroll
    for (int j = 0; j < 4; ++j) { x[j] = hadd2(x[j], hadd2(v[j], v[j + 3])); y[j] = hadd2(x[j], hadd2(u[j], u[j + 4])); pv[j] = p[j + 4]; }
    sts4(a7, x[0], x[1], x[2], x[3]);
    sts4(a9, y[0], y[1], y[2], y[3]);
  }
}
DEV void halo(uint32_t (&u)[10], uint32_t a, int lane) {
  asm volatile("{.reg .pred p,q; setp.eq.s32 p,%8,0; setp.lt.s32 q,%8,2;\n@p ld.shared.v4.u32 {%2,%3,%4,%5},[%6];\n@q ld.shared.v2.u32 {%0,%1},[%7];}"
    : "+r"(u[0]), "+r"(u[1]), "+r"(u[2]), "+r"(u[3]), "+r"(u[4]), "+r"(u[5]) : "r"(a), "r"(a + 24 - 16 * lane), "r"(lane));
}
#define ROT 2
#define G1 -1
#define G2 0
#define G3 1
#define TPS 0x6135
#define GMASK ((G1 >= 0 ? 2 : 0) | (G2 >= 0 ? 4 : 0) | (G3 >= 0 ? 8 : 0))
#define GATE1(g, n, p) if (g >= 0 && (g & 3) == p) mbar_arrive1_if(B_G + 8 * n, k4 == (g >> 2));
#define GATE(p) GATE1(G1, 0, p) GATE1(G2, 1, p) GATE1(G3, 2, p)
#define TMASK(p) (((TPS & 15) == p) | ((((TPS >> 4) & 15) == p) << 1) | ((((TPS >> 8) & 15) == p) << 2) | ((((TPS >> 12) & 15) == p) << 3))
#define TURN(p) if (TMASK(p) == 15) bar_arrive(NB_T + 1 + k4, 256); else if (TMASK(p)) { if ((TMASK(p) >> k4) & 1) bar_arrive(NB_T + 1 + k4, 256); }
#define ANN(p, dep) if (EA & (0x1111 * p)) cnt_add(P, 1 + 5 * layer + k4, c, (32 * (v ^ 3) + lane) | (dep) | ((~(EA >> (4 * k4)) & p) << 8));
DEV void w_load(const CUtensorMap* mW, int cg, int h) {
  mbar_expect1(B_W + 8 * h, 24576);
  tma3(SM_S0 + (h & 3) * 24576, mW, 64 * cg, 64 * h, B_W + 8 * h);
}

DEV void conv(const Params& P, const CUtensorMap* mW, int c, int k4, int w, int layer) {
  const uint32_t zero = P.zero;
  PW(4 * k4 + w)
  int lane = lane_here(zero);
  const int g = lane >> 2, t = lane & 3, v = w ^ (ROT * (k4 & 1)), tid = 32 * v + lane;
  const uint32_t reg = SM_R + k4 * 16384, tp = SM_TAP + k4 * TAP_SZ;
  const uint32_t g0 = tp + ((g & 1) ? T_O : T_E) + 2 * (2 * t - g);
  uint32_t F[18][4], U[20], qc[4][4];
#define LO(q, a) q[0] = lds1(a); q[2] = lds1(a + 16);
#define HI(q, a) q[1] = lds1(a - 128); q[3] = lds1(a - 112);
  {
    const uint32_t ga = g0 - 32 * (w & 1) - 576 * (w >> 1), g2 = tp + T_C - 258 - 32 * w + 4 * (t - g);
    F[0][2] = lds1(ga + 48);
#pragma unroll
    for (int j = 0; j < 8; ++j) { F[j][0] = lds1(ga + 32 - 32 * j); F[j][1] = lds1(ga + 16 - 32 * j); }
#pragma unroll
    for (int j = 0; j < 20; ++j) U[j] = lds1(ga - 224 - 16 * j);
#pragma unroll
    for (int j = 0; j < 4; ++j) { LO(qc[j], g2 + 32 * j) HI(qc[j], g2 + 32 * j) }
  }
  if (layer) { mbar_wait(B_ED, 0); mbar_wait(B_ED + 8, 0); }
  sts4z_if(reg + lane * 16 + (w ? w * 3584 + 1024 : 0), w < 3);
  PROF(5, a_pre);
  if (k4 == 3 && w == 3) {
    mbar_wait(B_E, layer);
    mbar_wait(B_K, 0);
#pragma unroll
    for (int h = 0; h < 4; ++h) w_load(mW, c & 7, h);
  }
  mbar_wait(k4 && ((GMASK >> k4) & 1) ? B_G - 8 + 8 * k4 : B_E, layer);
  PROF(6, a_x);
  const uint32_t ua = reg + R_U + uoff(tid);
  uint4 x[2];
  uint32_t pv[4];
  {
    uint4 s[4];
#pragma unroll
    for (int z = 0; z < 2; ++z) x[z] = lds4(reg + R_B + tid * 16 + z * 2048);
#pragma unroll
    for (int z = 0; z < 4; ++z) s[z] = lds4(SM_RES + tid * 16 + (z >> 1) * 2048 + (z & 1) * 4096);
    for (int it = 0;; ++it) {
      uint32_t m = min(x[0].x, x[1].x);
#pragma unroll
      for (int z = 0; z < 4; ++z) m = min(m, min(s[z].x, s[z].z));
      if (m) break;
#pragma unroll
      for (int z = 0; z < 2; ++z) x[z] = ldr4(&P.S->XG[layer][(128 * k4 + c) * 256 + opq(tid) + z * 128]);
#pragma unroll
      for (int z = 0; z < 4; ++z) s[z] = ldr4(&P.S->SR[layer][c >> 4][opq(tid) + (z >> 1) * 128 + (z & 1) * 256]);
#pragma unroll
      for (int z = 0; z < 4; ++z) sts4(SM_RES + tid * 16 + (z >> 1) * 2048 + (z & 1) * 4096, s[z].x, s[z].y, s[z].z, s[z].w);
      spin_guard(it);
    }
    __syncwarp();
    uint32_t u[2][10];
#pragma unroll
    for (int z = 0; z < 2; ++z) {
      u[z][6] = hmul2(hsub2(x[z].x, s[2 * z].y), s[2 * z].x); u[z][7] = hmul2(hsub2(x[z].y, s[2 * z].w), s[2 * z].z);
      u[z][8] = hmul2(hsub2(x[z].z, s[2 * z + 1].y), s[2 * z + 1].x); u[z][9] = hmul2(hsub2(x[z].w, s[2 * z + 1].w), s[2 * z + 1].z);
      sts4(ua + z * 2048, u[z][6], u[z][7], u[z][8], u[z][9]);
    }
#pragma unroll
    for (int j = 0; j < 6; ++j) u[0][j] = __shfl_up_sync(0xffffffffu, u[0][j < 2 ? 8 + j : 4 + j], j < 2 ? 2 : 1);
    bar_sync(NB_WG + k4, 128);
    GATE(0)
    PROF(7, a_u);
    const uint32_t h1 = reg + R_U + v * 512 - 64;
    halo(u[0], h1, lane);
    if (v < 2) {
      u[1][0] = 0;
#pragma unroll
      for (int j = 1; j < 6; ++j) u[1][j] = __shfl_up_sync(0xffffffffu, u[1][j < 2 ? 8 + j : 4 + j], j < 2 ? 2 : 1);
      halo(u[1], h1 + 2048, lane);
      boxes<false>(u[1], reg + tid * 16 + 2048, 0, 0, pv);
    }
    const uint32_t bo = reg + R_B + tid * 16 + (v >> 1) * 1056;
    const uint32_t be = tid == 127 ? reg + R_B + 1024 : bo + (tid == 63 ? 2112 : 1056);
    boxes<true>(u[0], reg + tid * 16, (lane & 1) ? be : bo, (lane & 1) ? bo : be, pv);
    sts4z_if(reg + R_B + 1040, tid == 0);
  }
  GATE(1)
  fence_async_smem();
  if (k4 == 3 && w < 3) {
    const uint32_t src = SM_RES + 8192 + w * 2048, f = (w >> 1) - 1;
#pragma unroll
    for (int z = 0; z < 4; ++z) sts4(src + lane * 16 + z * 512, f, f, f, f);
    fence_async_smem();
    __syncwarp();
    if (w < 2) {
#pragma unroll
      for (int z = 0; z < 4; ++z) bulk_store(&P.S->O[((c >> 3) * 16 + w * 8 + (c & 7)) * 512] + z * 128, src, 2048);
    } else {
#pragma unroll
      for (int z = 0; z < 2; ++z) {
        bulk_store(&P.S->H[(c + 8) * 256] + z * 128, src, 2048);
        bulk_store(P.S->F + ((c >> 3) * 64 + 4 * (c & 7)) + z * 32, src, 16);
      }
      bulk_store(&P.S->PS[c * 64], src, 1024);
      bulk_store(&P.S->ST[c * 4], src, 64);
      if (c < 5) bulk_store(P.S->C + (c + 5 - 5 * layer) * 1024, src, 128 * NCOPY * NSUB);
    }
    asm volatile("cp.async.bulk.commit_group;" ::: "memory");
  }
  const uint32_t id = opq(0x3210u);
#pragma unroll
  for (int j = 0; j < 8; ++j) { F[j][3] = cpy(F[j][0], id); if (j) F[j][2] = cpy(F[j - 1][1], id); }
  PROF(8, a_box);
  bar_sync(NB_T + k4, k4 ? 256 : 128);
  PROF(9, a_turn);
  float acc[32], f1[24], f3[16];
  uint32_t qa[4][4], qb[4][4], fp[4];
  const uint64_t db = mkdesc(reg + R_U, 16, 512, 2) + 2;
#define STEP(mm) wg_fence(); mm; wg_commit(); wg_wait<2>();
#define D(j) STEP(wg_rs64k(acc, F[j], db - 2 * j, j))
#define C(j) STEP(wg_rs32t(f3, qc[j], mkdesc(reg + R_B, 128, 1040, 0) + 16 * j, j))
#define NIL(q) { const uint32_t z = here(zero); q[2][1] = cpy(z, 0); q[2][3] = cpy(z, 1); q[3][1] = cpy(z, 2); q[3][3] = cpy(z, 3); }
#define X(j) F[j][0] = cpy(U[2 * j - 16], ix); F[j][1] = cpy(U[2 * j - 15], ix); F[j][3] = cpy(F[j][0], ix); F[j][2] = cpy(F[j - 1][1], ix);
#define PIN ix = 0x3210u | here(zero);
  const uint32_t g1 = g0 - 2 * 576 - 16 * w;
  const uint64_t d1 = mkdesc(reg + R_A5, 128, 512, 0);
  constexpr int O3 = (R_A3 - R_A5) / 16;
  uint32_t ix;
  undef(acc);
  D(0) TURN(0) D(1) D(2) D(3) D(4) D(5)
  undef(f3);
  C(0) C(1) TURN(1) PIN X(8) X(9) C(2) C(3) LO(qa[0], g1)
  D(6) HI(qa[0], g1) PIN X(10) D(7) LO(qa[1], g1 + 32) X(11)
  fp[0] = pack2(f3[0], f3[1]); fp[1] = pack2(f3[4], f3[5]); fp[2] = pack2(f3[8] + f3[2], f3[9] + f3[3]); fp[3] = pack2(f3[12] + f3[6], f3[13] + f3[7]);
  D(8) HI(qa[1], g1 + 32) PIN ix |= fp[0] & fp[1] & fp[2] & fp[3] & zero; X(12) D(9) LO(qa[2], g1 - 64) X(13)
  D(10) TURN(2) LO(qa[3], g1 - 32) X(14) D(11) LO(qb[0], g1 - 192) PIN X(15) D(12) HI(qb[0], g1 - 192) X(16)
  D(13) LO(qb[1], g1 - 160) X(17) D(14) TURN(3) HI(qb[1], g1 - 160) NIL(qa)
  D(15) LO(qb[2], g1 - 256) D(16) LO(qb[3], g1 - 224) NIL(qb) D(17) TURN(4)
  PROF(10, a_den);
  undef(f1);
  wg_fence();
#pragma unroll
  for (int j = 0; j < 4; ++j) wg_rs48t(f1, qa[j], d1 + 16 * (j & 1) - 32 * (j >> 1), j);
  wg_commit();
  wg_wait<1>();
  TURN(5)
  wg_fence();
#pragma unroll
  for (int j = 0; j < 4; ++j) wg_rs48t(f1, qb[j], d1 + O3 + 16 * (j & 1) - 32 * (j >> 1), 1);
  wg_commit();
  TURN(6)
  asm volatile("cp.async.bulk.wait_group 0;" ::: "memory");
  uint32_t k1024 = lds16(tp + T_E - 2 * 639);
  lane = lane_here(zero);
  uint32_t yp[16];
#pragma unroll
  for (int z = 0; z < 16; ++z) yp[z] = pack2(acc[2 * z], acc[2 * z + 1]);
  const int p = (lane + 9 * (w >> 1)) & 31;
  const uint32_t ya = reg + ((w >> 1) ? R_B : R_U) + p * 64 + (((2 * (w & 1)) ^ ((p >> 1) & 3)) * 16);
  const uint32_t up = p < lane ? 2048 : 0;
  const uint32_t fa = reg + R_A5 + (lane >> 3) * 512 + w * 128 + (lane & 7) * 16;
  const uint32_t fc = reg + R_A3 + uoff(64 * (lane >> 4) + 16 * w + 2 * (lane & 7) + 1 - ((lane >> 3) & 1));
  wg_wait<0>();
  GATE(2)
  PROF(11, a_far);
  bar_sync(NB_WG + k4, 128);
#pragma unroll
  for (int z = 0; z < 4; ++z) {
    const uint32_t* a = yp + 8 * (z >> 1) + (z & 1);
    stsm4t((ya + (up ^ ((z >> 1) * 2048))) ^ ((z & 1) * 16), a[0], a[2], a[4], a[6]);
  }
  stsm4(fa, pack2(f1[0], f1[1]), pack2(f1[4], f1[5]), pack2(f1[8] + f1[2], f1[9] + f1[3]), pack2(f1[12] + f1[6], f1[13] + f1[7]));
  stsm2(fa + 2048, pack2(f1[16] + f1[10], f1[17] + f1[11]), pack2(f1[20] + f1[14], f1[21] + f1[15]));
  stsm4(fc, fp[0], fp[1], fp[2], fp[3]);
  bar_sync(NB_WG + k4, 128);
  PROF(12, a_sts);
  {
    const int o = 32 * v + lane;
    const uint32_t a = reg + uoff(o), b = reg + R_A5 + o * 16;
    uint4 y[2];
    y[0] = hadd8(lds4(a + R_U), hadd8(lds4(o >= 36 ? a + R_B : reg), lds4(v >= 2 ? b - 1024 : reg)));
    uint4 h = lds4(a + R_A3);
    k1024 = prmt(k1024, k1024, 0x1010);
    h = make_uint4(hfma2(pv[0], k1024, h.x), hfma2(pv[1], k1024, h.y), hfma2(pv[2], k1024, h.z), hfma2(pv[3], k1024, h.w));
    y[1] = hadd8(lds4(a + R_U + 2048), hadd8(lds4(a + R_B + 2048), hadd8(lds4(b + 1024), h)));
    const int e0 = (o >> 3) * 8192 + (128 * k4 + c) * 16 + (((o & 4) + ((o >> 1) & 1)) ^ (c & 7)) * 2 + (o & 1);
    ANN(2, y[0].x & y[1].x & zero)
    const uint32_t me = (e0 & 3) == ((c >> 1) & 3), m0 = me & ~c, m1 = me & c, tag = 1 - layer;
#pragma unroll
    for (int z = 0; z < 2; ++z) {
      const uint4 r = hadd8(x[z], y[z]);
      str2((uint2*)P.S->XF + e0 + z * 131072, tagged(prmt(r.x, r.y, 0x5410), m0, tag), tagged(prmt(r.z, r.w, 0x5410), m1, tag));
      str2((uint2*)P.S->XF + (e0 ^ 4) + z * 131072, tagged(prmt(r.x, r.y, 0x7632), m0, tag), tagged(prmt(r.z, r.w, 0x7632), m1, tag));
    }
  }
  ANN(1, 0)
  GATE(3)
  PROF(13, a_out);
}

#define WGATE 1
#define FH 1
#define QPIN 1
#define XORD 1
DEV void x_load(const Params& P, int c, int q, int layer) {
#pragma unroll
  for (int z = 0; z < 2; ++z) {
    const int e = z ^ (XORD && q == 3 && !(c & 4));
    mbar_expect1(B_X + 16 * q + 8 * e, 16384);
    bulk(xstage(q, e), P.S->XF + ((2 * (c >> 3) + 1 - e) * 4096 + q * 1024), 16384, B_X + 16 * q + 8 * e);
  }
}

DEV void means(uint32_t (&m)[4], int row, int lane, int layer, uint32_t zero) {
  mbar_wait(B_CS, 0);
  mbar_wait(B_ST, layer);
  const uint32_t a = SM_MISC + row * 4 + (lane & 28), k = (lane & 3) ? 0u : ~0u;
  m[0] = lds1(a) & k; m[1] = lds1(a + 32) & k; m[2] = m[0] & zero; m[3] = m[1] & zero;
}

DEV void attn_phase(const Params& P, int c, int e, int w, int lane, int layer) {
  PW(4 * e + w)
  const int cg = c & 7, J = 2 * (c >> 3) + 1 - e;
  float acc[96];
  zerov(acc);
  uint32_t m[4] = {0, 0, 0, 0};
#pragma unroll 1
  for (int q = 0;; ++q) {
    const uint64_t da = mkdesc(xstage(q, e), 16, 1024, 1), db = mkdesc(SM_S0 + (q & 1) * 49152, 8192, 1024, 1);
    const uint32_t wr = mbar_test2(B_W + 16 * q, layer), xa = xstage(q, e) + w * 4096 + lane * 132;
    mbar_wait(B_X + 16 * q + 8 * e, layer);
    for (int it = 0;; ++it) {
      const uint32_t ok = both(lds1(xa), lds1(xa ^ 32), layer) & both(lds1(xa ^ 64), lds1(xa ^ 96), layer);
      if (__all_sync(0xffffffffu, ok & 1)) break;
      EVENT(8 * layer + 2 * q + e);
#pragma unroll 1
      for (int j = 0; j < 8; ++j) cp16(xstage(q, e) + w * 4096 + j * 512 + lane * 16, P.S->XF + (J * 4096 + q * 1024 + w * 256 + j * 32 + lane));
      asm volatile("cp.async.wait_all;" ::: "memory");
      fence_async_smem();
      __syncwarp();
      spin_guard(it);
    }
    bool all = __all_sync(0xffffffffu, wr);
    if (q == 0 && e && w == 0) {
      bar_sync(NB_H, 256);
      cnt_wait(P, 2 + 5 * layer, c, lane);
      x_load(P, c, 1, layer);
      PROF(27, m_xi);
    }
    if (q == 3 && e) means(m, 16 * w, lane, layer, P.zero);
    if (!all) { mbar_wait(B_W + 16 * q, layer); all = mbar_test(B_W + 16 * q + 8, layer); }
    bar_sync(e ? NB_Q : q ? NB_T : NB_T + 4, 256);
    PROF(14 + q, m_q);
    wg_fence();
#pragma unroll
    for (int k = 0; k < 8; ++k) {
      if (k == 4) { wg_commit(); if (!all) mbar_wait(B_W + 16 * q + 8, layer); wg_fence(); }
      wg_ss192(acc, da + k * 128, db + (k >> 2) * 1536 + (k & 3) * 128, 1);
    }
    wg_commit();
    if (q == 3) break;
    bar_arrive(e ? NB_T : NB_Q, 256);
    if (FH) { wg_wait<1>(); mbar_arrive1_if(B_FH + 8 * q, e && q < 2); }
    wg_wait<0>();
    mbar_arrive1(B_F + 8 * q);
  }
  const int pos = 2 - 2 * e + (w >> 1);
  uint4* h = P.S->H + ((c + 8) * 256 + (w & 1) * 128 + lane);
  {
    if (!e) means(m, 64 + 16 * w, lane, layer, P.zero);
    PROF(28, m_sub);
    wg_fence();
    wg_rs192t(acc, m, mkdesc(SM_CS, 0, 32, 0));
    wg_commit();
    bar_arrive_if(NB_Q, 256, !e);
    keep(h, P.zero);
    wg_wait<0>();
    mbar_arrive1(B_F + 24);
  }
  PROF(18, m_qkv);
  lane = opq(lane);
  const int g = lane >> 2, t = lane & 3;
  uint32_t Q[4][4], K[4][3][2], V[4][3][2];
  const uint32_t ra = SM_STAT + 256 + (32 - 32 * e + 8 * w) * 16;
  float r0, r1;
  uint4 k0, k1, k2;
  {
#pragma unroll
    for (int z = 0; z < 4; ++z) {
      K[z][2][0] = nz(pack2(acc[34 + 8 * z], acc[35 + 8 * z])); K[z][2][1] = pack2(acc[38 + 8 * z], acc[39 + 8 * z]);
      V[z][2][0] = pack2(acc[66 + 8 * z], acc[67 + 8 * z]); V[z][2][1] = pack2(acc[70 + 8 * z], acc[71 + 8 * z]);
      str4_if(h + z * 32, K[z][2][0], K[z][2][1], V[z][2][0], V[z][2][1], pos == 3);
    }
    bar_arrive_if(NB_RL, 128, pos == 3);
#pragma unroll
    for (int z = 0; z < 8; ++z) {
      V[z >> 1][2][z & 1] = movm(V[z >> 1][2][z & 1]);
      K[z >> 1][1][z & 1] = pack2(acc[32 + 4 * z], acc[33 + 4 * z]);
      V[z >> 1][1][z & 1] = pack2(acc[64 + 4 * z], acc[65 + 4 * z]);
    }
    const uint32_t kv = (w & 1) * 2048 + lane * 16;
    if (pos < 3) {
      mbar_wait(B_F + 16 + 8 * e, layer);
#pragma unroll
      for (int z = 0; z < 4; ++z) sts4(kvslot(cg, pos + 1) + kv + z * 512, K[z][2][0], K[z][2][1], V[z][2][0], V[z][2][1]);
      bar_arrive(NB_H + pos + 1, 128);
    }
    r0 = lds1f(ra + (g >> 1) * 16 + (g & 1) * 4); r1 = lds1f(ra + 64 + (g >> 1) * 16 + (g & 1) * 4);
    k1 = lds4(ra + 16 * t); k2 = lds4(ra + 64 + 16 * t);
    PROF(19, m_kv);
    uint32_t pin = QPIN ? P.zero : 0;
#pragma unroll
    for (int z = 0; z < 8; ++z) {
      V[z >> 1][1][z & 1] = movm(V[z >> 1][1][z & 1]);
      Q[z >> 1][2 * (z & 1)] = pack2(acc[4 * z], acc[4 * z + 1]);
      Q[z >> 1][2 * (z & 1) + 1] = pack2(acc[4 * z + 2], acc[4 * z + 3]);
      if (QPIN) pin &= Q[z >> 1][2 * (z & 1)] & Q[z >> 1][2 * (z & 1) + 1];
    }
    mbar_wait(B_F + 24, layer);
    bar_sync(NB_H + pos + pin, pos ? 128 : 160);
    k0 = lds4(ra - 192 + 16 * t);
#pragma unroll
    for (int z = 0; z < 4; ++z) {
      const uint4 hv = lds4(kvslot(cg, pos) + kv + z * 512);
      K[z][0][0] = hv.x; K[z][0][1] = hv.y; V[z][0][0] = hv.z; V[z][0][1] = hv.w;
    }
  }
  PROF(20, m_halo);
  const uint32_t ob = e ? SM_S1 : SM_XA;
  {
    const bool p0 = 2 * t > g, p1 = 2 * t + 1 > g, first = c < 8 && pos == 0;
    const uint32_t M = (p0 ? 0xFFFFu : 0u) | (p1 ? 0xFFFF0000u : 0u);
    const float sc0 = r0 * (0.25f * 1.4426950408889634f), sc1 = r1 * (0.25f * 1.4426950408889634f);
    const float sk[4] = {__uint_as_float(p0 ? k0.x : k1.x) * sc0, __uint_as_float(p1 ? k0.y : k1.y) * sc0,
                         __uint_as_float(p0 ? k1.x : k2.x) * sc1, __uint_as_float(p1 ? k1.y : k2.y) * sc1};
    const uint32_t rm[4] = {k0.z & M, k1.z & ~M, k1.z & M, k2.z & ~M}, s0 = k0.w | P.zero, s1 = k1.w | P.zero;
    const int oo = cg * 512 + (2 * (w & 2) + (w & 1)) * 64 + (lane ^ (g >> 1));
    uint4* O = P.S->O + (J * 4096 + oo);
#pragma unroll
    for (int h2 = 0; h2 < 2; ++h2) {
      uint32_t A[2], B[2], mx[2];
#pragma unroll
      for (int z = 0; z < 2; ++z) {
        const int h = 2 * h2 + z;
        float S[3][4];
#pragma unroll
        for (int n = 0; n < 3; ++n) mma16z(S[n], Q[h][0], Q[h][1], Q[h][2], Q[h][3], K[h][n][0], K[h][n][1]);
        if (first) { S[0][0] = __uint_as_float(0xFF800000u); S[0][1] = S[0][0]; }
        A[z] = pack2((p0 ? S[0][0] : S[1][0]) * sk[0], (p0 ? S[1][2] : S[2][2]) * sk[2]);
        B[z] = pack2((p1 ? S[0][1] : S[1][1]) * sk[1], (p1 ? S[1][3] : S[2][3]) * sk[3]);
      }
#pragma unroll
      for (int z = 0; z < 2; ++z) mx[z] = hmax2(A[z], B[z]);
#pragma unroll
      for (int z = 0; z < 2; ++z) mx[z] = hmax2(mx[z], __shfl_xor_sync(0xffffffffu, mx[z], 1));
#pragma unroll
      for (int z = 0; z < 2; ++z) mx[z] = hmax2(mx[z], __shfl_xor_sync(0xffffffffu, mx[z], 2));
      float Oa[2][3][4];
#pragma unroll
      for (int z = 0; z < 2; ++z) {
        const int h = 2 * h2 + z;
        const uint32_t a = hsub2(A[z], mx[z]), b = hsub2(B[z], mx[z]);
        const uint32_t w0 = pack2(ex2(bflo(a)), ex2(bflo(b))), w1 = pack2(ex2(bfhi(a)), ex2(bfhi(b)));
        const uint32_t u0 = hmul2(w0, rm[0]), u1 = hmul2(w0, rm[1]), u2 = hmul2(w1, rm[2]), u3 = hmul2(w1, rm[3]);
        const uint32_t z0 = w0 & P.zero, z1 = w1 & P.zero;
        mma16z(Oa[z][2], u0, z0, u1, u2, s0, s1);
#pragma unroll
        for (int d = 0; d < 2; ++d) mma16z(Oa[z][d], u0, z0, u1, u2, V[h][0][d], V[h][1][d]);
        mma8(Oa[z][2], z1, u3, k2.w);
#pragma unroll
        for (int d = 0; d < 2; ++d) mma8(Oa[z][d], z1, u3, V[h][2][d]);
      }
#pragma unroll
      for (int r = 0; r < 4; r += 2) {
        const float i0 = rcp(Oa[0][2][r]), i1 = rcp(Oa[1][2][r]);
        const uint32_t o0 = pack2(Oa[0][0][r] * i0, Oa[0][0][r + 1] * i0), o1 = pack2(Oa[0][1][r] * i0, Oa[0][1][r + 1] * i0);
        const uint32_t o2 = pack2(Oa[1][0][r] * i1, Oa[1][0][r + 1] * i1), o3 = pack2(Oa[1][1][r] * i1, Oa[1][1][r + 1] * i1);
        str4(O + h2 * 32 + r * 64, o0, o1, o2, o3);
        sts4(ob + oo * 16 + h2 * 512 + r * 1024, o0, o1, o2, o3);
      }
    }
  }
  bar_arrive(NB_T + 1 + e, 160);
  fence_async_smem();
  PROF(21, m_att);
  uint32_t res[8][2];
  mbar_wait(B_RES, layer);
  {
    const uint32_t a = SM_RES + e * 8192 + (lane >> 4) * 1024 + (lane & 7) * 128 + (((2 * (w & 2) + ((lane >> 2) & 2) + (w & 1)) ^ (lane & 7)) * 16);
#pragma unroll
    for (int j = 0; j < 8; j += 2) ldsm4t(res[j][0], res[j][1], res[j + 1][0], res[j + 1][1], a + j * 1024);
  }
  PROF(26, m_res);
  if (WGATE) bar_sync(NB_T, 256); else bar_sync(NB_WG + e, 128);
  XgAddr xa = xg_addr<true>(P.S->XG[1] + (64 * cg * 256 + 8 * J), ob, w, lane, P.zero);
  uint4* ps = &P.S->PS[((4 * J + w) * 8 + cg) * 8 + g];
  keep(ps, P.zero);
  if (layer) {
    xa.a = ob + w * 2048 + (lane & 15) * 128 + (((lane >> 4) ^ (lane & 7)) * 16);
    xa.b = ob + w * 2048 + (lane >> 3) * 128 + (((lane & 7) ^ (lane >> 3)) * 16);
    xa.dst = (uint4*)P.out + ((64 * J + 16 * w + 2 * (lane >> 3)) * 64 + 8 * cg + (lane & 7));
  }
  uint32_t y[8][2];
#pragma unroll 1
  for (int it = 0;; ++it) {
    float ac[32];
    zerov(ac);
#pragma unroll 1
    for (int n = 0; n < 8; ++n) {
      const int s = n == 0 ? cg : n - (n <= cg);
      mbar_wait(n ? B_O + 64 * e + 8 * s : B_WO, layer);
      if (n == 1) PROF(22, m_o1);
      if (n == 7) PROF(23, m_o7);
      const uint64_t da = mkdesc(ob + s * 8192, 16, 1024, 2), db = mkdesc(SM_R + s * 8192, 16, 1024, 1);
      wg_fence();
#pragma unroll
      for (int k = 0; k < 4; ++k) wg_ss64(ac, da + (k >> 1) * 32 + (k & 1) * 2, db + k * 128, 1);
      wg_commit();
    }
    wg_wait<0>();
    const bool bad = ac[0] != ac[0] || ac[2] != ac[2];
#pragma unroll
    for (int j = 0; j < 8; ++j) {
      y[j][0] = hadd2(res[j][0], pack2(ac[4 * j], ac[4 * j + 1]));
      y[j][1] = hadd2(res[j][1], pack2(ac[4 * j + 2], ac[4 * j + 3]));
    }
    if (!bar_any(NB_WG + e, 128, bad) || it == 16) break;
    EVENT(24 + 2 * layer + e);
    refetch(ob, P.S->O + J * 4096, 32768, e, w);
  }
  PROF(24, m_wo);
  if (layer == 0) {
    const float4 s = gram(y, g, P.zero);
    xg_put<true>(xa, y);
    str4_if(ps, nz(__float_as_uint(s.x)), __float_as_uint(s.y), __float_as_uint(s.z), __float_as_uint(s.w), t == (g >> 1));
    mbar_arrive1(B_ED + 8 * e);
    bar_sync(NB_WG + e, 128);
    xg_store(xa);
    bar_arrive(NB_T + 3, 288);
  } else {
#pragma unroll
    for (int j = 0; j < 8; j += 2) stsm4(xa.a ^ (j * 16), y[j][0], y[j][1], y[j + 1][0], y[j + 1][1]);
    __syncwarp();
#pragma unroll
    for (int k = 0; k < 4; ++k) {
      const uint4 v = lds4((xa.b ^ ((k & 1) * 64)) + k * 512);
      stw4(xa.dst + ((k & 1) * 8 + (k >> 1)) * 64, v.x, v.y, v.z, v.w);
    }
  }
  PROF(25, m_epi);
}

#define HDELAY 300
#define ODELAY 200
#define PDELAY 0
#define FDELAY 200
#define CSP 0
#define CSU 4
#define PHOLD 0
#define XDEL 300
#define WOQ 2
#define H5 1
#define SRDELAY 300
#define ZPACE 20

DEV void o_load(const Params& P, int c, int e, int lane, int layer) {
  PW(8 + e)
  const int J = 2 * (c >> 3) + 1 - e;
#pragma unroll 1
  for (int s = 0; s < 8; ++s) mbar_expect1(B_O + 64 * e + 8 * s, s == (c & 7) ? 0 : 8192);
  bar_sync(NB_T + 1 + e, 160);
  flag_set1(P.S->F + (J * 32 + 4 * (c & 7)));
  if (ODELAY) delay(ODELAY);
  PROF(26, a_go);
  poll(P.S->F + (J * 32 + (lane & 28)), 1);
  PROF(25, h_seen);
  bar_sync_if(NB_Q, 64, e);
#pragma unroll 1
  for (int s = 0; s < 8; ++s)
    if (s != (c & 7)) bulk((e ? SM_S1 : SM_XA) + s * 8192, P.S->O + (J * 4096 + s * 512), 8192, B_O + 64 * e + 8 * s);
  bar_arrive_if(NB_Q, 64, !e);
  PROF(28, a_o);
}

DEV void stats(const Params& P, int c, int w, int lane, int layer) {
  PW(12 + w)
  lane = opq(lane);
  const int r = (lane & 6) + ((lane >> 3) & 1), k = (2 * (c & 3) + (lane & 1)) ^ r, e = 1 - ((c >> 2) & 1);
  const uint32_t o = (32 * w + 8 * (lane >> 4) + r) * 128 + k * 16;
  const uint32_t mk = ((k & 1) == (r >> 2)) << (r & 3), tag = 1 - layer;
  float v[16];
#pragma unroll
  for (int z = 0; z < 16; ++z) v[z] = 0.f;
#pragma unroll 1
  for (int q = 0; q < 4; ++q) {
    mbar_wait(B_X + 16 * q + 8 * e, layer);
    PROF(19 + q, s_l);
    uint4 x, y;
    for (int it = 0;; ++it) {
      x = lds4v(xstage(q, e) + o); y = lds4v(xstage(q, e) + o + 2048);
      const uint32_t bad = (((x.x ^ tag) | (y.x ^ tag)) & mk) | (((x.y ^ tag) | (y.y ^ tag)) & (mk >> 1)) |
                           (((x.z ^ tag) | (y.z ^ tag)) & (mk >> 2)) | (((x.w ^ tag) | (y.w ^ tag)) & (mk >> 3));
      if (!__any_sync(0xffffffffu, bad & 1)) break;
      spin_guard(it);
    }
    mbar_arrive1(B_F + 8 * q);
    const uint32_t ws[8] = {x.x, x.y, x.z, x.w, y.x, y.y, y.z, y.w};
#pragma unroll
    for (int z = 0; z < 8; ++z) {
      const float lo = bflo(ws[z]), hi = bfhi(ws[z]);
      float* u = v + 4 * (z & 3);
      u[0] += lo; u[1] += lo * lo; u[2] += hi; u[3] += hi * hi;
    }
  }
  PROFD(14, s_part, __float_as_uint(v[0]));
  fold<8>(v, lane, 16); fold<4>(v, lane, 8); fold<2>(v, lane, 4); fold<1>(v, lane, 2);
  PROFD(16, s_fold, __float_as_uint(v[0]));
  if (w) {
    sts1(SM_MISC - 128 + w * 128 + lane * 4, __float_as_uint(v[0]));
    bar_arrive(NB_P, 128);
  } else {
    bar_sync(NB_P, 128);
    v[0] += lds1f(SM_MISC + lane * 4) + lds1f(SM_MISC + 128 + lane * 4) + lds1f(SM_MISC + 256 + lane * 4);
    float m;
    const float sd = ln_sd(v[0], __shfl_xor_sync(0xffffffffu, v[0], 2), m);
    if (!(lane & 2)) str1((uint32_t*)P.S->ST + (16 * c + 8 * (lane & 1) + (lane >> 2)), pack2(m, sd));
    sts4(SM_STAT - 32 + min(lane, 17) * 16, 0x3F800000u, 0x3F800000u, 0x3F803F80u, 0x3F803F80u);
    fence_async_smem();
    PROF(17, s_pub);
    uint4 s;
    for (int it = 0;; ++it) {
      s = ldr4(P.S->ST + ((c >> 3) * 32 + lane));
      if (__all_sync(0xffffffffu, min4(s) != 0u)) break;
      spin_guard(it);
    }
    PROF(18, s_seen);
    const float r0 = rcp(bfhi(s.x)), r1 = rcp(bfhi(s.y)), r2 = rcp(bfhi(s.z)), r3 = rcp(bfhi(s.w));
    const uint32_t sg = 0x80008000u;
    sts4(SM_MISC + lane * 16, prmt(s.x, s.x, 0x1010) ^ sg, prmt(s.y, s.y, 0x1010) ^ sg, prmt(s.z, s.z, 0x1010) ^ sg, prmt(s.w, s.w, 0x1010) ^ sg);
    sts4(SM_STAT + 256 + lane * 32, __float_as_uint(r0), __float_as_uint(r1), pack2(r0, r1), prmt(s.x, s.y, 0x7632));
    sts4(SM_STAT + 272 + lane * 32, __float_as_uint(r2), __float_as_uint(r3), pack2(r2, r3), prmt(s.z, s.w, 0x7632));
    __syncwarp();
    mbar_arrive1(B_ST);
  }
  PROF(15, s_stat);
  if (w == 1) {
    mbar_wait(B_ST, layer);
    if (c >= 8) {
      uint2 s;
      for (int it = 0;; ++it) {
        s = ldr2((const uint2*)P.S->ST + ((c >> 3) * 64 - 12 + (lane & 11)));
        if (__all_sync(0xffffffffu, min(s.x, s.y) != 0u)) break;
        spin_guard(it);
      }
      const float r0 = rcp(bfhi(s.x)), r1 = rcp(bfhi(s.y));
      sts4(SM_STAT + 64 + (lane & 11) * 16, __float_as_uint(r0), __float_as_uint(r1), pack2(r0, r1), prmt(s.x, s.y, 0x7632));
    }
    bar_arrive(NB_H, 160);
  }
  if (w >= 2) {
    const uint4* h = P.S->H + (c * 256 + (w & 1) * 128 + lane);
    uint4 hv[4];
#pragma unroll
    for (int z = 0; z < 4; ++z) hv[z] = make_uint4(0, 0, 0, 0);
    bar_sync(NB_RL, 128);
    PROFD(26, s_hb, lds1v(SM_MISC));
    delay(HDELAY);
    for (int it = 0; c >= 8; ++it) {
#pragma unroll
      for (int z = 0; z < 4; ++z) hv[z] = ldr4(h + z * 32);
      if (__all_sync(0xffffffffu, min(min(hv[0].x, hv[1].x), min(hv[2].x, hv[3].x)) != 0u)) break;
      spin_guard(it);
    }
    mbar_wait(B_F + 24, layer);
#pragma unroll
    for (int z = 0; z < 4; ++z) sts4(kvslot(c & 7, 0) + (w & 1) * 2048 + lane * 16 + z * 512, hv[z].x, hv[z].y, movm(hv[z].z), movm(hv[z].w));
    bar_arrive(NB_H, 160);
    PROF(25, s_halo);
  }
}

DEV void finalize(const Params& P, int c, int lane, int layer) {
  PW(12)
  float z[4];
  if (layer == 0) {
    bar_sync(NB_P, 256);
    z[0] = z[1] = z[2] = z[3] = 0.f;
#pragma unroll
    for (int k = 0; k < 2; ++k) { const float4 a = lds4f(SM_RES + 8192 + k * 512 + lane * 16); z[0] += a.x; z[1] += a.y; z[2] += a.z; z[3] += a.w; }
  } else {
    mbar_wait(B_ED + 8 - 2 * (c & 4), 0);
    if (FDELAY) delay(FDELAY);
    const uint4* ps = &P.S->PS[c * 64 + lane];
    uint4 a, b;
    for (int it = 0;; ++it) {
      a = ldr4(ps); b = ldr4(ps + 32);
      if (__all_sync(0xffffffffu, min(a.x, b.x) != 0u)) break;
      spin_guard(it);
    }
    z[0] = __uint_as_float(a.x) + __uint_as_float(b.x); z[1] = __uint_as_float(a.y) + __uint_as_float(b.y);
    z[2] = __uint_as_float(a.z) + __uint_as_float(b.z); z[3] = __uint_as_float(a.w) + __uint_as_float(b.w);
  }
#pragma unroll
  for (int o = 8; o < 32; o <<= 1)
#pragma unroll
    for (int k = 0; k < 4; ++k) z[k] += __shfl_xor_sync(0xffffffffu, z[k], o);
  float m0, m1;
  const float r0 = rcp(ln_sd(z[0], z[1], m0)), r1 = rcp(ln_sd(z[2], z[3], m1));
  const uint32_t wr = nz(pack2(r0, r1)), wm = pack2(m0, m1);
  uint2* so = (uint2*)P.S->SR[layer] + ((lane >> 3) * 1024 + (lane & 2) * 256 + 4 * c + ((lane >> 1) & 2) + (lane & 1));
  str2(so, wr, wm); str2(so + 4096, wr, wm);
  bar_arrive_if(NB_Q, 448, !layer);
  PROF(23, s_sr);
}

DEV void announce(const Params& P, int c, int lane, int layer) {
  PW(13)
  bar_sync(NB_T + 3, layer ? 288 : 160);
  cnt_add(P, 5 * layer, c, lane);
  bar_sync_if(NB_Q, 448, !layer);
  fence_async_smem();
  PROF(24, s_own);
}

DEV void fetch(const Params& P, int c, int lane, int layer) {
  PW(13)
  mbar_expect1(B_E, 24576);
  cnt_wait(P, 5 * layer, c, lane);
#pragma unroll
  for (int k = 0; k < 4; ++k) bulk(SM_R + k * 16384 + R_B, P.S->XG[layer] + (128 * k + c) * 256, 4096, B_E);
  if (layer) delay(SRDELAY);
  bulk(SM_RES, P.S->SR[layer][c >> 4], 8192, B_E);
  if (!layer) { if (!CSP) l2_prefetch(P.wqkv + c * 6144, 12288); l2_prefetch(P.wo + c * 2048, 4096); }
  if (PHOLD) mbar_arrive1_if(B_ST + 8, !layer);
  PROF(25, s_all);
}

DEV void cs_part(const Params& P, int c, int w, int lane, int layer) {
  float cs[8];
#pragma unroll
  for (int k = 0; k < 8; ++k) cs[k] = 0.f;
  const int col = w * 512 + 64 * (c & 7) + 8 * (lane & 7);
#pragma unroll 1
  for (int r = 8 * layer; r < 8; r += CSU) {
    uint4 v[CSU];
#pragma unroll
    for (int k = 0; k < CSU; ++k) v[k] = ldnc4(P.wqkv + ((32 * (c >> 3) + 4 * r + (lane >> 3)) * 1536 + col) + 4 * k * 1536);
#pragma unroll
    for (int k = 0; k < CSU; ++k) {
      cs[0] += bflo(v[k].x); cs[1] += bfhi(v[k].x); cs[2] += bflo(v[k].y); cs[3] += bfhi(v[k].y);
      cs[4] += bflo(v[k].z); cs[5] += bfhi(v[k].z); cs[6] += bflo(v[k].w); cs[7] += bfhi(v[k].w);
    }
  }
  fold<4>(cs, lane, 16); fold<2>(cs, lane, 8);
  str2((float*)P.S->CS + ((c >> 3) * 1536 + col + 2 * (lane >> 3)), max(__float_as_uint(cs[0]), 1u - layer), __float_as_uint(cs[1]));
}

DEV void cs_sum(const Params& P, int c, int w, int lane) {
  float a, b;
  for (int it = 0;; ++it) {
    uint32_t m = ~0u;
    a = b = 0.f;
#pragma unroll
    for (int k = 0; k < 16; ++k) {
      const uint2 u = ldr2((const float*)P.S->CS + (w * 512 + 64 * (c & 7) + 2 * lane) + k * 1536);
      a += __uint_as_float(u.x); b += __uint_as_float(u.y); m = min(m, u.x);
    }
    if (__all_sync(0xffffffffu, m != 0u)) break;
    spin_guard(it);
  }
  const uint32_t hi = pack2(a, b), ad = SM_CS + w * 256 + (lane >> 2) * 32 + (lane & 3) * 4;
  sts1(ad, hi); sts1(ad + 16, pack2(a - bflo(hi), b - bfhi(hi)));
  fence_async_smem();
  __syncwarp();
  mbar_arrive1(B_CS);
}

DEV void x0_get(uint32_t (&x)[8][2], uint32_t a) {
  asm volatile("cp.async.wait_group 0;" ::: "memory");
#pragma unroll
  for (int z = 0; z < 4; ++z) {
    const uint4 v = lds4(a + z * 512);
    x[2 * (z & 2)][z & 1] = v.x; x[2 * (z & 2) + 1][z & 1] = v.y; x[2 * (z & 2) + 2][z & 1] = v.z; x[2 * (z & 2) + 3][z & 1] = v.w;
  }
}

DEV void par_load(const Params& P, int ch, int m, uint32_t (&pv)[8]) {
  const int mo = ch * 128 + m;
  pv[0] = ldnc16(P.Are + mo); pv[1] = ldnc16(P.Aim + mo); pv[2] = ldnc16(P.Bre + mo); pv[3] = ldnc16(P.Bim + mo);
  pv[4] = ldnc16(P.Cre + mo); pv[5] = ldnc16(P.Cim + mo); pv[6] = ldnc16(P.logdt + ch); pv[7] = ldnc16(P.dskip + ch);
}

__global__ void __launch_bounds__(NTHR, 1)
fused_kernel(const __grid_constant__ Params P, const __grid_constant__ CUtensorMap mapW,
             const __grid_constant__ CUtensorMap mapWo) {
  extern __shared__ __align__(1024) uint8_t smem_raw[];
  if (s2u(smem_raw) != SB) __trap();
  const int warp0 = __shfl_sync(0xffffffffu, threadIdx.x >> 5, 0), lane0 = threadIdx.x & 31;
  uint32_t smid; asm volatile("mov.u32 %0,%%smid;" : "=r"(smid));
  const int c = __shfl_sync(0xffffffffu, P.by_sm ? P.role[smid] : blockIdx.x, 0);
  if (c == 255) {
    if (threadIdx.x < NCOPY * NSUB)
#pragma unroll 1
      for (int it = 0; it < 256 && ldr1(P.S->C + 32 * threadIdx.x) < 128 / NSUB; ++it) __nanosleep(200);
    return;
  }
  const int cg = c & 7;
  PW(warp0)
  uint32_t dskip;
  {
    [[maybe_unused]] const int layer = 0;
    const int lane = lane0, g = lane >> 2, t = lane & 3, warp = warp0, k4 = warp >> 2, w = warp & 3;
    uint32_t pv[8];
    if (k4 < 3) par_load(P, 128 * k4 + c, 32 * w + lane, pv);
    else {
#pragma unroll
      for (int n = 0; n < 8; ++n) pv[n] = 0;
    }
    __syncthreads();
    if (XDEL) delay(XDEL);
    const uint16_t* r = P.x0 + ((k4 < 2 ? 8192 * c + 64 * warp : (128 * (c >> 3) + 16 * w) * 512 + 64 * cg) + 1024 * g + 8 * t);
    const uint32_t xa = SM_R + k4 * 16384 + w * 2048 + lane * 16;
    if (k4 != 2) {
#pragma unroll
      for (int z = 0; z < 4; ++z) cp16(xa + z * 512, r + (z & 1) * 512 + (z & 2) * 16);
    }
    sts4(SM_TAP + k4 * TAP_SZ + (32 * w + lane) * 16, 0, 0, 0, 0);
    sts4z_if(SM_TAP + k4 * TAP_SZ + 2048 + (32 * w + lane) * 16, w < 3);
    uint32_t x[8][2];
    if (k4 == 3) {
#pragma unroll
      for (int z = 0; z < 4; ++z) cp16(xa - 16384 + z * 512, r + 32768 + (z & 1) * 512 + (z & 2) * 16);
      asm volatile("cp.async.commit_group;" ::: "memory");
      if (threadIdx.x == 448) {
        asm volatile("prefetch.tensormap [%0];" :: "l"(&mapW) : "memory");
        asm volatile("prefetch.tensormap [%0];" :: "l"(&mapWo) : "memory");
      }
      __syncwarp();
      if (PDELAY) delay(PDELAY);
      par_load(P, 128 * k4 + c, 32 * w + lane, pv);
      XgAddr xd = xg_addr<false>(P.S->XG[0] + (64 * cg * 256 + 16 * (c >> 3)), SM_R + 3 * 16384 + 8192, w, lane, P.zero);
      x0_get(x, xa);
      PROF(27, a_ld);
      xg_put<false>(xd, x);
      x0_get(x, xa - 16384);
      xd.a -= 16384;
      xg_put<false>(xd, x);
      bar_sync(NB_WG + 3, 128);
      xg_store(xd);
      xd.b -= 16384; xd.dst += 8;
      xg_store(xd);
      bar_arrive(NB_T + 3, 160);
      bar_sync(NB_Q, 448);
    } else asm volatile("cp.async.commit_group;" ::: "memory");
    tables(pv, k4, w, lane);
    if (k4 < 2) {
      x0_get(x, xa);
      const float4 s = gram(x, g, P.zero);
      if (t == (g >> 1)) sts4f(SM_RES + 8192 + (warp * 8 + g) * 16, s.x, s.y, s.z, s.w);
      __syncwarp();
      bar_arrive_if(NB_P, 256, warp != 7);
    }
    if (k4 == 2) {
#pragma unroll
      for (int n = 0; n < 14; ++n) mbar_init1(SM_BAR + (n < 10 ? w * 80 : 240 + w * 32) + n * 8, n < 10 ? 1 : (CNT >> (8 * w + 2 * (n - 10 & 2))) & 15);
    }
    dskip = pv[7];
    PROF(1, a_x0);
  }
#pragma unroll 1
  for (int layer = 0; layer < 2; ++layer) {
    int lane = lane_here(P.zero);
    const int warp = warp0 | (layer & P.zero), k4 = warp >> 2, w = warp & 3;
    if (warp == (layer ? 12 : 7)) finalize(P, c, lane, layer);
    if (warp == (layer ? 13 : 6)) { announce(P, c, lane, layer); fetch(P, c, lane, layer); }
    if (layer == 0) {
      if (CSP && k4 == 1 && w != 2) { if (CSP > 1) delay(CSP); cs_part(P, c, w - (w >> 1), lane, 0); }
      taps(dskip, k4, w, lane);
    }
    if (!layer && ((PHOLD >> k4) & 1)) mbar_wait(B_ST + 8, 0);
    conv(P, &mapW, c, k4, w, layer);
    lane = lane_here(P.zero);
    if (k4 < 2) {
      bar_arrive_if(NB_H, 256, warp != 4);
      if (warp == 0) {
        mbar_wait(B_K, 0);
        cnt_wait(P, 1 + 5 * layer, c, lane);
        x_load(P, c, 0, layer);
        PROF(27, m_xi);
      } else if (k4 == 0 && (CSP == 0 || layer)) cs_part(P, c, w - 1, lane, CSP ? 1 : layer);
      attn_phase(P, c, k4, w, lane, layer);
    } else {
      bar_arrive_if(NB_RL, 256, warp >= 10);
      if (k4 == 3) {
        stats(P, c, w, lane, layer);
      } else if (w < 2) {
        bar_sync_if(NB_RL, 256, w);
        cnt_wait(P, 3 + 5 * layer + w, c, lane);
        bar_sync_if(NB_RL, 256, !w);
        if (w) mbar_wait(B_F, layer);
        x_load(P, c, 2 + w, layer);
        if (H5 && w) w_load(&mapW, cg, 5);
        PROF(14, h_xi);
        if (w == 1) str4(&P.S->SR[layer][lane >> 2][4 * c + (lane & 3)], 0, 0, 0, 0);
      } else if (w == 2) {
        mbar_expect1(B_WO, 65536);
        mbar_expect1(B_RES, 16384);
#pragma unroll 1
        for (int q = 0; q < 4; ++q) {
          if (FH && q < 2) { mbar_wait(B_FH + 8 * q, layer); w_load(&mapW, cg, 4 + 2 * q); }
          mbar_wait(B_F + 8 * q, layer);
          if (!FH && q < 2) w_load(&mapW, cg, 4 + 2 * q);
          if (q == 1 || (q == 0 && !H5)) w_load(&mapW, cg, 5 + 2 * q);
          if (WOQ == 0 && ((q + 1) & 2)) tma5(SM_R + (q & 2) * 16384, &mapWo, 64 * cg, 4 * (q & 2), B_WO);
          if (WOQ && q == 2) {
            if (WOQ >= 2) mbar_wait(B_ST, layer);
            tma5(SM_R, &mapWo, 64 * cg, 0, B_WO);
            if (WOQ < 3) tma5(SM_R + 32768, &mapWo, 64 * cg, 8, B_WO);
          }
          if (q == 3) {
#pragma unroll
            for (int e = 0; e < 2; ++e) bulk(SM_RES + e * 8192, P.S->XF + ((2 * (c >> 3) + 1 - e) * 4096 + cg * 512), 8192, B_RES);
          }
          PROF(15 + q, h_w);
        }
      }
      if (k4 == 2 && w != 2) {
        if (layer == 0) cs_sum(P, c, w - (w >> 1), lane);
        if (w == 3) {
          uint4* xz = P.S->XG[layer] + (c * 256 + lane);
          mbar_wait(B_F, layer);
#pragma unroll 1
          for (int k = 0; k < 32; ++k) {
            str4(xz + ((k >> 3) * 32768 + (k & 7) * 32), 0, 0, 0, 0);
            if (ZPACE) __nanosleep(ZPACE);
          }
          PROF(19, h_z);
        }
      }
      if (warp < 10) o_load(P, c, w, lane, layer);
    }
    asm volatile("mov.b32 %0,0;" : "=r"(dskip));
  }
}

typedef CUresult (*EncodeFn)(CUtensorMap*, CUtensorMapDataType, cuuint32_t, void*, const cuuint64_t*, const cuuint64_t*,
                             const cuuint32_t*, const cuuint32_t*, CUtensorMapInterleave, CUtensorMapSwizzle,
                             CUtensorMapL2promotion, CUtensorMapFloatOOBfill);

#define POOL 0
#define GOFF 0
static int place_roles(uint8_t* role) {
  int dev = 0, nsm = 0;
  cudaGetDevice(&dev);
  cudaDeviceGetAttribute(&nsm, cudaDevAttrMultiProcessorCount, dev);
  if (nsm < 128 || nsm > 144 || (nsm & 1)) return 0;
  cudaFuncSetAttribute(fused_kernel, cudaFuncAttributeNonPortableClusterSizeAllowed, 1);
  int occ[9] = {0};
  for (int k = 2; k <= 8; ++k) {
    cudaLaunchConfig_t cfg = {};
    cudaLaunchAttribute at[1];
    at[0].id = cudaLaunchAttributeClusterDimension;
    at[0].val.clusterDim.x = 2 * k; at[0].val.clusterDim.y = 1; at[0].val.clusterDim.z = 1;
    cfg.gridDim = dim3(2 * k); cfg.blockDim = dim3(NTHR); cfg.dynamicSmemBytes = SM_TOTAL; cfg.attrs = at; cfg.numAttrs = 1;
    if (cudaOccupancyMaxActiveClusters(&occ[k], fused_kernel, &cfg) != cudaSuccess) { cudaGetLastError(); occ[k] = 0; }
  }
  int n[10];
  n[7] = occ[8]; n[6] = occ[7]; n[5] = occ[6] - 0; n[4] = occ[5];
  n[3] = occ[4] - n[7]; n[1] = occ[2] - n[3] - n[5] - n[7]; n[0] = n[2] = n[1];
  n[8] = occ[3] - n[2] - n[5];
  const int ntpc = nsm / 2;
  int sum = 0;
  bool ok = n[0] > 0 && n[0] <= 8;
  for (int r = 0; r < 9; ++r) { ok = ok && n[r] >= 0 && (r == 0 || n[r] <= n[r - 1]); sum += n[r]; }
  if (!ok || sum > ntpc) { for (int r = 0; r < 9; ++r) n[r] = r < 8 ? 8 : 0; sum = 64; }
  int tp[8][9], cnt[8] = {0}, pool[72], np = 0, id = 0;
  for (int r = 0; r < 9; ++r)
    for (int g = n[0] - n[r]; g < n[0]; ++g) tp[g][cnt[g]++] = id++;
  for (; id < ntpc; ++id) pool[np++] = id;
  int order[72], no = 0;
  for (int g = 0; g < n[0]; ++g) {
    const int full = cnt[g] / 4 * 4;
    for (int k = 0; k < cnt[g]; ++k) { if (k < full) order[no++] = tp[g][k]; else pool[np++] = tp[g][k]; }
  }
  for (int k = 0; k < np; ++k) order[no++] = pool[POOL == 1 ? np - 1 - k : POOL == 2 ? (k + np - 2) % np : k];
  for (int k = 0; k < 144; ++k) role[k] = 255;
  for (int k = 0; k < 64; ++k) { role[2 * order[k]] = (2 * k + GOFF) & 127; role[2 * order[k] + 1] = (2 * k + 1 + GOFF) & 127; }
  return nsm;
}

extern "C" void kernel_launch(void* const* d_in, const int* in_sizes, int n_in, void* d_out, int out_size) {
  (void)in_sizes; (void)n_in; (void)out_size;
  static EncodeFn enc = nullptr;
  static uint8_t role[144];
  static int nsm = 0;
  static void* scratch = nullptr;
  if (!enc) {
    void* fn = nullptr;
    cudaDriverEntryPointQueryResult qr;
    cudaGetDriverEntryPoint("cuTensorMapEncodeTiled", &fn, cudaEnableDefault, &qr);
    enc = (EncodeFn)fn;
    cudaFuncSetAttribute(fused_kernel, cudaFuncAttributeMaxDynamicSharedMemorySize, SM_TOTAL);
    nsm = place_roles(role);
    cudaGetSymbolAddress(&scratch, g_S);
  }
  CUtensorMap mW, mWo;
  {
    cuuint64_t dim[3] = {512, 512, 3}, str[2] = {3072, 1024};
    cuuint32_t box[3] = {64, 64, 3}, es[3] = {1, 1, 1};
    enc(&mW, CU_TENSOR_MAP_DATA_TYPE_BFLOAT16, 3, d_in[10], dim, str, box, es, CU_TENSOR_MAP_INTERLEAVE_NONE,
        CU_TENSOR_MAP_SWIZZLE_128B, CU_TENSOR_MAP_L2_PROMOTION_NONE, CU_TENSOR_MAP_FLOAT_OOB_FILL_NONE);
  }
  {
    cuuint64_t dim[5] = {512, 2, 4, 4, 16}, str[4] = {1024, 8192, 2048, 32768};
    cuuint32_t box[5] = {64, 2, 4, 4, 8}, es[5] = {1, 1, 1, 1, 1};
    enc(&mWo, CU_TENSOR_MAP_DATA_TYPE_BFLOAT16, 5, d_in[11], dim, str, box, es, CU_TENSOR_MAP_INTERLEAVE_NONE,
        CU_TENSOR_MAP_SWIZZLE_128B, CU_TENSOR_MAP_L2_PROMOTION_NONE, CU_TENSOR_MAP_FLOAT_OOB_FILL_NONE);
  }
  Params P;
  P.x0 = (const uint16_t*)d_in[0]; P.Are = (const uint16_t*)d_in[1]; P.Aim = (const uint16_t*)d_in[2];
  P.Bre = (const uint16_t*)d_in[3]; P.Bim = (const uint16_t*)d_in[4]; P.Cre = (const uint16_t*)d_in[5];
  P.Cim = (const uint16_t*)d_in[6]; P.logdt = (const uint16_t*)d_in[7]; P.dskip = (const uint16_t*)d_in[8];
  P.wqkv = (const uint16_t*)d_in[10]; P.wo = (const uint16_t*)d_in[11]; P.out = (uint16_t*)d_out;
  for (int k = 0; k < 144; ++k) P.role[k] = role[k];
  P.by_sm = nsm > 0;
  P.zero = 0;
  P.S = (Scratch*)scratch;
  fused_kernel<<<nsm > 0 ? nsm : 128, NTHR, SM_TOTAL, cudaStreamPerThread>>>(P, mW, mWo);
}
```

```cpp
#include <cuda_runtime.h>
#include <cuda_bf16.h>
#include <cuda.h>
#include <stdint.h>

#define DEV __device__ __forceinline__

#define NCOPY 4
#define NSUB 1
#define EA 0x2221
constexpr int NTHR = 512;
constexpr int SPIN_LIMIT = 1 << 22;

constexpr uint32_t SB = 1024;
constexpr uint32_t SM_XA   = SB;
constexpr uint32_t SM_S0   = SM_XA + 16384;
constexpr uint32_t SM_S1   = SM_S0 + 49152;
constexpr uint32_t SM_XB   = SM_S1 + 49152;
constexpr uint32_t SM_R    = SM_XB + 16384;
constexpr uint32_t SM_RES  = SM_R + 65536;
constexpr uint32_t SM_TAP  = SM_RES + 16384;
constexpr int TAP_SZ = 3584;
constexpr uint32_t SM_CS   = SM_TAP + 4 * TAP_SZ;
constexpr uint32_t SM_STAT = SM_CS + 800;
constexpr uint32_t SM_MISC = SM_STAT + 1280;
constexpr uint32_t SM_BAR  = SM_MISC + 512;
constexpr int SM_TOTAL = SM_BAR + 448 - SB;
constexpr int R_U = 512, R_A5 = 5120, R_A3 = 8704, R_B = 11776;
constexpr int T_E = 1536, T_O = T_E + 1602, T_C = 3714;
constexpr uint32_t B_W = SM_BAR, B_X = SM_BAR + 64, B_O = SM_BAR + 128, B_WO = SM_BAR + 256, B_RES = SM_BAR + 264;
constexpr uint32_t B_ST = SM_BAR + 272, B_R = SM_BAR + 288, B_E = SM_BAR + 304;
constexpr uint32_t B_F = SM_BAR + 320, B_G = SM_BAR + 352, B_K = SM_BAR + 376, B_ED = SM_BAR + 384, B_CS = SM_BAR + 400, B_FH = SM_BAR + 416;
constexpr uint32_t CNT = 0x143444CC;
constexpr int NB_WG = 1, NB_T = 5, NB_Q = 10, NB_H = 11, NB_P = 14, NB_RL = 15;

struct Scratch {
  uint4    XG[2][512 * 256];
  uint4    XF[32 * 4096];
  uint4    O[32 * 8 * 512];
  uint32_t F[32 * 32];
  uint4    H[17 * 8 * 256];
  uint4    SR[2][8][512];
  uint4    ST[32 * 16];
  uint4    PS[128 * 64];
  float4   CS[16 * 1536 / 4];
  uint32_t C[10 * 32 * 32];
};
__device__ __align__(1024) Scratch g_S;

struct Params {
  int by_sm;
  uint32_t zero;
  Scratch* S;
  const uint16_t *x0, *Are, *Aim, *Bre, *Bim, *Cre, *Cim, *logdt, *dskip, *wqkv, *wo;
  uint16_t* out;
  uint8_t role[144];
};
#define EVENT(n) do {} while (0)
#define PROFD(slot, name, v) do {} while (0)
#define PROF(slot, name) do {} while (0)
#define PW(x)

DEV uint32_t s2u(const void* p) { return (uint32_t)__cvta_generic_to_shared(p); }
template <class T> DEV T opq(T x) { asm volatile("" : "+r"(x)); return x; }
DEV uint32_t pack2(float lo, float hi) { uint32_t d; asm("cvt.rn.bf16x2.f32 %0,%1,%2;" : "=r"(d) : "f"(hi), "f"(lo)); return d; }
DEV float bflo(uint32_t v) { return __uint_as_float(v << 16); }
DEV float bfhi(uint32_t v) { return __uint_as_float(v & 0xFFFF0000u); }
DEV float bfr(float x) { return bflo(pack2(x, 0.f)); }
DEV uint32_t hadd2(uint32_t a, uint32_t b) { uint32_t d; asm("add.rn.bf16x2 %0,%1,%2;" : "=r"(d) : "r"(a), "r"(b)); return d; }
DEV uint32_t hsub2(uint32_t a, uint32_t b) { uint32_t d; asm("sub.rn.bf16x2 %0,%1,%2;" : "=r"(d) : "r"(a), "r"(b)); return d; }
DEV uint32_t hmul2(uint32_t a, uint32_t b) { uint32_t d; asm("mul.rn.bf16x2 %0,%1,%2;" : "=r"(d) : "r"(a), "r"(b)); return d; }
DEV uint32_t hfma2(uint32_t a, uint32_t b, uint32_t c) { uint32_t d; asm("fma.rn.bf16x2 %0,%1,%2,%3;" : "=r"(d) : "r"(a), "r"(b), "r"(c)); return d; }
DEV uint32_t hmax2(uint32_t a, uint32_t b) { uint32_t d; asm("max.bf16x2 %0,%1,%2;" : "=r"(d) : "r"(a), "r"(b)); return d; }
DEV uint32_t prmt(uint32_t a, uint32_t b, uint32_t s) { uint32_t d; asm("prmt.b32 %0,%1,%2,%3;" : "=r"(d) : "r"(a), "r"(b), "r"(s)); return d; }
DEV uint32_t nz(uint32_t v) { uint32_t d; asm("max.u32 %0,%1,1;" : "=r"(d) : "r"(v)); return d; }
DEV uint32_t tagged(uint32_t v, uint32_t m, uint32_t tag) { return (v & ~m) | (tag & m); }
DEV uint32_t both(uint32_t a, uint32_t b, uint32_t x) { uint32_t d; asm("lop3.b32 %0,%1,%2,%3,0x42;" : "=r"(d) : "r"(a), "r"(b), "r"(x)); return d; }
DEV uint4 hadd8(const uint4& a, const uint4& b) { return make_uint4(hadd2(a.x, b.x), hadd2(a.y, b.y), hadd2(a.z, b.z), hadd2(a.w, b.w)); }
DEV uint32_t min4(const uint4& v) { return min(min(v.x, v.y), min(v.z, v.w)); }
DEV float rcp(float x) { float y; asm("rcp.approx.ftz.f32 %0,%1;" : "=f"(y) : "f"(x)); return y; }
DEV float sqrt_(float x) { float y; asm("sqrt.approx.ftz.f32 %0,%1;" : "=f"(y) : "f"(x)); return y; }
DEV float ex2(float x) { float y; asm("ex2.approx.ftz.f32 %0,%1;" : "=f"(y) : "f"(x)); return y; }

DEV uint4 ldr4(const void* p) { uint4 v; asm volatile("ld.relaxed.gpu.global.v4.u32 {%0,%1,%2,%3},[%4];" : "=r"(v.x), "=r"(v.y), "=r"(v.z), "=r"(v.w) : "l"(p) : "memory"); return v; }
DEV void ldr4_if(uint4& v, const void* p, bool c) {
  asm volatile("{.reg .pred q; setp.ne.u32 q,%5,0; @q ld.relaxed.gpu.global.v4.u32 {%0,%1,%2,%3},[%4];}"
    : "+r"(v.x), "+r"(v.y), "+r"(v.z), "+r"(v.w) : "l"(p), "r"((uint32_t)c) : "memory");
}
DEV uint2 ldr2(const void* p) { uint2 v; asm volatile("ld.relaxed.gpu.global.v2.u32 {%0,%1},[%2];" : "=r"(v.x), "=r"(v.y) : "l"(p) : "memory"); return v; }
DEV uint32_t ldr1(const void* p) { uint32_t v; asm volatile("ld.relaxed.gpu.global.u32 %0,[%1];" : "=r"(v) : "l"(p) : "memory"); return v; }
DEV void str4(void* p, uint32_t a, uint32_t b, uint32_t c, uint32_t d) { asm volatile("st.relaxed.gpu.global.v4.u32 [%0],{%1,%2,%3,%4};" :: "l"(p), "r"(a), "r"(b), "r"(c), "r"(d) : "memory"); }
DEV void str4_if(void* p, uint32_t a, uint32_t b, uint32_t c, uint32_t d, bool q) {
  asm volatile("{.reg .pred q; setp.ne.u32 q,%5,0; @q st.relaxed.gpu.global.v4.u32 [%0],{%1,%2,%3,%4};}" :: "l"(p), "r"(a), "r"(b), "r"(c), "r"(d), "r"((uint32_t)q) : "memory");
}
DEV void str2(void* p, uint32_t a, uint32_t b) { asm volatile("st.relaxed.gpu.global.v2.u32 [%0],{%1,%2};" :: "l"(p), "r"(a), "r"(b) : "memory"); }
DEV void str1(void* p, uint32_t a) { asm volatile("st.relaxed.gpu.global.u32 [%0],%1;" :: "l"(p), "r"(a) : "memory"); }
DEV void stw4(void* p, uint32_t a, uint32_t b, uint32_t c, uint32_t d) { asm volatile("st.global.v4.u32 [%0],{%1,%2,%3,%4};" :: "l"(p), "r"(a), "r"(b), "r"(c), "r"(d) : "memory"); }
DEV uint4 ldnc4(const void* p) { uint4 v; asm volatile("ld.global.nc.v4.u32 {%0,%1,%2,%3},[%4];" : "=r"(v.x), "=r"(v.y), "=r"(v.z), "=r"(v.w) : "l"(p)); return v; }
DEV uint4 ldw4(const void* p) { uint4 v; asm volatile("ld.global.v4.u32 {%0,%1,%2,%3},[%4];" : "=r"(v.x), "=r"(v.y), "=r"(v.z), "=r"(v.w) : "l"(p) : "memory"); return v; }
DEV void cp16(uint32_t d, const void* p) { asm volatile("cp.async.cg.shared.global [%0],[%1],16;" :: "r"(d), "l"(p) : "memory"); }
DEV uint32_t ldnc16(const void* p) { uint32_t v; asm volatile("ld.global.u16 %0,[%1];" : "=r"(v) : "l"(p) : "memory"); return v; }

DEV uint32_t lds1v(uint32_t a) { uint32_t v; asm volatile("ld.volatile.shared.u32 %0,[%1];" : "=r"(v) : "r"(a) : "memory"); return v; }
DEV uint4 lds4v(uint32_t a) { uint4 v; asm volatile("ld.volatile.shared.v4.u32 {%0,%1,%2,%3},[%4];" : "=r"(v.x), "=r"(v.y), "=r"(v.z), "=r"(v.w) : "r"(a) : "memory"); return v; }
DEV uint32_t lds1(uint32_t a) { uint32_t v; asm volatile("ld.shared.u32 %0,[%1];" : "=r"(v) : "r"(a)); return v; }
DEV uint2 lds2(uint32_t a) { uint2 v; asm volatile("ld.shared.v2.u32 {%0,%1},[%2];" : "=r"(v.x), "=r"(v.y) : "r"(a)); return v; }
DEV uint4 lds4(uint32_t a) { uint4 v; asm volatile("ld.shared.v4.u32 {%0,%1,%2,%3},[%4];" : "=r"(v.x), "=r"(v.y), "=r"(v.z), "=r"(v.w) : "r"(a)); return v; }
DEV uint32_t lds16(uint32_t a) { uint32_t v; asm volatile("ld.shared.u16 %0,[%1];" : "=r"(v) : "r"(a)); return v; }
DEV float lds1f(uint32_t a) { float v; asm volatile("ld.shared.f32 %0,[%1];" : "=f"(v) : "r"(a)); return v; }
DEV float2 lds2f(uint32_t a) { float2 v; asm volatile("ld.shared.v2.f32 {%0,%1},[%2];" : "=f"(v.x), "=f"(v.y) : "r"(a)); return v; }
DEV float4 lds4f(uint32_t a) { float4 v; asm volatile("ld.shared.v4.f32 {%0,%1,%2,%3},[%4];" : "=f"(v.x), "=f"(v.y), "=f"(v.z), "=f"(v.w) : "r"(a)); return v; }
DEV void sts1(uint32_t a, uint32_t v) { asm volatile("st.shared.u32 [%0],%1;" :: "r"(a), "r"(v) : "memory"); }
DEV void sts16(uint32_t a, uint32_t v) { asm volatile("{.reg .b16 h; cvt.u16.u32 h,%1; st.shared.u16 [%0],h;}" :: "r"(a), "r"(v) : "memory"); }
DEV void sts2f(uint32_t a, float x, float y) { asm volatile("st.shared.v2.f32 [%0],{%1,%2};" :: "r"(a), "f"(x), "f"(y) : "memory"); }
DEV void sts4f(uint32_t a, float x, float y, float z, float w) { asm volatile("st.shared.v4.f32 [%0],{%1,%2,%3,%4};" :: "r"(a), "f"(x), "f"(y), "f"(z), "f"(w) : "memory"); }
DEV void sts4(uint32_t a, uint32_t x, uint32_t y, uint32_t z, uint32_t w) { asm volatile("st.shared.v4.u32 [%0],{%1,%2,%3,%4};" :: "r"(a), "r"(x), "r"(y), "r"(z), "r"(w) : "memory"); }
DEV void sts4z_if(uint32_t a, bool c) { asm volatile("{.reg .pred q; setp.ne.u32 q,%1,0; @q st.shared.v4.u32 [%0],{%2,%2,%2,%2};}" :: "r"(a), "r"((uint32_t)c), "r"(0) : "memory"); }

DEV void ldsm4t(uint32_t& r0, uint32_t& r1, uint32_t& r2, uint32_t& r3, uint32_t a) { asm volatile("ldmatrix.sync.aligned.m8n8.x4.trans.shared.b16 {%0,%1,%2,%3},[%4];" : "=r"(r0), "=r"(r1), "=r"(r2), "=r"(r3) : "r"(a) : "memory"); }
DEV void stsm4(uint32_t a, uint32_t r0, uint32_t r1, uint32_t r2, uint32_t r3) { asm volatile("stmatrix.sync.aligned.m8n8.x4.shared.b16 [%0],{%1,%2,%3,%4};" :: "r"(a), "r"(r0), "r"(r1), "r"(r2), "r"(r3) : "memory"); }
DEV void stsm2(uint32_t a, uint32_t r0, uint32_t r1) { asm volatile("stmatrix.sync.aligned.m8n8.x2.shared.b16 [%0],{%1,%2};" :: "r"(a), "r"(r0), "r"(r1) : "memory"); }
DEV void stsm4t(uint32_t a, uint32_t r0, uint32_t r1, uint32_t r2, uint32_t r3) { asm volatile("stmatrix.sync.aligned.m8n8.x4.trans.shared.b16 [%0],{%1,%2,%3,%4};" :: "r"(a), "r"(r0), "r"(r1), "r"(r2), "r"(r3) : "memory"); }
DEV uint32_t movm(uint32_t a) { uint32_t d; asm volatile("movmatrix.sync.aligned.m8n8.trans.b16 %0,%1;" : "=r"(d) : "r"(a)); return d; }
DEV void mma16(float (&d)[4], uint32_t a0, uint32_t a1, uint32_t a2, uint32_t a3, uint32_t b0, uint32_t b1) {
  asm volatile("mma.sync.aligned.m16n8k16.row.col.f32.bf16.bf16.f32 {%0,%1,%2,%3},{%4,%5,%6,%7},{%8,%9},{%0,%1,%2,%3};"
    : "+f"(d[0]), "+f"(d[1]), "+f"(d[2]), "+f"(d[3]) : "r"(a0), "r"(a1), "r"(a2), "r"(a3), "r"(b0), "r"(b1));
}
DEV void mma16z(float (&d)[4], uint32_t a0, uint32_t a1, uint32_t a2, uint32_t a3, uint32_t b0, uint32_t b1) {
  asm volatile("mma.sync.aligned.m16n8k16.row.col.f32.bf16.bf16.f32 {%0,%1,%2,%3},{%4,%5,%6,%7},{%8,%9},{%10,%10,%10,%10};"
    : "=f"(d[0]), "=f"(d[1]), "=f"(d[2]), "=f"(d[3]) : "r"(a0), "r"(a1), "r"(a2), "r"(a3), "r"(b0), "r"(b1), "f"(0.f));
}
DEV void mma8z(float (&d)[4], uint32_t a0, uint32_t a1, uint32_t b0) {
  asm volatile("mma.sync.aligned.m16n8k8.row.col.f32.bf16.bf16.f32 {%0,%1,%2,%3},{%4,%5},{%6},{%7,%7,%7,%7};"
    : "=f"(d[0]), "=f"(d[1]), "=f"(d[2]), "=f"(d[3]) : "r"(a0), "r"(a1), "r"(b0), "f"(0.f));
}
DEV void mma8(float (&d)[4], uint32_t a0, uint32_t a1, uint32_t b0) {
  asm volatile("mma.sync.aligned.m16n8k8.row.col.f32.bf16.bf16.f32 {%0,%1,%2,%3},{%4,%5},{%6},{%0,%1,%2,%3};"
    : "+f"(d[0]), "+f"(d[1]), "+f"(d[2]), "+f"(d[3]) : "r"(a0), "r"(a1), "r"(b0));
}

DEV void bar_sync(int id, int n) { asm volatile("bar.sync %0,%1;" :: "r"(id), "r"(n) : "memory"); }
DEV void bar_arrive(int id, int n) { asm volatile("bar.arrive %0,%1;" :: "r"(id), "r"(n) : "memory"); }
DEV void bar_sync_if(int id, int n, int c) { asm volatile("{.reg .pred q; setp.ne.s32 q,%2,0; @q bar.sync %0,%1;}" :: "r"(id), "r"(n), "r"(c) : "memory"); }
DEV void bar_arrive_if(int id, int n, int c) { asm volatile("{.reg .pred q; setp.ne.s32 q,%2,0; @q bar.arrive %0,%1;}" :: "r"(id), "r"(n), "r"(c) : "memory"); }
DEV bool bar_any(int id, int n, bool c) {
  uint32_t r; asm volatile("{.reg .pred p,q; setp.ne.u32 q,%3,0; bar.red.or.pred p,%1,%2,q; selp.u32 %0,1,0,p;}" : "=r"(r) : "r"(id), "r"(n), "r"((uint32_t)c) : "memory");
  return __any_sync(0xffffffffu, r);
}
DEV void fence_async_glob() { asm volatile("fence.proxy.async.global;" ::: "memory"); }
DEV void fence_async_smem() { asm volatile("fence.proxy.async.shared::cta;" ::: "memory"); }
DEV void fence_gpu() { asm volatile("fence.acq_rel.gpu;" ::: "memory"); }
DEV void mbar_wait(uint32_t b, uint32_t ph) {
  asm volatile("{\n.reg .pred p;\nW: mbarrier.try_wait.parity.shared::cta.b64 p,[%0],%1;\n@!p bra W;\n}" :: "r"(b), "r"(ph) : "memory");
}
DEV bool mbar_test(uint32_t b, uint32_t ph) {
  uint32_t r; asm volatile("{.reg .pred p; mbarrier.test_wait.parity.shared::cta.b64 p,[%1],%2; selp.u32 %0,1,0,p;}" : "=r"(r) : "r"(b), "r"(ph) : "memory");
  return __all_sync(0xffffffffu, r);
}
DEV uint32_t mbar_test2(uint32_t b, uint32_t ph) {
  uint32_t r; asm volatile("{.reg .pred p,q; mbarrier.test_wait.parity.shared::cta.b64 p,[%1],%2; mbarrier.test_wait.parity.shared::cta.b64 q,[%1+8],%2;\n"
                           "and.pred p,p,q; selp.u32 %0,1,0,p;}" : "=r"(r) : "r"(b), "r"(ph) : "memory");
  return r;
}
DEV void spin_guard(int it) { asm volatile("{.reg .pred p; setp.gt.s32 p,%0,%1; @p trap;}" :: "r"(it), "n"(SPIN_LIMIT)); }
DEV uint32_t here(uint32_t zero) {
  uint32_t d; asm volatile("mov.u32 %0,%%clock;" : "=r"(d) :: "memory"); return d & zero;
}
DEV int lane_here(uint32_t zero) {
  uint32_t d; asm volatile("mov.u32 %0,%%laneid;" : "=r"(d)); return d | here(zero);
}
DEV void delay(uint32_t n) { const uint32_t t0 = clock(); while ((uint32_t)clock() - t0 < n); __syncwarp(); }
DEV void poll(const uint32_t* p, uint32_t n) {
  for (int it = 0; !__all_sync(0xffffffffu, ldr1(p) >= n); ++it) spin_guard(it);
}
DEV void cnt_add(const Params& P, int n, int c, int lane) { asm volatile("{.reg .pred p; setp.lt.s32 p,%1,%2; @p red.relaxed.gpu.global.add.u32 [%0],1;}" :: "l"(P.S->C + (32 * (NSUB * lane + c % NSUB) + n * 1024)), "r"(lane), "n"(NCOPY) : "memory"); }
DEV void cnt_wait(const Params& P, int n, int c, int lane) { poll(P.S->C + (32 * (NSUB * (c / (128 / NCOPY)) + lane % NSUB) + n * 1024), 128 / NSUB); }
DEV void mbar_init1(uint32_t b, int n) { asm volatile("{.reg .pred p; elect.sync _|p,0xffffffff; @p mbarrier.init.shared::cta.b64 [%0],%1;}" :: "r"(b), "r"(n) : "memory"); }
DEV void mbar_arrive1(uint32_t b) { asm volatile("{.reg .pred p; elect.sync _|p,0xffffffff; @p mbarrier.arrive.shared::cta.b64 _,[%0];}" :: "r"(b) : "memory"); }
DEV void mbar_arrive1_if(uint32_t b, int c) {
  asm volatile("{.reg .pred p,q; setp.ne.s32 q,%1,0; elect.sync _|p,0xffffffff; and.pred p,p,q; @p mbarrier.arrive.shared::cta.b64 _,[%0];}" :: "r"(b), "r"(c) : "memory");
}
DEV void mbar_expect1(uint32_t b, int bytes) { asm volatile("{.reg .pred p; elect.sync _|p,0xffffffff; @p mbarrier.arrive.expect_tx.shared::cta.b64 _,[%0],%1;}" :: "r"(b), "r"(bytes) : "memory"); }
DEV void flag_set1(uint32_t* q) { asm volatile("{.reg .pred p; elect.sync _|p,0xffffffff; @p st.relaxed.gpu.global.u32 [%0],1;}" :: "l"(q) : "memory"); }
DEV void tma3(uint32_t dst, const CUtensorMap* m, int c0, int c1, uint32_t bar) {
  asm volatile("{.reg .pred p; elect.sync _|p,0xffffffff;\n"
    "@p cp.async.bulk.tensor.3d.shared::cluster.global.mbarrier::complete_tx::bytes [%0],[%1,{%2,%3,%5}],[%4];}"
    :: "r"(dst), "l"(m), "r"(c0), "r"(c1), "r"(bar), "r"(0) : "memory");
}
DEV void tma5(uint32_t dst, const CUtensorMap* m, int c0, int c4, uint32_t bar) {
  asm volatile("{.reg .pred p; elect.sync _|p,0xffffffff;\n"
    "@p cp.async.bulk.tensor.5d.shared::cluster.global.mbarrier::complete_tx::bytes [%0],[%1,{%2,%5,%5,%5,%3}],[%4];}"
    :: "r"(dst), "l"(m), "r"(c0), "r"(c4), "r"(bar), "r"(0) : "memory");
}
DEV void bulk(uint32_t dst, const void* src, int bytes, uint32_t bar) {
  asm volatile("{.reg .pred p; elect.sync _|p,0xffffffff;\n@p cp.async.bulk.shared::cluster.global.mbarrier::complete_tx::bytes [%0],[%1],%2,[%3];}" :: "r"(dst), "l"(src), "r"(bytes), "r"(bar) : "memory");
}
DEV void bulk_store(void* dst, uint32_t src, int bytes) {
  asm volatile("{.reg .pred p; elect.sync _|p,0xffffffff;\n@p cp.async.bulk.global.shared::cta.bulk_group [%0],[%1],%2;}" :: "l"(dst), "r"(src), "r"(bytes) : "memory");
}
DEV void l2_prefetch(const void* src, int bytes) {
  asm volatile("{.reg .pred p; elect.sync _|p,0xffffffff;\n@p cp.async.bulk.prefetch.L2.global [%0],%1;}" :: "l"(src), "r"(bytes) : "memory");
}

DEV uint64_t mkdesc(uint32_t addr, uint32_t lbo, uint32_t sbo, uint32_t swz) {
  return (uint64_t)((addr >> 4) | ((lbo >> 4) << 16)) | ((uint64_t)((sbo >> 4) | (swz << 30)) << 32);
}
DEV void wg_fence() { asm volatile("wgmma.fence.sync.aligned;" ::: "memory"); }
DEV void wg_commit() { asm volatile("wgmma.commit_group.sync.aligned;" ::: "memory"); }
template <int N> DEV void wg_wait() { asm volatile("wgmma.wait_group.sync.aligned %0;" :: "n"(N) : "memory"); }
template <int N> DEV void zerov(float (&d)[N]) {
#pragma unroll
  for (int i = 0; i < N; ++i) asm volatile("mov.b32 %0,0;" : "=f"(d[i]));
}
template <int N> DEV void undef(float (&d)[N]) {
#pragma unroll
  for (int i = 0; i < N; ++i) asm volatile("" : "=f"(d[i]));
}
#define R4(d, o) "+f"(d[o]), "+f"(d[o + 1]), "+f"(d[o + 2]), "+f"(d[o + 3])
#define R8(d, o) R4(d, o), R4(d, o + 4)
#define R16(d, o) R8(d, o), R8(d, o + 8)
#define R32(d, o) R16(d, o), R16(d, o + 16)
#define L0 "%0,%1,%2,%3,%4,%5,%6,%7,%8,%9,"
#define L10(a) "%" #a "0,%" #a "1,%" #a "2,%" #a "3,%" #a "4,%" #a "5,%" #a "6,%" #a "7,%" #a "8,%" #a "9,"
#define WG_HEAD(pr, n) "{.reg .pred p; setp.ne.s32 p,%" #pr ",0;\nwgmma.mma_async.sync.aligned.m64n" #n "k16.f32.bf16.bf16 {"
DEV void wg_rs64k(float (&d)[32], const uint32_t (&a)[4], uint64_t db, int acc) {
  asm volatile(WG_HEAD(37, 64) L0 L10(1) L10(2) "%30,%31},{%32,%33,%34,%35},%36,p,1,1,0;}"
    : R32(d, 0) : "r"(a[0]), "r"(a[1]), "r"(a[2]), "r"(a[3]), "l"(db), "r"(acc));
}
DEV void wg_rs48t(float (&d)[24], const uint32_t (&a)[4], uint64_t db, int acc) {
  asm volatile(WG_HEAD(29, 48) L0 L10(1) "%20,%21,%22,%23},{%24,%25,%26,%27},%28,p,1,1,1;}"
    : R16(d, 0), R8(d, 16) : "r"(a[0]), "r"(a[1]), "r"(a[2]), "r"(a[3]), "l"(db), "r"(acc));
}
DEV void wg_rs32t(float (&d)[16], const uint32_t (&a)[4], uint64_t db, int acc) {
  asm volatile(WG_HEAD(21, 32) L0 "%10,%11,%12,%13,%14,%15},{%16,%17,%18,%19},%20,p,1,1,1;}"
    : R16(d, 0) : "r"(a[0]), "r"(a[1]), "r"(a[2]), "r"(a[3]), "l"(db), "r"(acc));
}
DEV void wg_ss48(float (&d)[24], uint64_t da, uint64_t db, int acc) {
  asm volatile(WG_HEAD(26, 48) L0 L10(1) "%20,%21,%22,%23},%24,%25,p,1,1,1,1;}" : R16(d, 0), R8(d, 16) : "l"(da), "l"(db), "r"(acc));
}
DEV void wg_ss64(float (&d)[32], uint64_t da, uint64_t db, int acc) {
  asm volatile(WG_HEAD(34, 64) L0 L10(1) L10(2) "%30,%31},%32,%33,p,1,1,0,1;}" : R32(d, 0) : "l"(da), "l"(db), "r"(acc));
}
DEV void wg_ss192(float (&d)[96], uint64_t da, uint64_t db, int acc) {
  asm volatile(WG_HEAD(98, 192) L0 L10(1) L10(2) L10(3) L10(4) L10(5) L10(6) L10(7) L10(8) "%90,%91,%92,%93,%94,%95},%96,%97,p,1,1,1,1;}"
    : R32(d, 0), R32(d, 32), R32(d, 64) : "l"(da), "l"(db), "r"(acc));
}

DEV void wg_rs192t(float (&d)[96], const uint32_t (&a)[4], uint64_t db) {
  asm volatile("wgmma.mma_async.sync.aligned.m64n192k16.f32.bf16.bf16 {" L0 L10(1) L10(2) L10(3) L10(4) L10(5) L10(6) L10(7) L10(8) "%90,%91,%92,%93,%94,%95},{%96,%97,%98,%99},%100,1,1,1,1;"
    : R32(d, 0), R32(d, 32), R32(d, 64) : "r"(a[0]), "r"(a[1]), "r"(a[2]), "r"(a[3]), "l"(db));
}

DEV float ln_sd(float s, float q, float& m) {
  m = s * (1.f / 512.f);
  return bfr(sqrt_(bfr(bfr(fmaxf(q * (1.f / 512.f) - m * m, 0.f)) + 1e-5f)));
}
DEV float4 gram(const uint32_t (&w)[8][2], int g, uint32_t zero) {
  float s[4], q[4][4];
  const uint32_t o0 = 0x3F803F80u | zero, o1 = 0x3F803F80u ^ zero;
#pragma unroll
  for (int j = 0; j < 8; ++j) {
#pragma unroll
    for (int h = 0; h < 2; ++h) { if (j < 2) mma8z(q[2 * j + h], w[j][0], w[j][1], w[j][h]); else mma8(q[2 * (j & 1) + h], w[j][0], w[j][1], w[j][h]); }
    if (j == 1) mma16z(s, w[0][0], w[0][1], w[1][0], w[1][1], o0, o1);
    else if (j & 1) mma16(s, w[j - 1][0], w[j - 1][1], w[j][0], w[j][1], o0, o1);
  }
  const bool od = g & 1;
  return make_float4(s[0], od ? q[0][1] + q[2][1] : q[0][0] + q[2][0], s[2], od ? q[1][3] + q[3][3] : q[1][2] + q[3][2]);
}
DEV void keep(uint32_t v, uint32_t zero) {
  asm volatile("{.reg .pred p; setp.ne.u32 p,%1,0; @p st.shared.u32 [%0],%0;}" :: "r"(v), "r"(zero) : "memory");
}
DEV void keep(const void* v, uint32_t zero) { asm volatile("{.reg .pred p; setp.ne.u32 p,%1,0; @p st.global.u32 [%0],%1;}" :: "l"(v), "r"(zero) : "memory"); }
struct XgAddr { uint32_t a, b; uint4* dst; };
template <bool FRAG> DEV XgAddr xg_addr(uint4* dst, uint32_t stg, int wp, int lane, uint32_t zero) {
  const int t = lane & 3, r = 4 * wp + (lane >> 3);
  XgAddr x = {stg + t * (FRAG ? 256 : 1024) + ((wp ^ t) * 32) + (lane >> 2) * 4,
              stg + r * 128 + (((lane & 7) ^ (2 * (((r >> 1) ^ (r >> 3)) & 3))) * 16), dst + (r * 256 + (lane & 7))};
  keep(x.a, zero); keep(x.b, zero); keep(x.dst, zero);
  return x;
}
template <bool FRAG> DEV void xg_put(const XgAddr& x, const uint32_t (&w)[8][2]) {
#pragma unroll
  for (int n = 0; n < 8; ++n) {
    const uint32_t b = (x.a ^ ((n & 3) * 32)) + (FRAG ? n * 1024 : (n >> 2) * 4096 + (n & 3) * 256);
    sts1(b, prmt(w[n][0], w[n][1], 0x5410)); sts1(b + 128, prmt(w[n][0], w[n][1], 0x7632));
  }
}
DEV void xg_store(const XgAddr& x) {
#pragma unroll
  for (int k = 0; k < 4; ++k) {
    const uint4 v = lds4((x.b ^ ((k & 1) * 64)) + k * 2048);
    str4(x.dst + k * 4096, nz(v.x), v.y, v.z, v.w);
  }
}
template <int N, int M> DEV void fold(float (&v)[M], int lane, int bit) {
  const bool b = lane & bit;
#pragma unroll
  for (int k = 0; k < N; ++k) { const float sn = b ? v[k] : v[k + N], kp = b ? v[k + N] : v[k]; v[k] = kp + __shfl_xor_sync(0xffffffffu, sn, bit); }
}
DEV void refetch(uint32_t dst, const uint4* src, int half, int e, int w) {
#pragma unroll 1
  for (int r = 0; r < 2; ++r) {
    if (w == 0) { mbar_expect1(B_R + 8 * e, half); bulk(dst + r * half, src + r * (half >> 4), half, B_R + 8 * e); }
    mbar_wait(B_R + 8 * e, r);
    bar_sync(NB_WG + e, 128);
  }
}
DEV uint32_t kvslot(int cg, int pos) { return (pos & 2 ? SM_XA : SM_S1) + (cg < 4 ? 5 : 2) * 8192 + (pos & 1) * 4096; }
DEV uint32_t xstage(int q, int e) { return ((q + 1) & 2) ? SM_R + ((q & 2) + e) * 16384 : e ? SM_XB : SM_XA; }
DEV void cmul(float& orr, float& oi, float ar, float ai, float br, float bi) {
  float r = ar * br - ai * bi, i = ar * bi + ai * br; orr = r; oi = i;
}
DEV void cexp_(float al, float bt, float s, float& er, float& ei) {
  float mag = ex2(al * s), ph = bt * s;
  ph -= rintf(ph);
  float ang = ph * 6.283185307179586f;
  er = mag * __cosf(ang); ei = mag * __sinf(ang);
}

#define KS 2048
DEV void put8(uint32_t a, const float (&r)[8], const float (&i)[8]) {
  sts4(a, pack2(r[0], r[1]), pack2(r[2], r[3]), pack2(r[4], r[5]), pack2(r[6], r[7]));
  sts4(a + 1024, pack2(i[0], i[1]), pack2(i[2], i[3]), pack2(i[4], i[5]), pack2(i[6], i[7]));
}
DEV void tables(const uint32_t (&pv)[8], int k4, int w, int lane) {
  PW(4 * k4 + w)
  [[maybe_unused]] const int layer = 0;
  const float dt = bfr(__expf(bflo(pv[6])));
  const float al = dt * bflo(pv[0]) * 1.4426950408889634f, bt = dt * bflo(pv[1]) * 0.15915494309189535f;
  float qr[8], qi[8], yr[8], yi[8];
  cmul(qr[0], qi[0], bflo(pv[4]), bflo(pv[5]), dt * bflo(pv[2]), dt * bflo(pv[3]));
  PROFD(2, a_par, __float_as_uint(qr[0] + al + bt));
  float e1r, e1i, eMr, eMi, eLr, eLi;
  cexp_(al, bt, 1.f, e1r, e1i); cexp_(al, -bt, 8.f, yr[1], yi[1]); cexp_(al, -bt, 64.f, eMr, eMi); cexp_(al, bt, 256.f, eLr, eLi);
  const uint32_t ad = SB + k4 * 32768 + (w & 1) * 512 + lane * 16, am = ad + (w >> 1) * KS, an = ad + (8 + 3 * (w >> 1)) * KS;
  yr[0] = 1.f; yi[0] = 0.f;
#pragma unroll
  for (int k = 1; k < 8; ++k) {
    cmul(qr[k], qi[k], qr[k - 1], qi[k - 1], e1r, e1i);
    if (k > 1) cmul(yr[k], yi[k], yr[k - 1], yi[k - 1], yr[1], yi[1]);
  }
  put8(an, qr, qi);
#pragma unroll
  for (int j = 0; j < 4; ++j) {
    put8(am + j * 2 * KS, yr, yi);
#pragma unroll
    for (int k = 0; k < 8; ++k) {
      if (j == 0 && k == 0) { yr[0] = eMr; yi[0] = eMi; } else if (j < 3) cmul(yr[k], yi[k], yr[k], yi[k], eMr, eMi);
    }
    if (j == 0) {
#pragma unroll
      for (int k = 0; k < 8; ++k) { const int o = k < 4 ? 2 * k : k < 6 ? 2 * k - 8 : k - 2; cmul(qr[k], qi[k], qr[o], qi[o], eLr, eLi); }
      put8(an + KS, qr, qi);
    } else if (j == 1) {
#pragma unroll
      for (int k = 0; k < 5; ++k) cmul(qr[k], qi[k], qr[k ? k - 1 : 6], qi[k ? k - 1 : 6], eLr, eLi);
      put8(an + 2 * KS, qr, qi);
    }
  }
  PROF(3, a_tab);
}

DEV void sts16_if(uint32_t a, uint32_t v, bool c) { asm volatile("{.reg .pred q; .reg .b16 h; setp.ne.u32 q,%2,0; cvt.u16.u32 h,%1; @q st.shared.u16 [%0],h;}" :: "r"(a), "r"(v), "r"((uint32_t)c) : "memory"); }
DEV void sts1_if(uint32_t a, uint32_t v, bool c) { asm volatile("{.reg .pred q; setp.ne.u32 q,%2,0; @q st.shared.u32 [%0],%1;}" :: "r"(a), "r"(v), "r"((uint32_t)c) : "memory"); }
DEV void taps(uint32_t dskip, int k4, int w, int lane) {
  PW(4 * k4 + w)
  [[maybe_unused]] const int layer = 0;
  fence_async_smem();
  bar_sync((k4 & 1) ? NB_WG + k4 : NB_Q, (k4 & 1) ? 128 : 448);
  float d[24];
  undef(d);
  const uint64_t da = mkdesc(SB + k4 * 32768, 1024, KS, 0);
  wg_fence();
#pragma unroll
  for (int j = 0; j < 8; ++j) wg_ss48(d, da + j * 8, da + KS / 2 + j * 8, j);
  wg_commit();
  const int b = 8 * w + (lane >> 2), t = lane & 3, id = 32 * w + lane;
  constexpr int DO = T_O - T_E;
  const uint32_t te = SM_TAP + k4 * TAP_SZ + T_E, a0 = te - 16 * b - 4 * t;
  const uint32_t a1 = a0 - 512 - 4 * t, a2 = te - 2 * (511 + b) - 64 * t, a3 = te + (T_C - T_E) - 2 * (127 + b) - 128 * t;
  wg_wait<0>();
  PROF(4, a_mma);
  {
    const uint32_t v = pack2(d[1] + d[15], d[0] + d[14] + (id ? 0.f : bflo(dskip)));
    sts1(a0 + DO - 2, v); sts16(a0 - 2, v); sts16(a0, v >> 16);
  }
  {
    const uint32_t v = pack2(d[5] + d[19], d[4] + d[18]), u = prmt(v, v, 0x3232);
    const bool lo = t < 2, k512 = id == 2;
    sts1_if(k512 ? te - 2 * 512 : a1, u, (lo && id) || k512);
    sts1_if(k512 ? te - 2 * 514 : a1 - 4, k512 ? u : v, lo || k512);
    sts1_if(k512 ? te + DO - 2 * 513 : a1 + DO - 2, u, lo || k512);
    sts16(lo ? a1 + DO - 4 : a2 + DO - 194, v);
    sts16(lo ? (id ? a1 + DO + 2 : a1) : k512 ? te + DO - 2 * 511 : a2 + DO, u);
    sts16_if(a2 - 194, v, !lo);
    sts16_if(k512 ? te + DO - 2 * 514 : a2, u, !lo);
  }
  {
    const uint32_t v = pack2(d[8] + d[22], d[9] + d[23]);
    sts16_if(id ? a3 : te - 2 * 639, v, t < 2 || id == 2);
    sts16_if(a3 - 64, v >> 16, t < 2);
    sts16_if(te + DO - 2 * 639, v, id == 0);
  }
  bar_sync(NB_WG + k4, 128);
  mbar_arrive1_if(B_K, w == 0);
}

DEV uint32_t cpy(uint32_t v, uint32_t id) {
  uint32_t d; asm volatile("prmt.b32 %0,%1,%1,%2;" : "=r"(d) : "r"(v), "r"(id)); return d;
}
DEV uint32_t uoff(int s) { return (s ^ ((s >> 3) & 3)) * 16; }
template <bool FULL> DEV void boxes(const uint32_t (&u)[10], uint32_t a, uint32_t a9, uint32_t a7, uint32_t (&pv)[4]) {
  uint32_t v[8], p[8], x[4], y[4];
#pragma unroll
  for (int j = 0; j < 8; ++j) { v[j] = prmt(u[j], u[j + 1], 0x5432); p[j] = hadd2(u[j], v[j]); }
#pragma unroll
  for (int j = 0; j < 4; ++j) { x[j] = hadd2(hadd2(p[j + 1], p[j + 2]), u[j + 3]); y[j] = hadd2(v[j + 3], p[j + 4]); }
  sts4(a + R_A5, x[0], x[1], x[2], x[3]);
  sts4(a + R_A3, y[0], y[1], y[2], y[3]);
  if (FULL) {
#pragma unroll
    for (int j = 0; j < 4; ++j) { x[j] = hadd2(x[j], hadd2(v[j], v[j + 3])); y[j] = hadd2(x[j], hadd2(u[j], u[j + 4])); pv[j] = p[j + 4]; }
    sts4(a7, x[0], x[1], x[2], x[3]);
    sts4(a9, y[0], y[1], y[2], y[3]);
  }
}
DEV void halo(uint32_t (&u)[10], uint32_t a, int lane) {
  asm volatile("{.reg .pred p,q; setp.eq.s32 p,%8,0; setp.lt.s32 q,%8,2;\n@p ld.shared.v4.u32 {%2,%3,%4,%5},[%6];\n@q ld.shared.v2.u32 {%0,%1},[%7];}"
    : "+r"(u[0]), "+r"(u[1]), "+r"(u[2]), "+r"(u[3]), "+r"(u[4]), "+r"(u[5]) : "r"(a), "r"(a + 24 - 16 * lane), "r"(lane));
}
#define ROT 2
#define G1 -1
#define G2 0
#define G3 1
#define TPS 0x9135
#define GMASK ((G1 >= 0 ? 2 : 0) | (G2 >= 0 ? 4 : 0) | (G3 >= 0 ? 8 : 0))
#define GATE1(g, n, p) if (g >= 0 && (g & 3) == p) mbar_arrive1_if(B_G + 8 * n, k4 == (g >> 2));
#define GATE(p) GATE1(G1, 0, p) GATE1(G2, 1, p) GATE1(G3, 2, p)
#define TMASK(p) (((TPS & 15) == p) | ((((TPS >> 4) & 15) == p) << 1) | ((((TPS >> 8) & 15) == p) << 2) | ((((TPS >> 12) & 15) == p) << 3))
#define TURN(p) if (TMASK(p) == 15) bar_arrive(NB_T + 1 + k4, 256); else if (TMASK(p)) { if ((TMASK(p) >> k4) & 1) bar_arrive(NB_T + 1 + k4, 256); }
#define ANN(p, dep) if (EA & (0x1111 * p)) cnt_add(P, 1 + 5 * layer + k4, c, (32 * (v ^ 3) + lane) | (dep) | ((~(EA >> (4 * k4)) & p) << 8));
DEV void w_load(const CUtensorMap* mW, int cg, int h) {
  mbar_expect1(B_W + 8 * h, 24576);
  tma3(SM_S0 + (h & 3) * 24576, mW, 64 * cg, 64 * h, B_W + 8 * h);
}

DEV void conv(const Params& P, const CUtensorMap* mW, int c, int k4, int w, int layer) {
  const uint32_t zero = P.zero;
  PW(4 * k4 + w)
  int lane = lane_here(zero);
  const int g = lane >> 2, t = lane & 3, v = w ^ (ROT * (k4 & 1)), tid = 32 * v + lane;
  const uint32_t reg = SM_R + k4 * 16384, tp = SM_TAP + k4 * TAP_SZ;
  const uint32_t g0 = tp + ((g & 1) ? T_O : T_E) + 2 * (2 * t - g);
  uint32_t F[18][4], U[20], qc[4][4];
#define LO(q, a) q[0] = lds1(a); q[2] = lds1(a + 16);
#define HI(q, a) q[1] = lds1(a - 128); q[3] = lds1(a - 112);
  {
    const uint32_t ga = g0 - 32 * (w & 1) - 576 * (w >> 1), g2 = tp + T_C - 258 - 32 * w + 4 * (t - g);
    F[0][2] = lds1(ga + 48);
#pragma unroll
    for (int j = 0; j < 8; ++j) { F[j][0] = lds1(ga + 32 - 32 * j); F[j][1] = lds1(ga + 16 - 32 * j); }
#pragma unroll
    for (int j = 0; j < 20; ++j) U[j] = lds1(ga - 224 - 16 * j);
#pragma unroll
    for (int j = 0; j < 4; ++j) { LO(qc[j], g2 + 32 * j) HI(qc[j], g2 + 32 * j) }
  }
  if (layer) { mbar_wait(B_ED, 0); mbar_wait(B_ED + 8, 0); }
  sts4z_if(reg + lane * 16 + (w ? w * 3584 + 1024 : 0), w < 3);
  PROF(5, a_pre);
  if (k4 == 3 && w == 3) {
    mbar_wait(B_E, layer);
    mbar_wait(B_K, 0);
#pragma unroll
    for (int h = 0; h < 4; ++h) w_load(mW, c & 7, h);
  }
  mbar_wait(k4 && ((GMASK >> k4) & 1) ? B_G - 8 + 8 * k4 : B_E, layer);
  PROF(6, a_x);
  const uint32_t ua = reg + R_U + uoff(tid);
  uint4 x[2];
  uint32_t pv[4];
  {
    uint4 s[4];
#pragma unroll
    for (int z = 0; z < 2; ++z) x[z] = lds4(reg + R_B + tid * 16 + z * 2048);
#pragma unroll
    for (int z = 0; z < 4; ++z) s[z] = lds4(SM_RES + tid * 16 + (z >> 1) * 2048 + (z & 1) * 4096);
    for (int it = 0;; ++it) {
      uint32_t m = min(x[0].x, x[1].x);
#pragma unroll
      for (int z = 0; z < 4; ++z) m = min(m, min(s[z].x, s[z].z));
      if (m) break;
#pragma unroll
      for (int z = 0; z < 2; ++z) x[z] = ldr4(&P.S->XG[layer][(128 * k4 + c) * 256 + opq(tid) + z * 128]);
#pragma unroll
      for (int z = 0; z < 4; ++z) s[z] = ldr4(&P.S->SR[layer][c >> 4][opq(tid) + (z >> 1) * 128 + (z & 1) * 256]);
#pragma unroll
      for (int z = 0; z < 4; ++z) sts4(SM_RES + tid * 16 + (z >> 1) * 2048 + (z & 1) * 4096, s[z].x, s[z].y, s[z].z, s[z].w);
      spin_guard(it);
    }
    __syncwarp();
    uint32_t u[2][10];
#pragma unroll
    for (int z = 0; z < 2; ++z) {
      u[z][6] = hmul2(hsub2(x[z].x, s[2 * z].y), s[2 * z].x); u[z][7] = hmul2(hsub2(x[z].y, s[2 * z].w), s[2 * z].z);
      u[z][8] = hmul2(hsub2(x[z].z, s[2 * z + 1].y), s[2 * z + 1].x); u[z][9] = hmul2(hsub2(x[z].w, s[2 * z + 1].w), s[2 * z + 1].z);
      sts4(ua + z * 2048, u[z][6], u[z][7], u[z][8], u[z][9]);
    }
#pragma unroll
    for (int j = 0; j < 6; ++j) u[0][j] = __shfl_up_sync(0xffffffffu, u[0][j < 2 ? 8 + j : 4 + j], j < 2 ? 2 : 1);
    bar_sync(NB_WG + k4, 128);
    GATE(0)
    PROF(7, a_u);
    const uint32_t h1 = reg + R_U + v * 512 - 64;
    halo(u[0], h1, lane);
    if (v < 2) {
      u[1][0] = 0;
#pragma unroll
      for (int j = 1; j < 6; ++j) u[1][j] = __shfl_up_sync(0xffffffffu, u[1][j < 2 ? 8 + j : 4 + j], j < 2 ? 2 : 1);
      halo(u[1], h1 + 2048, lane);
      boxes<false>(u[1], reg + tid * 16 + 2048, 0, 0, pv);
    }
    const uint32_t bo = reg + R_B + tid * 16 + (v >> 1) * 1056;
    const uint32_t be = tid == 127 ? reg + R_B + 1024 : bo + (tid == 63 ? 2112 : 1056);
    boxes<true>(u[0], reg + tid * 16, (lane & 1) ? be : bo, (lane & 1) ? bo : be, pv);
    sts4z_if(reg + R_B + 1040, tid == 0);
  }
  GATE(1)
  fence_async_smem();
  if (k4 == 3 && w < 3) {
    const uint32_t src = SM_RES + 8192 + w * 2048, f = (w >> 1) - 1;
#pragma unroll
    for (int z = 0; z < 4; ++z) sts4(src + lane * 16 + z * 512, f, f, f, f);
    fence_async_smem();
    __syncwarp();
    if (w < 2) {
#pragma unroll
      for (int z = 0; z < 4; ++z) bulk_store(&P.S->O[((c >> 3) * 16 + w * 8 + (c & 7)) * 512] + z * 128, src, 2048);
    } else {
#pragma unroll
      for (int z = 0; z < 2; ++z) {
        bulk_store(&P.S->H[(c + 8) * 256] + z * 128, src, 2048);
        bulk_store(P.S->F + ((c >> 3) * 64 + 4 * (c & 7)) + z * 32, src, 16);
      }
      bulk_store(&P.S->PS[c * 64], src, 1024);
      bulk_store(&P.S->ST[c * 4], src, 64);
      if (c < 5) bulk_store(P.S->C + (c + 5 - 5 * layer) * 1024, src, 128 * NCOPY * NSUB);
    }
    asm volatile("cp.async.bulk.commit_group;" ::: "memory");
  }
  const uint32_t id = opq(0x3210u);
#pragma unroll
  for (int j = 0; j < 8; ++j) { F[j][3] = cpy(F[j][0], id); if (j) F[j][2] = cpy(F[j - 1][1], id); }
  PROF(8, a_box);
  bar_sync(NB_T + k4, k4 ? 256 : 128);
  PROF(9, a_turn);
  float acc[32], f1[24], f3[16];
  uint32_t qa[4][4], qb[4][4], fp[4];
  const uint64_t db = mkdesc(reg + R_U, 16, 512, 2) + 2;
#define STEP(mm) wg_fence(); mm; wg_commit(); wg_wait<2>();
#define D(j) STEP(wg_rs64k(acc, F[j], db - 2 * j, j))
#define C(j) STEP(wg_rs32t(f3, qc[j], mkdesc(reg + R_B, 128, 1040, 0) + 16 * j, j))
#define NIL(q) { const uint32_t z = here(zero); q[2][1] = cpy(z, 0); q[2][3] = cpy(z, 1); q[3][1] = cpy(z, 2); q[3][3] = cpy(z, 3); }
#define X(j) F[j][0] = cpy(U[2 * j - 16], ix); F[j][1] = cpy(U[2 * j - 15], ix); F[j][3] = cpy(F[j][0], ix); F[j][2] = cpy(F[j - 1][1], ix);
#define PIN ix = 0x3210u | here(zero);
  const uint32_t g1 = g0 - 2 * 576 - 16 * w;
  const uint64_t d1 = mkdesc(reg + R_A5, 128, 512, 0);
  constexpr int O3 = (R_A3 - R_A5) / 16;
  uint32_t ix;
  undef(acc);
  D(0) TURN(0) D(1) D(2) D(3) D(4) D(5)
  undef(f3);
  C(0) C(1) TURN(1) PIN X(8) X(9) C(2) C(3) LO(qa[0], g1)
  D(6) HI(qa[0], g1) PIN X(10) D(7) LO(qa[1], g1 + 32) X(11)
  fp[0] = pack2(f3[0], f3[1]); fp[1] = pack2(f3[4], f3[5]); fp[2] = pack2(f3[8] + f3[2], f3[9] + f3[3]); fp[3] = pack2(f3[12] + f3[6], f3[13] + f3[7]);
  D(8) HI(qa[1], g1 + 32) PIN ix |= fp[0] & fp[1] & fp[2] & fp[3] & zero; X(12) D(9) LO(qa[2], g1 - 64) X(13)
  D(10) TURN(2) LO(qa[3], g1 - 32) X(14) D(11) LO(qb[0], g1 - 192) PIN X(15) D(12) HI(qb[0], g1 - 192) X(16)
  D(13) LO(qb[1], g1 - 160) X(17) D(14) TURN(3) HI(qb[1], g1 - 160) NIL(qa)
  D(15) LO(qb[2], g1 - 256) D(16) LO(qb[3], g1 - 224) NIL(qb) D(17) TURN(4)
  PROF(10, a_den);
  undef(f1);
  wg_fence();
#pragma unroll
  for (int j = 0; j < 4; ++j) wg_rs48t(f1, qa[j], d1 + 16 * (j & 1) - 32 * (j >> 1), j);
  wg_commit();
  wg_wait<1>();
  TURN(5)
  wg_fence();
#pragma unroll
  for (int j = 0; j < 4; ++j) wg_rs48t(f1, qb[j], d1 + O3 + 16 * (j & 1) - 32 * (j >> 1), 1);
  wg_commit();
  TURN(6)
  asm volatile("cp.async.bulk.wait_group 0;" ::: "memory");
  uint32_t k1024 = lds16(tp + T_E - 2 * 639);
  lane = lane_here(zero);
  uint32_t yp[16];
#pragma unroll
  for (int z = 0; z < 16; ++z) yp[z] = pack2(acc[2 * z], acc[2 * z + 1]);
  const int p = (lane + 9 * (w >> 1)) & 31;
  const uint32_t ya = reg + ((w >> 1) ? R_B : R_U) + p * 64 + (((2 * (w & 1)) ^ ((p >> 1) & 3)) * 16);
  const uint32_t up = p < lane ? 2048 : 0;
  const uint32_t fa = reg + R_A5 + (lane >> 3) * 512 + w * 128 + (lane & 7) * 16;
  const uint32_t fc = reg + R_A3 + uoff(64 * (lane >> 4) + 16 * w + 2 * (lane & 7) + 1 - ((lane >> 3) & 1));
  wg_wait<0>();
  GATE(2)
  PROF(11, a_far);
  bar_sync(NB_WG + k4, 128);
#pragma unroll
  for (int z = 0; z < 4; ++z) {
    const uint32_t* a = yp + 8 * (z >> 1) + (z & 1);
    stsm4t((ya + (up ^ ((z >> 1) * 2048))) ^ ((z & 1) * 16), a[0], a[2], a[4], a[6]);
  }
  stsm4(fa, pack2(f1[0], f1[1]), pack2(f1[4], f1[5]), pack2(f1[8] + f1[2], f1[9] + f1[3]), pack2(f1[12] + f1[6], f1[13] + f1[7]));
  stsm2(fa + 2048, pack2(f1[16] + f1[10], f1[17] + f1[11]), pack2(f1[20] + f1[14], f1[21] + f1[15]));
  stsm4(fc, fp[0], fp[1], fp[2], fp[3]);
  bar_sync(NB_WG + k4, 128);
  TURN(7)
  PROF(12, a_sts);
  {
    const int o = 32 * v + lane;
    const uint32_t a = reg + uoff(o), b = reg + R_A5 + o * 16;
    uint4 y[2];
    y[0] = hadd8(lds4(a + R_U), hadd8(lds4(o >= 36 ? a + R_B : reg), lds4(v >= 2 ? b - 1024 : reg)));
    uint4 h = lds4(a + R_A3);
    k1024 = prmt(k1024, k1024, 0x1010);
    h = make_uint4(hfma2(pv[0], k1024, h.x), hfma2(pv[1], k1024, h.y), hfma2(pv[2], k1024, h.z), hfma2(pv[3], k1024, h.w));
    y[1] = hadd8(lds4(a + R_U + 2048), hadd8(lds4(a + R_B + 2048), hadd8(lds4(b + 1024), h)));
    const int e0 = (o >> 3) * 8192 + (128 * k4 + c) * 16 + (((o & 4) + ((o >> 1) & 1)) ^ (c & 7)) * 2 + (o & 1);
    if (TMASK(8)) bar_arrive_if(NB_T + 1 + k4 + (y[0].x & y[1].x & zero), 256, (TMASK(8) >> k4) & 1);
    ANN(2, y[0].x & y[1].x & zero)
    const uint32_t me = (e0 & 3) == ((c >> 1) & 3), m0 = me & ~c, m1 = me & c, tag = 1 - layer;
#pragma unroll
    for (int z = 0; z < 2; ++z) {
      const uint4 r = hadd8(x[z], y[z]);
      str2((uint2*)P.S->XF + e0 + z * 131072, tagged(prmt(r.x, r.y, 0x5410), m0, tag), tagged(prmt(r.z, r.w, 0x5410), m1, tag));
      str2((uint2*)P.S->XF + (e0 ^ 4) + z * 131072, tagged(prmt(r.x, r.y, 0x7632), m0, tag), tagged(prmt(r.z, r.w, 0x7632), m1, tag));
    }
  }
  ANN(1, 0)
  TURN(9)
  GATE(3)
  PROF(13, a_out);
}

#define WGATE 1
#define FH 1
#define QPIN 1
#define XORD 1
DEV void x_load(const Params& P, int c, int q, int layer) {
#pragma unroll
  for (int z = 0; z < 2; ++z) {
    const int e = z ^ (XORD && q == 3 && !(c & 4));
    mbar_expect1(B_X + 16 * q + 8 * e, 16384);
    bulk(xstage(q, e), P.S->XF + ((2 * (c >> 3) + 1 - e) * 4096 + q * 1024), 16384, B_X + 16 * q + 8 * e);
  }
}

DEV void means(uint32_t (&m)[4], int row, int lane, int layer, uint32_t zero) {
  mbar_wait(B_CS, 0);
  mbar_wait(B_ST, layer);
  const uint32_t a = SM_MISC + row * 4 + (lane & 28), k = (lane & 3) ? 0u : ~0u;
  m[0] = lds1(a) & k; m[1] = lds1(a + 32) & k; m[2] = m[0] & zero; m[3] = m[1] & zero;
}

DEV void attn_phase(const Params& P, int c, int e, int w, int lane, int layer) {
  PW(4 * e + w)
  const int cg = c & 7, J = 2 * (c >> 3) + 1 - e;
  float acc[96];
  zerov(acc);
  uint32_t m[4] = {0, 0, 0, 0};
#pragma unroll 1
  for (int q = 0;; ++q) {
    const uint64_t da = mkdesc(xstage(q, e), 16, 1024, 1), db = mkdesc(SM_S0 + (q & 1) * 49152, 8192, 1024, 1);
    const uint32_t wr = mbar_test2(B_W + 16 * q, layer), xa = xstage(q, e) + w * 4096 + lane * 132;
    mbar_wait(B_X + 16 * q + 8 * e, layer);
    for (int it = 0;; ++it) {
      const uint32_t ok = both(lds1(xa), lds1(xa ^ 32), layer) & both(lds1(xa ^ 64), lds1(xa ^ 96), layer);
      if (__all_sync(0xffffffffu, ok & 1)) break;
      EVENT(8 * layer + 2 * q + e);
#pragma unroll 1
      for (int j = 0; j < 8; ++j) cp16(xstage(q, e) + w * 4096 + j * 512 + lane * 16, P.S->XF + (J * 4096 + q * 1024 + w * 256 + j * 32 + lane));
      asm volatile("cp.async.wait_all;" ::: "memory");
      fence_async_smem();
      __syncwarp();
      spin_guard(it);
    }
    bool all = __all_sync(0xffffffffu, wr);
    if (q == 0 && e && w == 0) {
      bar_sync(NB_H, 256);
      cnt_wait(P, 2 + 5 * layer, c, lane);
      x_load(P, c, 1, layer);
      PROF(27, m_xi);
    }
    if (q == 3 && e) means(m, 16 * w, lane, layer, P.zero);
    if (!all) { mbar_wait(B_W + 16 * q, layer); all = mbar_test(B_W + 16 * q + 8, layer); }
    bar_sync(e ? NB_Q : q ? NB_T : NB_T + 4, 256);
    PROF(14 + q, m_q);
    wg_fence();
#pragma unroll
    for (int k = 0; k < 8; ++k) {
      if (k == 4) { wg_commit(); if (!all) mbar_wait(B_W + 16 * q + 8, layer); wg_fence(); }
      wg_ss192(acc, da + k * 128, db + (k >> 2) * 1536 + (k & 3) * 128, 1);
    }
    wg_commit();
    if (q == 3) break;
    bar_arrive(e ? NB_T : NB_Q, 256);
    if (FH) { wg_wait<1>(); mbar_arrive1_if(B_FH + 8 * q, e && q < 2); }
    wg_wait<0>();
    mbar_arrive1(B_F + 8 * q);
  }
  const int pos = 2 - 2 * e + (w >> 1);
  uint4* h = P.S->H + ((c + 8) * 256 + (w & 1) * 128 + lane);
  {
    if (!e) means(m, 64 + 16 * w, lane, layer, P.zero);
    PROF(28, m_sub);
    wg_fence();
    wg_rs192t(acc, m, mkdesc(SM_CS, 0, 32, 0));
    wg_commit();
    bar_arrive_if(NB_Q, 256, !e);
    keep(h, P.zero);
    wg_wait<0>();
    mbar_arrive1(B_F + 24);
  }
  PROF(18, m_qkv);
  lane = opq(lane);
  const int g = lane >> 2, t = lane & 3;
  uint32_t Q[4][4], K[4][3][2], V[4][3][2];
  const uint32_t ra = SM_STAT + 256 + (32 - 32 * e + 8 * w) * 16;
  float r0, r1;
  uint4 k0, k1, k2;
  {
#pragma unroll
    for (int z = 0; z < 4; ++z) {
      K[z][2][0] = nz(pack2(acc[34 + 8 * z], acc[35 + 8 * z])); K[z][2][1] = pack2(acc[38 + 8 * z], acc[39 + 8 * z]);
      V[z][2][0] = pack2(acc[66 + 8 * z], acc[67 + 8 * z]); V[z][2][1] = pack2(acc[70 + 8 * z], acc[71 + 8 * z]);
      str4_if(h + z * 32, K[z][2][0], K[z][2][1], V[z][2][0], V[z][2][1], pos == 3);
    }
    bar_arrive_if(NB_RL, 128, pos == 3);
#pragma unroll
    for (int z = 0; z < 8; ++z) {
      V[z >> 1][2][z & 1] = movm(V[z >> 1][2][z & 1]);
      K[z >> 1][1][z & 1] = pack2(acc[32 + 4 * z], acc[33 + 4 * z]);
      V[z >> 1][1][z & 1] = pack2(acc[64 + 4 * z], acc[65 + 4 * z]);
    }
    const uint32_t kv = (w & 1) * 2048 + lane * 16;
    if (pos < 3) {
      mbar_wait(B_F + 16 + 8 * e, layer);
#pragma unroll
      for (int z = 0; z < 4; ++z) sts4(kvslot(cg, pos + 1) + kv + z * 512, K[z][2][0], K[z][2][1], V[z][2][0], V[z][2][1]);
      bar_arrive(NB_H + pos + 1, 128);
    }
    r0 = lds1f(ra + (g >> 1) * 16 + (g & 1) * 4); r1 = lds1f(ra + 64 + (g >> 1) * 16 + (g & 1) * 4);
    k1 = lds4(ra + 16 * t); k2 = lds4(ra + 64 + 16 * t);
    PROF(19, m_kv);
    uint32_t pin = QPIN ? P.zero : 0;
#pragma unroll
    for (int z = 0; z < 8; ++z) {
      V[z >> 1][1][z & 1] = movm(V[z >> 1][1][z & 1]);
      Q[z >> 1][2 * (z & 1)] = pack2(acc[4 * z], acc[4 * z + 1]);
      Q[z >> 1][2 * (z & 1) + 1] = pack2(acc[4 * z + 2], acc[4 * z + 3]);
      if (QPIN) pin &= Q[z >> 1][2 * (z & 1)] & Q[z >> 1][2 * (z & 1) + 1];
    }
    mbar_wait(B_F + 24, layer);
    bar_sync(NB_H + pos + pin, pos ? 128 : 160);
    k0 = lds4(ra - 192 + 16 * t);
#pragma unroll
    for (int z = 0; z < 4; ++z) {
      const uint4 hv = lds4(kvslot(cg, pos) + kv + z * 512);
      K[z][0][0] = hv.x; K[z][0][1] = hv.y; V[z][0][0] = hv.z; V[z][0][1] = hv.w;
    }
  }
  PROF(20, m_halo);
  const uint32_t ob = e ? SM_S1 : SM_XA;
  {
    const bool p0 = 2 * t > g, p1 = 2 * t + 1 > g, first = c < 8 && pos == 0;
    const uint32_t M = (p0 ? 0xFFFFu : 0u) | (p1 ? 0xFFFF0000u : 0u);
    const float sc0 = r0 * (0.25f * 1.4426950408889634f), sc1 = r1 * (0.25f * 1.4426950408889634f);
    const float sk[4] = {__uint_as_float(p0 ? k0.x : k1.x) * sc0, __uint_as_float(p1 ? k0.y : k1.y) * sc0,
                         __uint_as_float(p0 ? k1.x : k2.x) * sc1, __uint_as_float(p1 ? k1.y : k2.y) * sc1};
    const uint32_t rm[4] = {k0.z & M, k1.z & ~M, k1.z & M, k2.z & ~M}, s0 = k0.w | P.zero, s1 = k1.w | P.zero;
    const int oo = cg * 512 + (2 * (w & 2) + (w & 1)) * 64 + (lane ^ (g >> 1));
    uint4* O = P.S->O + (J * 4096 + oo);
#pragma unroll
    for (int h2 = 0; h2 < 2; ++h2) {
      uint32_t A[2], B[2], mx[2];
#pragma unroll
      for (int z = 0; z < 2; ++z) {
        const int h = 2 * h2 + z;
        float S[3][4];
#pragma unroll
        for (int n = 0; n < 3; ++n) mma16z(S[n], Q[h][0], Q[h][1], Q[h][2], Q[h][3], K[h][n][0], K[h][n][1]);
        if (first) { S[0][0] = __uint_as_float(0xFF800000u); S[0][1] = S[0][0]; }
        A[z] = pack2((p0 ? S[0][0] : S[1][0]) * sk[0], (p0 ? S[1][2] : S[2][2]) * sk[2]);
        B[z] = pack2((p1 ? S[0][1] : S[1][1]) * sk[1], (p1 ? S[1][3] : S[2][3]) * sk[3]);
      }
#pragma unroll
      for (int z = 0; z < 2; ++z) mx[z] = hmax2(A[z], B[z]);
#pragma unroll
      for (int z = 0; z < 2; ++z) mx[z] = hmax2(mx[z], __shfl_xor_sync(0xffffffffu, mx[z], 1));
#pragma unroll
      for (int z = 0; z < 2; ++z) mx[z] = hmax2(mx[z], __shfl_xor_sync(0xffffffffu, mx[z], 2));
      float Oa[2][3][4];
#pragma unroll
      for (int z = 0; z < 2; ++z) {
        const int h = 2 * h2 + z;
        const uint32_t a = hsub2(A[z], mx[z]), b = hsub2(B[z], mx[z]);
        const uint32_t w0 = pack2(ex2(bflo(a)), ex2(bflo(b))), w1 = pack2(ex2(bfhi(a)), ex2(bfhi(b)));
        const uint32_t u0 = hmul2(w0, rm[0]), u1 = hmul2(w0, rm[1]), u2 = hmul2(w1, rm[2]), u3 = hmul2(w1, rm[3]);
        const uint32_t z0 = w0 & P.zero, z1 = w1 & P.zero;
        mma16z(Oa[z][2], u0, z0, u1, u2, s0, s1);
#pragma unroll
        for (int d = 0; d < 2; ++d) mma16z(Oa[z][d], u0, z0, u1, u2, V[h][0][d], V[h][1][d]);
        mma8(Oa[z][2], z1, u3, k2.w);
#pragma unroll
        for (int d = 0; d < 2; ++d) mma8(Oa[z][d], z1, u3, V[h][2][d]);
      }
#pragma unroll
      for (int r = 0; r < 4; r += 2) {
        const float i0 = rcp(Oa[0][2][r]), i1 = rcp(Oa[1][2][r]);
        const uint32_t o0 = pack2(Oa[0][0][r] * i0, Oa[0][0][r + 1] * i0), o1 = pack2(Oa[0][1][r] * i0, Oa[0][1][r + 1] * i0);
        const uint32_t o2 = pack2(Oa[1][0][r] * i1, Oa[1][0][r + 1] * i1), o3 = pack2(Oa[1][1][r] * i1, Oa[1][1][r + 1] * i1);
        str4(O + h2 * 32 + r * 64, o0, o1, o2, o3);
        sts4(ob + oo * 16 + h2 * 512 + r * 1024, o0, o1, o2, o3);
      }
    }
  }
  bar_arrive(NB_T + 1 + e, 160);
  fence_async_smem();
  PROF(21, m_att);
  uint32_t res[8][2];
  mbar_wait(B_RES, layer);
  {
    const uint32_t a = SM_RES + e * 8192 + (lane >> 4) * 1024 + (lane & 7) * 128 + (((2 * (w & 2) + ((lane >> 2) & 2) + (w & 1)) ^ (lane & 7)) * 16);
#pragma unroll
    for (int j = 0; j < 8; j += 2) ldsm4t(res[j][0], res[j][1], res[j + 1][0], res[j + 1][1], a + j * 1024);
  }
  PROF(26, m_res);
  if (WGATE) bar_sync(NB_T, 256); else bar_sync(NB_WG + e, 128);
  XgAddr xa = xg_addr<true>(P.S->XG[1] + (64 * cg * 256 + 8 * J), ob, w, lane, P.zero);
  uint4* ps = &P.S->PS[((4 * J + w) * 8 + cg) * 8 + g];
  keep(ps, P.zero);
  if (layer) {
    xa.a = ob + w * 2048 + (lane & 15) * 128 + (((lane >> 4) ^ (lane & 7)) * 16);
    xa.b = ob + w * 2048 + (lane >> 3) * 128 + (((lane & 7) ^ (lane >> 3)) * 16);
    xa.dst = (uint4*)P.out + ((64 * J + 16 * w + 2 * (lane >> 3)) * 64 + 8 * cg + (lane & 7));
  }
  uint32_t y[8][2];
#pragma unroll 1
  for (int it = 0;; ++it) {
    float ac[32];
    zerov(ac);
#pragma unroll 1
    for (int n = 0; n < 8; ++n) {
      const int s = n == 0 ? cg : n - (n <= cg);
      mbar_wait(n ? B_O + 64 * e + 8 * s : B_WO, layer);
      if (n == 1) PROF(22, m_o1);
      if (n == 7) PROF(23, m_o7);
      const uint64_t da = mkdesc(ob + s * 8192, 16, 1024, 2), db = mkdesc(SM_R + s * 8192, 16, 1024, 1);
      wg_fence();
#pragma unroll
      for (int k = 0; k < 4; ++k) wg_ss64(ac, da + (k >> 1) * 32 + (k & 1) * 2, db + k * 128, 1);
      wg_commit();
    }
    wg_wait<0>();
    const bool bad = ac[0] != ac[0] || ac[2] != ac[2];
#pragma unroll
    for (int j = 0; j < 8; ++j) {
      y[j][0] = hadd2(res[j][0], pack2(ac[4 * j], ac[4 * j + 1]));
      y[j][1] = hadd2(res[j][1], pack2(ac[4 * j + 2], ac[4 * j + 3]));
    }
    if (!bar_any(NB_WG + e, 128, bad) || it == 16) break;
    EVENT(24 + 2 * layer + e);
    refetch(ob, P.S->O + J * 4096, 32768, e, w);
  }
  PROF(24, m_wo);
  if (layer == 0) {
    const float4 s = gram(y, g, P.zero);
    xg_put<true>(xa, y);
    str4_if(ps, nz(__float_as_uint(s.x)), __float_as_uint(s.y), __float_as_uint(s.z), __float_as_uint(s.w), t == (g >> 1));
    mbar_arrive1(B_ED + 8 * e);
    bar_sync(NB_WG + e, 128);
    xg_store(xa);
    bar_arrive(NB_T + 3, 288);
  } else {
#pragma unroll
    for (int j = 0; j < 8; j += 2) stsm4(xa.a ^ (j * 16), y[j][0], y[j][1], y[j + 1][0], y[j + 1][1]);
    __syncwarp();
#pragma unroll
    for (int k = 0; k < 4; ++k) {
      const uint4 v = lds4((xa.b ^ ((k & 1) * 64)) + k * 512);
      stw4(xa.dst + ((k & 1) * 8 + (k >> 1)) * 64, v.x, v.y, v.z, v.w);
    }
  }
  PROF(25, m_epi);
}

#define HDELAY 300
#define ODELAY 200
#define PDELAY 0
#define FDELAY 200
#define CSP 0
#define CSU 4
#define PHOLD 0
#define XDEL 300
#define WOQ 2
#define H5 1
#define SRDELAY 300
#define ZPACE 20

DEV void o_load(const Params& P, int c, int e, int lane, int layer) {
  PW(8 + e)
  const int J = 2 * (c >> 3) + 1 - e;
#pragma unroll 1
  for (int s = 0; s < 8; ++s) mbar_expect1(B_O + 64 * e + 8 * s, s == (c & 7) ? 0 : 8192);
  bar_sync(NB_T + 1 + e, 160);
  flag_set1(P.S->F + (J * 32 + 4 * (c & 7)));
  if (ODELAY) delay(ODELAY);
  PROF(26, a_go);
  poll(P.S->F + (J * 32 + (lane & 28)), 1);
  PROF(25, h_seen);
  bar_sync_if(NB_Q, 64, e);
#pragma unroll 1
  for (int s = 0; s < 8; ++s)
    if (s != (c & 7)) bulk((e ? SM_S1 : SM_XA) + s * 8192, P.S->O + (J * 4096 + s * 512), 8192, B_O + 64 * e + 8 * s);
  bar_arrive_if(NB_Q, 64, !e);
  PROF(28, a_o);
}

DEV void stats(const Params& P, int c, int w, int lane, int layer) {
  PW(12 + w)
  lane = opq(lane);
  const int r = (lane & 6) + ((lane >> 3) & 1), k = (2 * (c & 3) + (lane & 1)) ^ r, e = 1 - ((c >> 2) & 1);
  const uint32_t o = (32 * w + 8 * (lane >> 4) + r) * 128 + k * 16;
  const uint32_t mk = ((k & 1) == (r >> 2)) << (r & 3), tag = 1 - layer;
  float v[16];
#pragma unroll
  for (int z = 0; z < 16; ++z) v[z] = 0.f;
#pragma unroll 1
  for (int q = 0; q < 4; ++q) {
    mbar_wait(B_X + 16 * q + 8 * e, layer);
    PROF(19 + q, s_l);
    uint4 x, y;
    for (int it = 0;; ++it) {
      x = lds4v(xstage(q, e) + o); y = lds4v(xstage(q, e) + o + 2048);
      const uint32_t bad = (((x.x ^ tag) | (y.x ^ tag)) & mk) | (((x.y ^ tag) | (y.y ^ tag)) & (mk >> 1)) |
                           (((x.z ^ tag) | (y.z ^ tag)) & (mk >> 2)) | (((x.w ^ tag) | (y.w ^ tag)) & (mk >> 3));
      if (!__any_sync(0xffffffffu, bad & 1)) break;
      spin_guard(it);
    }
    mbar_arrive1(B_F + 8 * q);
    const uint32_t ws[8] = {x.x, x.y, x.z, x.w, y.x, y.y, y.z, y.w};
#pragma unroll
    for (int z = 0; z < 8; ++z) {
      const float lo = bflo(ws[z]), hi = bfhi(ws[z]);
      float* u = v + 4 * (z & 3);
      u[0] += lo; u[1] += lo * lo; u[2] += hi; u[3] += hi * hi;
    }
  }
  PROFD(14, s_part, __float_as_uint(v[0]));
  fold<8>(v, lane, 16); fold<4>(v, lane, 8); fold<2>(v, lane, 4); fold<1>(v, lane, 2);
  PROFD(16, s_fold, __float_as_uint(v[0]));
  if (w) {
    sts1(SM_MISC - 128 + w * 128 + lane * 4, __float_as_uint(v[0]));
    bar_arrive(NB_P, 128);
  } else {
    bar_sync(NB_P, 128);
    v[0] += lds1f(SM_MISC + lane * 4) + lds1f(SM_MISC + 128 + lane * 4) + lds1f(SM_MISC + 256 + lane * 4);
    float m;
    const float sd = ln_sd(v[0], __shfl_xor_sync(0xffffffffu, v[0], 2), m);
    if (!(lane & 2)) str1((uint32_t*)P.S->ST + (16 * c + 8 * (lane & 1) + (lane >> 2)), pack2(m, sd));
    sts4(SM_STAT - 32 + min(lane, 17) * 16, 0x3F800000u, 0x3F800000u, 0x3F803F80u, 0x3F803F80u);
    fence_async_smem();
    PROF(17, s_pub);
    uint4 s;
    for (int it = 0;; ++it) {
      s = ldr4(P.S->ST + ((c >> 3) * 32 + lane));
      if (__all_sync(0xffffffffu, min4(s) != 0u)) break;
      spin_guard(it);
    }
    PROF(18, s_seen);
    const float r0 = rcp(bfhi(s.x)), r1 = rcp(bfhi(s.y)), r2 = rcp(bfhi(s.z)), r3 = rcp(bfhi(s.w));
    const uint32_t sg = 0x80008000u;
    sts4(SM_MISC + lane * 16, prmt(s.x, s.x, 0x1010) ^ sg, prmt(s.y, s.y, 0x1010) ^ sg, prmt(s.z, s.z, 0x1010) ^ sg, prmt(s.w, s.w, 0x1010) ^ sg);
    sts4(SM_STAT + 256 + lane * 32, __float_as_uint(r0), __float_as_uint(r1), pack2(r0, r1), prmt(s.x, s.y, 0x7632));
    sts4(SM_STAT + 272 + lane * 32, __float_as_uint(r2), __float_as_uint(r3), pack2(r2, r3), prmt(s.z, s.w, 0x7632));
    __syncwarp();
    mbar_arrive1(B_ST);
  }
  PROF(15, s_stat);
  if (w == 1) {
    mbar_wait(B_ST, layer);
    if (c >= 8) {
      uint2 s;
      for (int it = 0;; ++it) {
        s = ldr2((const uint2*)P.S->ST + ((c >> 3) * 64 - 12 + (lane & 11)));
        if (__all_sync(0xffffffffu, min(s.x, s.y) != 0u)) break;
        spin_guard(it);
      }
      const float r0 = rcp(bfhi(s.x)), r1 = rcp(bfhi(s.y));
      sts4(SM_STAT + 64 + (lane & 11) * 16, __float_as_uint(r0), __float_as_uint(r1), pack2(r0, r1), prmt(s.x, s.y, 0x7632));
    }
    bar_arrive(NB_H, 160);
  }
  if (w >= 2) {
    const uint4* h = P.S->H + (c * 256 + (w & 1) * 128 + lane);
    uint4 hv[4];
#pragma unroll
    for (int z = 0; z < 4; ++z) hv[z] = make_uint4(0, 0, 0, 0);
    bar_sync(NB_RL, 128);
    PROFD(26, s_hb, lds1v(SM_MISC));
    delay(HDELAY);
    for (int it = 0; c >= 8; ++it) {
#pragma unroll
      for (int z = 0; z < 4; ++z) hv[z] = ldr4(h + z * 32);
      if (__all_sync(0xffffffffu, min(min(hv[0].x, hv[1].x), min(hv[2].x, hv[3].x)) != 0u)) break;
      spin_guard(it);
    }
    mbar_wait(B_F + 24, layer);
#pragma unroll
    for (int z = 0; z < 4; ++z) sts4(kvslot(c & 7, 0) + (w & 1) * 2048 + lane * 16 + z * 512, hv[z].x, hv[z].y, movm(hv[z].z), movm(hv[z].w));
    bar_arrive(NB_H, 160);
    PROF(25, s_halo);
  }
}

DEV void finalize(const Params& P, int c, int lane, int layer) {
  PW(12)
  float z[4];
  if (layer == 0) {
    bar_sync(NB_P, 256);
    z[0] = z[1] = z[2] = z[3] = 0.f;
#pragma unroll
    for (int k = 0; k < 2; ++k) { const float4 a = lds4f(SM_RES + 8192 + k * 512 + lane * 16); z[0] += a.x; z[1] += a.y; z[2] += a.z; z[3] += a.w; }
  } else {
    mbar_wait(B_ED + 8 - 2 * (c & 4), 0);
    if (FDELAY) delay(FDELAY);
    const uint4* ps = &P.S->PS[c * 64 + lane];
    uint4 a, b;
    for (int it = 0;; ++it) {
      a = ldr4(ps); b = ldr4(ps + 32);
      if (__all_sync(0xffffffffu, min(a.x, b.x) != 0u)) break;
      spin_guard(it);
    }
    z[0] = __uint_as_float(a.x) + __uint_as_float(b.x); z[1] = __uint_as_float(a.y) + __uint_as_float(b.y);
    z[2] = __uint_as_float(a.z) + __uint_as_float(b.z); z[3] = __uint_as_float(a.w) + __uint_as_float(b.w);
  }
#pragma unroll
  for (int o = 8; o < 32; o <<= 1)
#pragma unroll
    for (int k = 0; k < 4; ++k) z[k] += __shfl_xor_sync(0xffffffffu, z[k], o);
  float m0, m1;
  const float r0 = rcp(ln_sd(z[0], z[1], m0)), r1 = rcp(ln_sd(z[2], z[3], m1));
  const uint32_t wr = nz(pack2(r0, r1)), wm = pack2(m0, m1);
  uint2* so = (uint2*)P.S->SR[layer] + ((lane >> 3) * 1024 + (lane & 2) * 256 + 4 * c + ((lane >> 1) & 2) + (lane & 1));
  str2(so, wr, wm); str2(so + 4096, wr, wm);
  bar_arrive_if(NB_Q, 448, !layer);
  PROF(23, s_sr);
}

DEV void announce(const Params& P, int c, int lane, int layer) {
  PW(13)
  bar_sync(NB_T + 3, layer ? 288 : 160);
  cnt_add(P, 5 * layer, c, lane);
  bar_sync_if(NB_Q, 448, !layer);
  fence_async_smem();
  PROF(24, s_own);
}

DEV void fetch(const Params& P, int c, int lane, int layer) {
  PW(13)
  mbar_expect1(B_E, 24576);
  cnt_wait(P, 5 * layer, c, lane);
#pragma unroll
  for (int k = 0; k < 4; ++k) bulk(SM_R + k * 16384 + R_B, P.S->XG[layer] + (128 * k + c) * 256, 4096, B_E);
  if (layer) delay(SRDELAY);
  bulk(SM_RES, P.S->SR[layer][c >> 4], 8192, B_E);
  if (!layer) { if (!CSP) l2_prefetch(P.wqkv + c * 6144, 12288); l2_prefetch(P.wo + c * 2048, 4096); }
  if (PHOLD) mbar_arrive1_if(B_ST + 8, !layer);
  PROF(25, s_all);
}

DEV void cs_part(const Params& P, int c, int w, int lane, int layer) {
  float cs[8];
#pragma unroll
  for (int k = 0; k < 8; ++k) cs[k] = 0.f;
  const int col = w * 512 + 64 * (c & 7) + 8 * (lane & 7);
#pragma unroll 1
  for (int r = 8 * layer; r < 8; r += CSU) {
    uint4 v[CSU];
#pragma unroll
    for (int k = 0; k < CSU; ++k) v[k] = ldnc4(P.wqkv + ((32 * (c >> 3) + 4 * r + (lane >> 3)) * 1536 + col) + 4 * k * 1536);
#pragma unroll
    for (int k = 0; k < CSU; ++k) {
      cs[0] += bflo(v[k].x); cs[1] += bfhi(v[k].x); cs[2] += bflo(v[k].y); cs[3] += bfhi(v[k].y);
      cs[4] += bflo(v[k].z); cs[5] += bfhi(v[k].z); cs[6] += bflo(v[k].w); cs[7] += bfhi(v[k].w);
    }
  }
  fold<4>(cs, lane, 16); fold<2>(cs, lane, 8);
  str2((float*)P.S->CS + ((c >> 3) * 1536 + col + 2 * (lane >> 3)), max(__float_as_uint(cs[0]), 1u - layer), __float_as_uint(cs[1]));
}

DEV void cs_sum(const Params& P, int c, int w, int lane) {
  float a, b;
  for (int it = 0;; ++it) {
    uint32_t m = ~0u;
    a = b = 0.f;
#pragma unroll
    for (int k = 0; k < 16; ++k) {
      const uint2 u = ldr2((const float*)P.S->CS + (w * 512 + 64 * (c & 7) + 2 * lane) + k * 1536);
      a += __uint_as_float(u.x); b += __uint_as_float(u.y); m = min(m, u.x);
    }
    if (__all_sync(0xffffffffu, m != 0u)) break;
    spin_guard(it);
  }
  const uint32_t hi = pack2(a, b), ad = SM_CS + w * 256 + (lane >> 2) * 32 + (lane & 3) * 4;
  sts1(ad, hi); sts1(ad + 16, pack2(a - bflo(hi), b - bfhi(hi)));
  fence_async_smem();
  __syncwarp();
  mbar_arrive1(B_CS);
}

DEV void x0_get(uint32_t (&x)[8][2], uint32_t a) {
  asm volatile("cp.async.wait_group 0;" ::: "memory");
#pragma unroll
  for (int z = 0; z < 4; ++z) {
    const uint4 v = lds4(a + z * 512);
    x[2 * (z & 2)][z & 1] = v.x; x[2 * (z & 2) + 1][z & 1] = v.y; x[2 * (z & 2) + 2][z & 1] = v.z; x[2 * (z & 2) + 3][z & 1] = v.w;
  }
}

DEV void par_load(const Params& P, int ch, int m, uint32_t (&pv)[8]) {
  const int mo = ch * 128 + m;
  pv[0] = ldnc16(P.Are + mo); pv[1] = ldnc16(P.Aim + mo); pv[2] = ldnc16(P.Bre + mo); pv[3] = ldnc16(P.Bim + mo);
  pv[4] = ldnc16(P.Cre + mo); pv[5] = ldnc16(P.Cim + mo); pv[6] = ldnc16(P.logdt + ch); pv[7] = ldnc16(P.dskip + ch);
}

__global__ void __launch_bounds__(NTHR, 1)
fused_kernel(const __grid_constant__ Params P, const __grid_constant__ CUtensorMap mapW,
             const __grid_constant__ CUtensorMap mapWo) {
  extern __shared__ __align__(1024) uint8_t smem_raw[];
  if (s2u(smem_raw) != SB) __trap();
  const int warp0 = __shfl_sync(0xffffffffu, threadIdx.x >> 5, 0), lane0 = threadIdx.x & 31;
  uint32_t smid; asm volatile("mov.u32 %0,%%smid;" : "=r"(smid));
  const int c = __shfl_sync(0xffffffffu, P.by_sm ? P.role[smid] : blockIdx.x, 0);
  if (c == 255) {
    if (threadIdx.x < NCOPY * NSUB)
#pragma unroll 1
      for (int it = 0; it < 256 && ldr1(P.S->C + 32 * threadIdx.x) < 128 / NSUB; ++it) __nanosleep(200);
    return;
  }
  const int cg = c & 7;
  PW(warp0)
  uint32_t dskip;
  {
    [[maybe_unused]] const int layer = 0;
    const int lane = lane0, g = lane >> 2, t = lane & 3, warp = warp0, k4 = warp >> 2, w = warp & 3;
    uint32_t pv[8];
    if (k4 < 3) par_load(P, 128 * k4 + c, 32 * w + lane, pv);
    else {
#pragma unroll
      for (int n = 0; n < 8; ++n) pv[n] = 0;
    }
    __syncthreads();
    if (XDEL) delay(XDEL);
    const uint16_t* r = P.x0 + ((k4 < 2 ? 8192 * c + 64 * warp : (128 * (c >> 3) + 16 * w) * 512 + 64 * cg) + 1024 * g + 8 * t);
    const uint32_t xa = SM_R + k4 * 16384 + w * 2048 + lane * 16;
    if (k4 != 2) {
#pragma unroll
      for (int z = 0; z < 4; ++z) cp16(xa + z * 512, r + (z & 1) * 512 + (z & 2) * 16);
    }
    sts4(SM_TAP + k4 * TAP_SZ + (32 * w + lane) * 16, 0, 0, 0, 0);
    sts4z_if(SM_TAP + k4 * TAP_SZ + 2048 + (32 * w + lane) * 16, w < 3);
    uint32_t x[8][2];
    if (k4 == 3) {
#pragma unroll
      for (int z = 0; z < 4; ++z) cp16(xa - 16384 + z * 512, r + 32768 + (z & 1) * 512 + (z & 2) * 16);
      asm volatile("cp.async.commit_group;" ::: "memory");
      if (threadIdx.x == 448) {
        asm volatile("prefetch.tensormap [%0];" :: "l"(&mapW) : "memory");
        asm volatile("prefetch.tensormap [%0];" :: "l"(&mapWo) : "memory");
      }
      __syncwarp();
      if (PDELAY) delay(PDELAY);
      par_load(P, 128 * k4 + c, 32 * w + lane, pv);
      XgAddr xd = xg_addr<false>(P.S->XG[0] + (64 * cg * 256 + 16 * (c >> 3)), SM_R + 3 * 16384 + 8192, w, lane, P.zero);
      x0_get(x, xa);
      PROF(27, a_ld);
      xg_put<false>(xd, x);
      x0_get(x, xa - 16384);
      xd.a -= 16384;
      xg_put<false>(xd, x);
      bar_sync(NB_WG + 3, 128);
      xg_store(xd);
      xd.b -= 16384; xd.dst += 8;
      xg_store(xd);
      bar_arrive(NB_T + 3, 160);
      bar_sync(NB_Q, 448);
    } else asm volatile("cp.async.commit_group;" ::: "memory");
    tables(pv, k4, w, lane);
    if (k4 < 2) {
      x0_get(x, xa);
      const float4 s = gram(x, g, P.zero);
      if (t == (g >> 1)) sts4f(SM_RES + 8192 + (warp * 8 + g) * 16, s.x, s.y, s.z, s.w);
      __syncwarp();
      bar_arrive_if(NB_P, 256, warp != 7);
    }
    if (k4 == 2) {
#pragma unroll
      for (int n = 0; n < 14; ++n) mbar_init1(SM_BAR + (n < 10 ? w * 80 : 240 + w * 32) + n * 8, n < 10 ? 1 : (CNT >> (8 * w + 2 * (n - 10 & 2))) & 15);
    }
    dskip = pv[7];
    PROF(1, a_x0);
  }
#pragma unroll 1
  for (int layer = 0; layer < 2; ++layer) {
    int lane = lane_here(P.zero);
    const int warp = warp0 | (layer & P.zero), k4 = warp >> 2, w = warp & 3;
    if (warp == (layer ? 12 : 7)) finalize(P, c, lane, layer);
    if (warp == (layer ? 13 : 6)) { announce(P, c, lane, layer); fetch(P, c, lane, layer); }
    if (layer == 0) {
      if (CSP && k4 == 1 && w != 2) { if (CSP > 1) delay(CSP); cs_part(P, c, w - (w >> 1), lane, 0); }
      taps(dskip, k4, w, lane);
    }
    if (!layer && ((PHOLD >> k4) & 1)) mbar_wait(B_ST + 8, 0);
    conv(P, &mapW, c, k4, w, layer);
    lane = lane_here(P.zero);
    if (k4 < 2) {
      bar_arrive_if(NB_H, 256, warp != 4);
      if (warp == 0) {
        mbar_wait(B_K, 0);
        cnt_wait(P, 1 + 5 * layer, c, lane);
        x_load(P, c, 0, layer);
        PROF(27, m_xi);
      } else if (k4 == 0 && (CSP == 0 || layer)) cs_part(P, c, w - 1, lane, CSP ? 1 : layer);
      attn_phase(P, c, k4, w, lane, layer);
    } else {
      bar_arrive_if(NB_RL, 256, warp >= 10);
      if (k4 == 3) {
        stats(P, c, w, lane, layer);
      } else if (w < 2) {
        bar_sync_if(NB_RL, 256, w);
        cnt_wait(P, 3 + 5 * layer + w, c, lane);
        bar_sync_if(NB_RL, 256, !w);
        if (w) mbar_wait(B_F, layer);
        x_load(P, c, 2 + w, layer);
        if (H5 && w) w_load(&mapW, cg, 5);
        PROF(14, h_xi);
        if (w == 1) str4(&P.S->SR[layer][lane >> 2][4 * c + (lane & 3)], 0, 0, 0, 0);
      } else if (w == 2) {
        mbar_expect1(B_WO, 65536);
        mbar_expect1(B_RES, 16384);
#pragma unroll 1
        for (int q = 0; q < 4; ++q) {
          if (FH && q < 2) { mbar_wait(B_FH + 8 * q, layer); w_load(&mapW, cg, 4 + 2 * q); }
          mbar_wait(B_F + 8 * q, layer);
          if (!FH && q < 2) w_load(&mapW, cg, 4 + 2 * q);
          if (q == 1 || (q == 0 && !H5)) w_load(&mapW, cg, 5 + 2 * q);
          if (WOQ == 0 && ((q + 1) & 2)) tma5(SM_R + (q & 2) * 16384, &mapWo, 64 * cg, 4 * (q & 2), B_WO);
          if (WOQ && q == 2) {
            if (WOQ >= 2) mbar_wait(B_ST, layer);
            tma5(SM_R, &mapWo, 64 * cg, 0, B_WO);
            if (WOQ < 3) tma5(SM_R + 32768, &mapWo, 64 * cg, 8, B_WO);
          }
          if (q == 3) {
#pragma unroll
            for (int e = 0; e < 2; ++e) bulk(SM_RES + e * 8192, P.S->XF + ((2 * (c >> 3) + 1 - e) * 4096 + cg * 512), 8192, B_RES);
          }
          PROF(15 + q, h_w);
        }
      }
      if (k4 == 2 && w != 2) {
        if (layer == 0) cs_sum(P, c, w - (w >> 1), lane);
        if (w == 3) {
          uint4* xz = P.S->XG[layer] + (c * 256 + lane);
          mbar_wait(B_F, layer);
#pragma unroll 1
          for (int k = 0; k < 32; ++k) {
            str4(xz + ((k >> 3) * 32768 + (k & 7) * 32), 0, 0, 0, 0);
            if (ZPACE) __nanosleep(ZPACE);
          }
          PROF(19, h_z);
        }
      }
      if (warp < 10) o_load(P, c, w, lane, layer);
    }
    asm volatile("mov.b32 %0,0;" : "=r"(dskip));
  }
}

typedef CUresult (*EncodeFn)(CUtensorMap*, CUtensorMapDataType, cuuint32_t, void*, const cuuint64_t*, const cuuint64_t*,
                             const cuuint32_t*, const cuuint32_t*, CUtensorMapInterleave, CUtensorMapSwizzle,
                             CUtensorMapL2promotion, CUtensorMapFloatOOBfill);

#define POOL 0
#define GOFF 0
static int place_roles(uint8_t* role) {
  int dev = 0, nsm = 0;
  cudaGetDevice(&dev);
  cudaDeviceGetAttribute(&nsm, cudaDevAttrMultiProcessorCount, dev);
  if (nsm < 128 || nsm > 144 || (nsm & 1)) return 0;
  cudaFuncSetAttribute(fused_kernel, cudaFuncAttributeNonPortableClusterSizeAllowed, 1);
  int occ[9] = {0};
  for (int k = 2; k <= 8; ++k) {
    cudaLaunchConfig_t cfg = {};
    cudaLaunchAttribute at[1];
    at[0].id = cudaLaunchAttributeClusterDimension;
    at[0].val.clusterDim.x = 2 * k; at[0].val.clusterDim.y = 1; at[0].val.clusterDim.z = 1;
    cfg.gridDim = dim3(2 * k); cfg.blockDim = dim3(NTHR); cfg.dynamicSmemBytes = SM_TOTAL; cfg.attrs = at; cfg.numAttrs = 1;
    if (cudaOccupancyMaxActiveClusters(&occ[k], fused_kernel, &cfg) != cudaSuccess) { cudaGetLastError(); occ[k] = 0; }
  }
  int n[10];
  n[7] = occ[8]; n[6] = occ[7]; n[5] = occ[6] - 0; n[4] = occ[5];
  n[3] = occ[4] - n[7]; n[1] = occ[2] - n[3] - n[5] - n[7]; n[0] = n[2] = n[1];
  n[8] = occ[3] - n[2] - n[5];
  const int ntpc = nsm / 2;
  int sum = 0;
  bool ok = n[0] > 0 && n[0] <= 8;
  for (int r = 0; r < 9; ++r) { ok = ok && n[r] >= 0 && (r == 0 || n[r] <= n[r - 1]); sum += n[r]; }
  if (!ok || sum > ntpc) { for (int r = 0; r < 9; ++r) n[r] = r < 8 ? 8 : 0; sum = 64; }
  int tp[8][9], cnt[8] = {0}, pool[72], np = 0, id = 0;
  for (int r = 0; r < 9; ++r)
    for (int g = n[0] - n[r]; g < n[0]; ++g) tp[g][cnt[g]++] = id++;
  for (; id < ntpc; ++id) pool[np++] = id;
  int order[72], no = 0;
  for (int g = 0; g < n[0]; ++g) {
    const int full = cnt[g] / 4 * 4;
    for (int k = 0; k < cnt[g]; ++k) { if (k < full) order[no++] = tp[g][k]; else pool[np++] = tp[g][k]; }
  }
  for (int k = 0; k < np; ++k) order[no++] = pool[POOL == 1 ? np - 1 - k : POOL == 2 ? (k + np - 2) % np : k];
  for (int k = 0; k < 144; ++k) role[k] = 255;
  for (int k = 0; k < 64; ++k) { role[2 * order[k]] = (2 * k + GOFF) & 127; role[2 * order[k] + 1] = (2 * k + 1 + GOFF) & 127; }
  return nsm;
}

extern "C" void kernel_launch(void* const* d_in, const int* in_sizes, int n_in, void* d_out, int out_size) {
  (void)in_sizes; (void)n_in; (void)out_size;
  static EncodeFn enc = nullptr;
  static uint8_t role[144];
  static int nsm = 0;
  static void* scratch = nullptr;
  if (!enc) {
    void* fn = nullptr;
    cudaDriverEntryPointQueryResult qr;
    cudaGetDriverEntryPoint("cuTensorMapEncodeTiled", &fn, cudaEnableDefault, &qr);
    enc = (EncodeFn)fn;
    cudaFuncSetAttribute(fused_kernel, cudaFuncAttributeMaxDynamicSharedMemorySize, SM_TOTAL);
    nsm = place_roles(role);
    cudaGetSymbolAddress(&scratch, g_S);
  }
  CUtensorMap mW, mWo;
  {
    cuuint64_t dim[3] = {512, 512, 3}, str[2] = {3072, 1024};
    cuuint32_t box[3] = {64, 64, 3}, es[3] = {1, 1, 1};
    enc(&mW, CU_TENSOR_MAP_DATA_TYPE_BFLOAT16, 3, d_in[10], dim, str, box, es, CU_TENSOR_MAP_INTERLEAVE_NONE,
        CU_TENSOR_MAP_SWIZZLE_128B, CU_TENSOR_MAP_L2_PROMOTION_NONE, CU_TENSOR_MAP_FLOAT_OOB_FILL_NONE);
  }
  {
    cuuint64_t dim[5] = {512, 2, 4, 4, 16}, str[4] = {1024, 8192, 2048, 32768};
    cuuint32_t box[5] = {64, 2, 4, 4, 8}, es[5] = {1, 1, 1, 1, 1};
    enc(&mWo, CU_TENSOR_MAP_DATA_TYPE_BFLOAT16, 5, d_in[11], dim, str, box, es, CU_TENSOR_MAP_INTERLEAVE_NONE,
        CU_TENSOR_MAP_SWIZZLE_128B, CU_TENSOR_MAP_L2_PROMOTION_NONE, CU_TENSOR_MAP_FLOAT_OOB_FILL_NONE);
  }
  Params P;
  P.x0 = (const uint16_t*)d_in[0]; P.Are = (const uint16_t*)d_in[1]; P.Aim = (const uint16_t*)d_in[2];
  P.Bre = (const uint16_t*)d_in[3]; P.Bim = (const uint16_t*)d_in[4]; P.Cre = (const uint16_t*)d_in[5];
  P.Cim = (const uint16_t*)d_in[6]; P.logdt = (const uint16_t*)d_in[7]; P.dskip = (const uint16_t*)d_in[8];
  P.wqkv = (const uint16_t*)d_in[10]; P.wo = (const uint16_t*)d_in[11]; P.out = (uint16_t*)d_out;
  for (int k = 0; k < 144; ++k) P.role[k] = role[k];
  P.by_sm = nsm > 0;
  P.zero = 0;
  P.S = (Scratch*)scratch;
  fused_kernel<<<nsm > 0 ? nsm : 128, NTHR, SM_TOTAL, cudaStreamPerThread>>>(P, mW, mWo);
}
```

```cpp
#include <cuda_runtime.h>
#include <cuda_bf16.h>
#include <cuda.h>
#include <stdint.h>

#define DEV __device__ __forceinline__

#define NCOPY 4
#define NSUB 1
constexpr int NTHR = 512;
constexpr int SPIN_LIMIT = 1 << 22;

constexpr uint32_t SB = 1024;
constexpr uint32_t SM_XA   = SB;
constexpr uint32_t SM_S0   = SM_XA + 16384;
constexpr uint32_t SM_S1   = SM_S0 + 49152;
constexpr uint32_t SM_XB   = SM_S1 + 49152;
constexpr uint32_t SM_R    = SM_XB + 16384;
constexpr uint32_t SM_RES  = SM_R + 65536;
constexpr uint32_t SM_TAP  = SM_RES + 16384;
constexpr int TAP_SZ = 3584;
constexpr uint32_t SM_CS   = SM_TAP + 4 * TAP_SZ;
constexpr uint32_t SM_STAT = SM_CS + 800;
constexpr uint32_t SM_MISC = SM_STAT + 1280;
constexpr uint32_t SM_BAR  = SM_MISC + 512;
constexpr int SM_TOTAL = SM_BAR + 448 - SB;
constexpr int R_U = 512, R_A5 = 5120, R_A3 = 8704, R_B = 11776;
constexpr int T_E = 1536, T_O = T_E + 1602, T_C = 3714;
constexpr uint32_t B_W = SM_BAR, B_X = SM_BAR + 64, B_O = SM_BAR + 128, B_WO = SM_BAR + 256, B_RES = SM_BAR + 264;
constexpr uint32_t B_ST = SM_BAR + 272, B_R = SM_BAR + 288, B_E = SM_BAR + 304;
constexpr uint32_t B_F = SM_BAR + 320, B_G = SM_BAR + 352, B_K = SM_BAR + 376, B_ED = SM_BAR + 384, B_CS = SM_BAR + 400, B_FH = SM_BAR + 416;
constexpr uint32_t CNT = 0x143444CC;
constexpr int NB_WG = 1, NB_T = 5, NB_Q = 10, NB_H = 11, NB_P = 14, NB_RL = 15;

struct Scratch {
  uint32_t F[32 * 32];
  uint4    H[17 * 8 * 256];
  uint4    SR[2][8][512];
  uint4    ST[32 * 16];
  uint4    PS[128 * 64];
  float4   CS[16 * 1536 / 4];
  uint32_t C[10 * 32 * 32];
  uint4    XF[32 * 4096];
  uint4    O[32 * 8 * 512];
  uint4    XG[2][512 * 256];
};
__device__ __align__(1024) Scratch g_S;

struct Params {
  int by_sm;
  uint32_t zero;
  Scratch* S;
  const uint16_t *x0, *Are, *Aim, *Bre, *Bim, *Cre, *Cim, *logdt, *dskip, *wqkv, *wo;
  uint16_t* out;
  uint8_t role[144];
};
#define EVENT(n) do {} while (0)
#define PROFD(slot, name, v) do {} while (0)
#define PROF(slot, name) do {} while (0)
#define PW(x)

DEV uint32_t s2u(const void* p) { return (uint32_t)__cvta_generic_to_shared(p); }
template <class T> DEV T opq(T x) { asm volatile("" : "+r"(x)); return x; }
DEV uint32_t pack2(float lo, float hi) { uint32_t d; asm("cvt.rn.bf16x2.f32 %0,%1,%2;" : "=r"(d) : "f"(hi), "f"(lo)); return d; }
DEV float bflo(uint32_t v) { return __uint_as_float(v << 16); }
DEV float bfhi(uint32_t v) { return __uint_as_float(v & 0xFFFF0000u); }
DEV float bfr(float x) { return bflo(pack2(x, 0.f)); }
DEV uint32_t hadd2(uint32_t a, uint32_t b) { uint32_t d; asm("add.rn.bf16x2 %0,%1,%2;" : "=r"(d) : "r"(a), "r"(b)); return d; }
DEV uint32_t hsub2(uint32_t a, uint32_t b) { uint32_t d; asm("sub.rn.bf16x2 %0,%1,%2;" : "=r"(d) : "r"(a), "r"(b)); return d; }
DEV uint32_t hmul2(uint32_t a, uint32_t b) { uint32_t d; asm("mul.rn.bf16x2 %0,%1,%2;" : "=r"(d) : "r"(a), "r"(b)); return d; }
DEV uint32_t hfma2(uint32_t a, uint32_t b, uint32_t c) { uint32_t d; asm("fma.rn.bf16x2 %0,%1,%2,%3;" : "=r"(d) : "r"(a), "r"(b), "r"(c)); return d; }
DEV uint32_t hmax2(uint32_t a, uint32_t b) { uint32_t d; asm("max.bf16x2 %0,%1,%2;" : "=r"(d) : "r"(a), "r"(b)); return d; }
DEV uint32_t prmt(uint32_t a, uint32_t b, uint32_t s) { uint32_t d; asm("prmt.b32 %0,%1,%2,%3;" : "=r"(d) : "r"(a), "r"(b), "r"(s)); return d; }
DEV uint32_t nz(uint32_t v) { uint32_t d; asm("max.u32 %0,%1,1;" : "=r"(d) : "r"(v)); return d; }
DEV uint32_t tagged(uint32_t v, uint32_t m, uint32_t tag) { uint32_t d; asm("lop3.b32 %0,%1,%2,%3,0xB8;" : "=r"(d) : "r"(v), "r"(m), "r"(tag)); return d; }
DEV uint32_t both(uint32_t a, uint32_t b, uint32_t x) { uint32_t d; asm("lop3.b32 %0,%1,%2,%3,0x42;" : "=r"(d) : "r"(a), "r"(b), "r"(x)); return d; }
DEV uint4 hadd8(const uint4& a, const uint4& b) { return make_uint4(hadd2(a.x, b.x), hadd2(a.y, b.y), hadd2(a.z, b.z), hadd2(a.w, b.w)); }
DEV uint32_t min4(const uint4& v) { return min(min(v.x, v.y), min(v.z, v.w)); }
DEV float rcp(float x) { float y; asm("rcp.approx.ftz.f32 %0,%1;" : "=f"(y) : "f"(x)); return y; }
DEV float sqrt_(float x) { float y; asm("sqrt.approx.ftz.f32 %0,%1;" : "=f"(y) : "f"(x)); return y; }
DEV float ex2(float x) { float y; asm("ex2.approx.ftz.f32 %0,%1;" : "=f"(y) : "f"(x)); return y; }

DEV uint4 ldr4(const void* p) { uint4 v; asm volatile("ld.relaxed.gpu.global.v4.u32 {%0,%1,%2,%3},[%4];" : "=r"(v.x), "=r"(v.y), "=r"(v.z), "=r"(v.w) : "l"(p) : "memory"); return v; }
DEV void ldr4_if(uint4& v, const void* p, bool c) {
  asm volatile("{.reg .pred q; setp.ne.u32 q,%5,0; @q ld.relaxed.gpu.global.v4.u32 {%0,%1,%2,%3},[%4];}"
    : "+r"(v.x), "+r"(v.y), "+r"(v.z), "+r"(v.w) : "l"(p), "r"((uint32_t)c) : "memory");
}
DEV uint2 ldr2(const void* p) { uint2 v; asm volatile("ld.relaxed.gpu.global.v2.u32 {%0,%1},[%2];" : "=r"(v.x), "=r"(v.y) : "l"(p) : "memory"); return v; }
DEV uint32_t ldr1(const void* p) { uint32_t v; asm volatile("ld.relaxed.gpu.global.u32 %0,[%1];" : "=r"(v) : "l"(p) : "memory"); return v; }
DEV void str4(void* p, uint32_t a, uint32_t b, uint32_t c, uint32_t d) { asm volatile("st.relaxed.gpu.global.v4.u32 [%0],{%1,%2,%3,%4};" :: "l"(p), "r"(a), "r"(b), "r"(c), "r"(d) : "memory"); }
DEV void str4_if(void* p, uint32_t a, uint32_t b, uint32_t c, uint32_t d, bool q) {
  asm volatile("{.reg .pred q; setp.ne.u32 q,%5,0; @q st.relaxed.gpu.global.v4.u32 [%0],{%1,%2,%3,%4};}" :: "l"(p), "r"(a), "r"(b), "r"(c), "r"(d), "r"((uint32_t)q) : "memory");
}
DEV void str2(void* p, uint32_t a, uint32_t b) { asm volatile("st.relaxed.gpu.global.v2.u32 [%0],{%1,%2};" :: "l"(p), "r"(a), "r"(b) : "memory"); }
DEV void str1(void* p, uint32_t a) { asm volatile("st.relaxed.gpu.global.u32 [%0],%1;" :: "l"(p), "r"(a) : "memory"); }
DEV void stw4(void* p, uint32_t a, uint32_t b, uint32_t c, uint32_t d) { asm volatile("st.global.v4.u32 [%0],{%1,%2,%3,%4};" :: "l"(p), "r"(a), "r"(b), "r"(c), "r"(d) : "memory"); }
DEV uint4 ldnc4(const void* p) { uint4 v; asm volatile("ld.global.nc.v4.u32 {%0,%1,%2,%3},[%4];" : "=r"(v.x), "=r"(v.y), "=r"(v.z), "=r"(v.w) : "l"(p)); return v; }
DEV uint4 ldw4(const void* p) { uint4 v; asm volatile("ld.global.v4.u32 {%0,%1,%2,%3},[%4];" : "=r"(v.x), "=r"(v.y), "=r"(v.z), "=r"(v.w) : "l"(p) : "memory"); return v; }
DEV void cp16(uint32_t d, const void* p) { asm volatile("cp.async.cg.shared.global [%0],[%1],16;" :: "r"(d), "l"(p) : "memory"); }
DEV uint32_t ldnc16(const void* p) { uint32_t v; asm volatile("ld.global.u16 %0,[%1];" : "=r"(v) : "l"(p) : "memory"); return v; }

DEV uint32_t lds1v(uint32_t a) { uint32_t v; asm volatile("ld.volatile.shared.u32 %0,[%1];" : "=r"(v) : "r"(a) : "memory"); return v; }
DEV uint4 lds4v(uint32_t a) { uint4 v; asm volatile("ld.volatile.shared.v4.u32 {%0,%1,%2,%3},[%4];" : "=r"(v.x), "=r"(v.y), "=r"(v.z), "=r"(v.w) : "r"(a) : "memory"); return v; }
DEV uint32_t lds1(uint32_t a) { uint32_t v; asm volatile("ld.shared.u32 %0,[%1];" : "=r"(v) : "r"(a)); return v; }
DEV uint2 lds2(uint32_t a) { uint2 v; asm volatile("ld.shared.v2.u32 {%0,%1},[%2];" : "=r"(v.x), "=r"(v.y) : "r"(a)); return v; }
DEV uint4 lds4(uint32_t a) { uint4 v; asm volatile("ld.shared.v4.u32 {%0,%1,%2,%3},[%4];" : "=r"(v.x), "=r"(v.y), "=r"(v.z), "=r"(v.w) : "r"(a)); return v; }
DEV uint32_t lds16(uint32_t a) { uint32_t v; asm volatile("ld.shared.u16 %0,[%1];" : "=r"(v) : "r"(a)); return v; }
DEV float lds1f(uint32_t a) { float v; asm volatile("ld.shared.f32 %0,[%1];" : "=f"(v) : "r"(a)); return v; }
DEV float2 lds2f(uint32_t a) { float2 v; asm volatile("ld.shared.v2.f32 {%0,%1},[%2];" : "=f"(v.x), "=f"(v.y) : "r"(a)); return v; }
DEV float4 lds4f(uint32_t a) { float4 v; asm volatile("ld.shared.v4.f32 {%0,%1,%2,%3},[%4];" : "=f"(v.x), "=f"(v.y), "=f"(v.z), "=f"(v.w) : "r"(a)); return v; }
DEV void sts1(uint32_t a, uint32_t v) { asm volatile("st.shared.u32 [%0],%1;" :: "r"(a), "r"(v) : "memory"); }
DEV void sts16(uint32_t a, uint32_t v) { asm volatile("{.reg .b16 h; cvt.u16.u32 h,%1; st.shared.u16 [%0],h;}" :: "r"(a), "r"(v) : "memory"); }
DEV void sts2f(uint32_t a, float x, float y) { asm volatile("st.shared.v2.f32 [%0],{%1,%2};" :: "r"(a), "f"(x), "f"(y) : "memory"); }
DEV void sts4f(uint32_t a, float x, float y, float z, float w) { asm volatile("st.shared.v4.f32 [%0],{%1,%2,%3,%4};" :: "r"(a), "f"(x), "f"(y), "f"(z), "f"(w) : "memory"); }
DEV void sts4(uint32_t a, uint32_t x, uint32_t y, uint32_t z, uint32_t w) { asm volatile("st.shared.v4.u32 [%0],{%1,%2,%3,%4};" :: "r"(a), "r"(x), "r"(y), "r"(z), "r"(w) : "memory"); }
DEV void sts4z_if(uint32_t a, bool c) { asm volatile("{.reg .pred q; setp.ne.u32 q,%1,0; @q st.shared.v4.u32 [%0],{%2,%2,%2,%2};}" :: "r"(a), "r"((uint32_t)c), "r"(0) : "memory"); }

DEV void ldsm4t(uint32_t& r0, uint32_t& r1, uint32_t& r2, uint32_t& r3, uint32_t a) { asm volatile("ldmatrix.sync.aligned.m8n8.x4.trans.shared.b16 {%0,%1,%2,%3},[%4];" : "=r"(r0), "=r"(r1), "=r"(r2), "=r"(r3) : "r"(a) : "memory"); }
DEV void stsm4(uint32_t a, uint32_t r0, uint32_t r1, uint32_t r2, uint32_t r3) { asm volatile("stmatrix.sync.aligned.m8n8.x4.shared.b16 [%0],{%1,%2,%3,%4};" :: "r"(a), "r"(r0), "r"(r1), "r"(r2), "r"(r3) : "memory"); }
DEV void stsm2(uint32_t a, uint32_t r0, uint32_t r1) { asm volatile("stmatrix.sync.aligned.m8n8.x2.shared.b16 [%0],{%1,%2};" :: "r"(a), "r"(r0), "r"(r1) : "memory"); }
DEV void stsm4t(uint32_t a, uint32_t r0, uint32_t r1, uint32_t r2, uint32_t r3) { asm volatile("stmatrix.sync.aligned.m8n8.x4.trans.shared.b16 [%0],{%1,%2,%3,%4};" :: "r"(a), "r"(r0), "r"(r1), "r"(r2), "r"(r3) : "memory"); }
DEV uint32_t movm(uint32_t a) { uint32_t d; asm volatile("movmatrix.sync.aligned.m8n8.trans.b16 %0,%1;" : "=r"(d) : "r"(a)); return d; }
DEV void mma16(float (&d)[4], uint32_t a0, uint32_t a1, uint32_t a2, uint32_t a3, uint32_t b0, uint32_t b1) {
  asm volatile("mma.sync.aligned.m16n8k16.row.col.f32.bf16.bf16.f32 {%0,%1,%2,%3},{%4,%5,%6,%7},{%8,%9},{%0,%1,%2,%3};"
    : "+f"(d[0]), "+f"(d[1]), "+f"(d[2]), "+f"(d[3]) : "r"(a0), "r"(a1), "r"(a2), "r"(a3), "r"(b0), "r"(b1));
}
DEV void mma16z(float (&d)[4], uint32_t a0, uint32_t a1, uint32_t a2, uint32_t a3, uint32_t b0, uint32_t b1) {
  asm volatile("mma.sync.aligned.m16n8k16.row.col.f32.bf16.bf16.f32 {%0,%1,%2,%3},{%4,%5,%6,%7},{%8,%9},{%10,%10,%10,%10};"
    : "=f"(d[0]), "=f"(d[1]), "=f"(d[2]), "=f"(d[3]) : "r"(a0), "r"(a1), "r"(a2), "r"(a3), "r"(b0), "r"(b1), "f"(0.f));
}
DEV void mma8z(float (&d)[4], uint32_t a0, uint32_t a1, uint32_t b0) {
  asm volatile("mma.sync.aligned.m16n8k8.row.col.f32.bf16.bf16.f32 {%0,%1,%2,%3},{%4,%5},{%6},{%7,%7,%7,%7};"
    : "=f"(d[0]), "=f"(d[1]), "=f"(d[2]), "=f"(d[3]) : "r"(a0), "r"(a1), "r"(b0), "f"(0.f));
}
DEV void mma8(float (&d)[4], uint32_t a0, uint32_t a1, uint32_t b0) {
  asm volatile("mma.sync.aligned.m16n8k8.row.col.f32.bf16.bf16.f32 {%0,%1,%2,%3},{%4,%5},{%6},{%0,%1,%2,%3};"
    : "+f"(d[0]), "+f"(d[1]), "+f"(d[2]), "+f"(d[3]) : "r"(a0), "r"(a1), "r"(b0));
}

DEV void bar_sync(int id, int n) { asm volatile("bar.sync %0,%1;" :: "r"(id), "r"(n) : "memory"); }
DEV void bar_arrive(int id, int n) { asm volatile("bar.arrive %0,%1;" :: "r"(id), "r"(n) : "memory"); }
DEV void bar_sync_if(int id, int n, int c) { asm volatile("{.reg .pred q; setp.ne.s32 q,%2,0; @q bar.sync %0,%1;}" :: "r"(id), "r"(n), "r"(c) : "memory"); }
DEV void bar_arrive_if(int id, int n, int c) { asm volatile("{.reg .pred q; setp.ne.s32 q,%2,0; @q bar.arrive %0,%1;}" :: "r"(id), "r"(n), "r"(c) : "memory"); }
DEV bool bar_any(int id, int n, bool c) {
  uint32_t r; asm volatile("{.reg .pred p,q; setp.ne.u32 q,%3,0; bar.red.or.pred p,%1,%2,q; selp.u32 %0,1,0,p;}" : "=r"(r) : "r"(id), "r"(n), "r"((uint32_t)c) : "memory");
  return __any_sync(0xffffffffu, r);
}
DEV void fence_async_glob() { asm volatile("fence.proxy.async.global;" ::: "memory"); }
DEV void fence_async_smem() { asm volatile("fence.proxy.async.shared::cta;" ::: "memory"); }
DEV void fence_gpu() { asm volatile("fence.acq_rel.gpu;" ::: "memory"); }
DEV void mbar_wait(uint32_t b, uint32_t ph) {
  asm volatile("{\n.reg .pred p;\nW: mbarrier.try_wait.parity.shared::cta.b64 p,[%0],%1;\n@!p bra W;\n}" :: "r"(b), "r"(ph) : "memory");
}
DEV bool mbar_test(uint32_t b, uint32_t ph) {
  uint32_t r; asm volatile("{.reg .pred p; mbarrier.test_wait.parity.shared::cta.b64 p,[%1],%2; selp.u32 %0,1,0,p;}" : "=r"(r) : "r"(b), "r"(ph) : "memory");
  return __all_sync(0xffffffffu, r);
}
DEV uint32_t mbar_test2(uint32_t b, uint32_t ph) {
  uint32_t r; asm volatile("{.reg .pred p,q; mbarrier.test_wait.parity.shared::cta.b64 p,[%1],%2; mbarrier.test_wait.parity.shared::cta.b64 q,[%1+8],%2;\n"
                           "and.pred p,p,q; selp.u32 %0,1,0,p;}" : "=r"(r) : "r"(b), "r"(ph) : "memory");
  return r;
}
DEV void spin_guard(int it) { asm volatile("{.reg .pred p; setp.gt.s32 p,%0,%1; @p trap;}" :: "r"(it), "n"(SPIN_LIMIT)); }
DEV uint32_t here(uint32_t zero) {
  uint32_t d; asm volatile("mov.u32 %0,%%clock;" : "=r"(d) :: "memory"); return d & zero;
}
DEV int lane_here(uint32_t zero) {
  uint32_t d; asm volatile("mov.u32 %0,%%laneid;" : "=r"(d)); return d | here(zero);
}
DEV void delay(uint32_t n) { const uint32_t t0 = clock(); while ((uint32_t)clock() - t0 < n); __syncwarp(); }
DEV void poll(const uint32_t* p, uint32_t n) {
  for (int it = 0; !__all_sync(0xffffffffu, ldr1(p) >= n); ++it) spin_guard(it);
}
DEV void cnt_add(const Params& P, int n, int c, int lane) { asm volatile("{.reg .pred p; setp.lt.s32 p,%1,%2; @p red.relaxed.gpu.global.add.u32 [%0],1;}" :: "l"(P.S->C + (32 * (NSUB * lane + c % NSUB) + n * 1024)), "r"(lane), "n"(NCOPY) : "memory"); }
DEV uint32_t* cnt_at(const Params& P, int n, int c, int lane) { return P.S->C + (32 * (NSUB * lane + c % NSUB) + n * 1024); }
DEV void cnt_add(uint32_t* p, uint32_t one, bool q) { asm volatile("{.reg .pred p; setp.ne.u32 p,%2,0; @p red.relaxed.gpu.global.add.u32 [%0],%1;}" :: "l"(p), "r"(one), "r"((uint32_t)q) : "memory"); }
DEV void cnt_wait(const Params& P, int n, int c, int lane) { poll(P.S->C + (32 * (NSUB * (c / (128 / NCOPY)) + lane % NSUB) + n * 1024), 128 / NSUB); }
DEV void mbar_init1(uint32_t b, int n) { asm volatile("{.reg .pred p; elect.sync _|p,0xffffffff; @p mbarrier.init.shared::cta.b64 [%0],%1;}" :: "r"(b), "r"(n) : "memory"); }
DEV void mbar_arrive1(uint32_t b) { asm volatile("{.reg .pred p; elect.sync _|p,0xffffffff; @p mbarrier.arrive.shared::cta.b64 _,[%0];}" :: "r"(b) : "memory"); }
DEV void mbar_arrive1_if(uint32_t b, int c) {
  asm volatile("{.reg .pred p,q; setp.ne.s32 q,%1,0; elect.sync _|p,0xffffffff; and.pred p,p,q; @p mbarrier.arrive.shared::cta.b64 _,[%0];}" :: "r"(b), "r"(c) : "memory");
}
DEV void mbar_expect1(uint32_t b, int bytes) { asm volatile("{.reg .pred p; elect.sync _|p,0xffffffff; @p mbarrier.arrive.expect_tx.shared::cta.b64 _,[%0],%1;}" :: "r"(b), "r"(bytes) : "memory"); }
DEV void flag_set1(uint32_t* q) { asm volatile("{.reg .pred p; elect.sync _|p,0xffffffff; @p st.relaxed.gpu.global.u32 [%0],1;}" :: "l"(q) : "memory"); }
DEV void tma3(uint32_t dst, const CUtensorMap* m, int c0, int c1, uint32_t bar) {
  asm volatile("{.reg .pred p; elect.sync _|p,0xffffffff;\n"
    "@p cp.async.bulk.tensor.3d.shared::cluster.global.mbarrier::complete_tx::bytes [%0],[%1,{%2,%3,%5}],[%4];}"
    :: "r"(dst), "l"(m), "r"(c0), "r"(c1), "r"(bar), "r"(0) : "memory");
}
DEV void tma5(uint32_t dst, const CUtensorMap* m, int c0, int c4, uint32_t bar) {
  asm volatile("{.reg .pred p; elect.sync _|p,0xffffffff;\n"
    "@p cp.async.bulk.tensor.5d.shared::cluster.global.mbarrier::complete_tx::bytes [%0],[%1,{%2,%5,%5,%5,%3}],[%4];}"
    :: "r"(dst), "l"(m), "r"(c0), "r"(c4), "r"(bar), "r"(0) : "memory");
}
DEV void bulk(uint32_t dst, const void* src, int bytes, uint32_t bar) {
  asm volatile("{.reg .pred p; elect.sync _|p,0xffffffff;\n@p cp.async.bulk.shared::cluster.global.mbarrier::complete_tx::bytes [%0],[%1],%2,[%3];}" :: "r"(dst), "l"(src), "r"(bytes), "r"(bar) : "memory");
}
DEV void bulk_store(void* dst, uint32_t src, int bytes) {
  asm volatile("{.reg .pred p; elect.sync _|p,0xffffffff;\n@p cp.async.bulk.global.shared::cta.bulk_group [%0],[%1],%2;}" :: "l"(dst), "r"(src), "r"(bytes) : "memory");
}
DEV void l2_prefetch(const void* src, int bytes) {
  asm volatile("{.reg .pred p; elect.sync _|p,0xffffffff;\n@p cp.async.bulk.prefetch.L2.global [%0],%1;}" :: "l"(src), "r"(bytes) : "memory");
}

DEV uint64_t mkdesc(uint32_t addr, uint32_t lbo, uint32_t sbo, uint32_t swz) {
  return (uint64_t)((addr >> 4) | ((lbo >> 4) << 16)) | ((uint64_t)((sbo >> 4) | (swz << 30)) << 32);
}
DEV void wg_fence() { asm volatile("wgmma.fence.sync.aligned;" ::: "memory"); }
DEV void wg_commit() { asm volatile("wgmma.commit_group.sync.aligned;" ::: "memory"); }
template <int N> DEV void wg_wait() { asm volatile("wgmma.wait_group.sync.aligned %0;" :: "n"(N) : "memory"); }
template <int N> DEV void zerov(float (&d)[N]) {
#pragma unroll
  for (int i = 0; i < N; ++i) asm volatile("mov.b32 %0,0;" : "=f"(d[i]));
}
template <int N> DEV void undef(float (&d)[N]) {
#pragma unroll
  for (int i = 0; i < N; ++i) asm volatile("" : "=f"(d[i]));
}
#define R4(d, o) "+f"(d[o]), "+f"(d[o + 1]), "+f"(d[o + 2]), "+f"(d[o + 3])
#define R8(d, o) R4(d, o), R4(d, o + 4)
#define R16(d, o) R8(d, o), R8(d, o + 8)
#define R32(d, o) R16(d, o), R16(d, o + 16)
#define L0 "%0,%1,%2,%3,%4,%5,%6,%7,%8,%9,"
#define L10(a) "%" #a "0,%" #a "1,%" #a "2,%" #a "3,%" #a "4,%" #a "5,%" #a "6,%" #a "7,%" #a "8,%" #a "9,"
#define WG_HEAD(pr, n) "{.reg .pred p; setp.ne.s32 p,%" #pr ",0;\nwgmma.mma_async.sync.aligned.m64n" #n "k16.f32.bf16.bf16 {"
DEV void wg_rs64k(float (&d)[32], const uint32_t (&a)[4], uint64_t db, int acc) {
  asm volatile(WG_HEAD(37, 64) L0 L10(1) L10(2) "%30,%31},{%32,%33,%34,%35},%36,p,1,1,0;}"
    : R32(d, 0) : "r"(a[0]), "r"(a[1]), "r"(a[2]), "r"(a[3]), "l"(db), "r"(acc));
}
DEV void wg_rs48t(float (&d)[24], const uint32_t (&a)[4], uint64_t db, int acc) {
  asm volatile(WG_HEAD(29, 48) L0 L10(1) "%20,%21,%22,%23},{%24,%25,%26,%27},%28,p,1,1,1;}"
    : R16(d, 0), R8(d, 16) : "r"(a[0]), "r"(a[1]), "r"(a[2]), "r"(a[3]), "l"(db), "r"(acc));
}
DEV void wg_rs32t(float (&d)[16], const uint32_t (&a)[4], uint64_t db, int acc) {
  asm volatile(WG_HEAD(21, 32) L0 "%10,%11,%12,%13,%14,%15},{%16,%17,%18,%19},%20,p,1,1,1;}"
    : R16(d, 0) : "r"(a[0]), "r"(a[1]), "r"(a[2]), "r"(a[3]), "l"(db), "r"(acc));
}
DEV void wg_ss48(float (&d)[24], uint64_t da, uint64_t db, int acc) {
  asm volatile(WG_HEAD(26, 48) L0 L10(1) "%20,%21,%22,%23},%24,%25,p,1,1,1,1;}" : R16(d, 0), R8(d, 16) : "l"(da), "l"(db), "r"(acc));
}
DEV void wg_ss64(float (&d)[32], uint64_t da, uint64_t db, int acc) {
  asm volatile(WG_HEAD(34, 64) L0 L10(1) L10(2) "%30,%31},%32,%33,p,1,1,0,1;}" : R32(d, 0) : "l"(da), "l"(db), "r"(acc));
}
DEV void wg_ss192(float (&d)[96], uint64_t da, uint64_t db, int acc) {
  asm volatile(WG_HEAD(98, 192) L0 L10(1) L10(2) L10(3) L10(4) L10(5) L10(6) L10(7) L10(8) "%90,%91,%92,%93,%94,%95},%96,%97,p,1,1,1,1;}"
    : R32(d, 0), R32(d, 32), R32(d, 64) : "l"(da), "l"(db), "r"(acc));
}

DEV void wg_rs192t(float (&d)[96], const uint32_t (&a)[4], uint64_t db) {
  asm volatile("wgmma.mma_async.sync.aligned.m64n192k16.f32.bf16.bf16 {" L0 L10(1) L10(2) L10(3) L10(4) L10(5) L10(6) L10(7) L10(8) "%90,%91,%92,%93,%94,%95},{%96,%97,%98,%99},%100,1,1,1,1;"
    : R32(d, 0), R32(d, 32), R32(d, 64) : "r"(a[0]), "r"(a[1]), "r"(a[2]), "r"(a[3]), "l"(db));
}

DEV float ln_sd(float s, float q, float& m) {
  m = s * (1.f / 512.f);
  return bfr(sqrt_(bfr(bfr(fmaxf(q * (1.f / 512.f) - m * m, 0.f)) + 1e-5f)));
}
DEV float4 gram(const uint32_t (&w)[8][2], int g, uint32_t zero) {
  float s[4], q[4][4];
  const uint32_t o0 = 0x3F803F80u | zero, o1 = 0x3F803F80u ^ zero;
#pragma unroll
  for (int j = 0; j < 8; ++j) {
#pragma unroll
    for (int h = 0; h < 2; ++h) { if (j < 2) mma8z(q[2 * j + h], w[j][0], w[j][1], w[j][h]); else mma8(q[2 * (j & 1) + h], w[j][0], w[j][1], w[j][h]); }
    if (j == 1) mma16z(s, w[0][0], w[0][1], w[1][0], w[1][1], o0, o1);
    else if (j & 1) mma16(s, w[j - 1][0], w[j - 1][1], w[j][0], w[j][1], o0, o1);
  }
  const bool od = g & 1;
  return make_float4(s[0], od ? q[0][1] + q[2][1] : q[0][0] + q[2][0], s[2], od ? q[1][3] + q[3][3] : q[1][2] + q[3][2]);
}
DEV void keep(uint32_t v, uint32_t zero) {
  asm volatile("{.reg .pred p; setp.ne.u32 p,%1,0; @p st.shared.u32 [%0],%0;}" :: "r"(v), "r"(zero) : "memory");
}
DEV void keep(const void* v, uint32_t zero) { asm volatile("{.reg .pred p; setp.ne.u32 p,%1,0; @p st.global.u32 [%0],%1;}" :: "l"(v), "r"(zero) : "memory"); }
struct XgAddr { uint32_t a, b; uint4* dst; };
template <bool FRAG> DEV XgAddr xg_addr(uint4* dst, uint32_t stg, int wp, int lane, uint32_t zero) {
  const int t = lane & 3, r = 4 * wp + (lane >> 3);
  XgAddr x = {stg + t * (FRAG ? 256 : 1024) + ((wp ^ t) * 32) + (lane >> 2) * 4,
              stg + r * 128 + (((lane & 7) ^ (2 * (((r >> 1) ^ (r >> 3)) & 3))) * 16), dst + (r * 256 + (lane & 7))};
  keep(x.a, zero); keep(x.b, zero); keep(x.dst, zero);
  return x;
}
template <bool FRAG> DEV void xg_put(const XgAddr& x, const uint32_t (&w)[8][2]) {
#pragma unroll
  for (int n = 0; n < 8; ++n) {
    const uint32_t b = (x.a ^ ((n & 3) * 32)) + (FRAG ? n * 1024 : (n >> 2) * 4096 + (n & 3) * 256);
    sts1(b, prmt(w[n][0], w[n][1], 0x5410)); sts1(b + 128, prmt(w[n][0], w[n][1], 0x7632));
  }
}
DEV void xg_store(const XgAddr& x) {
#pragma unroll
  for (int k = 0; k < 4; ++k) {
    const uint4 v = lds4((x.b ^ ((k & 1) * 64)) + k * 2048);
    str4(x.dst + k * 4096, nz(v.x), v.y, v.z, v.w);
  }
}
template <int N, int M> DEV void fold(float (&v)[M], int lane, int bit) {
  const bool b = lane & bit;
#pragma unroll
  for (int k = 0; k < N; ++k) { const float sn = b ? v[k] : v[k + N], kp = b ? v[k + N] : v[k]; v[k] = kp + __shfl_xor_sync(0xffffffffu, sn, bit); }
}
DEV void refetch(uint32_t dst, const uint4* src, int half, int e, int w) {
#pragma unroll 1
  for (int r = 0; r < 2; ++r) {
    if (w == 0) { mbar_expect1(B_R + 8 * e, half); bulk(dst + r * half, src + r * (half >> 4), half, B_R + 8 * e); }
    mbar_wait(B_R + 8 * e, r);
    bar_sync(NB_WG + e, 128);
  }
}
DEV uint32_t kvslot(int cg, int pos) { return (pos & 2 ? SM_XA : SM_S1) + (cg < 4 ? 5 : 2) * 8192 + (pos & 1) * 4096; }
DEV uint32_t xstage(int q, int e) { return ((q + 1) & 2) ? SM_R + ((q & 2) + e) * 16384 : e ? SM_XB : SM_XA; }
DEV void cmul(float& orr, float& oi, float ar, float ai, float br, float bi) {
  float r = ar * br - ai * bi, i = ar * bi + ai * br; orr = r; oi = i;
}
DEV void cexp_(float al, float bt, float s, float& er, float& ei) {
  float mag = ex2(al * s), ph = bt * s;
  ph -= rintf(ph);
  float ang = ph * 6.283185307179586f;
  er = mag * __cosf(ang); ei = mag * __sinf(ang);
}

#define KS 2048
DEV void put8(uint32_t a, const float (&r)[8], const float (&i)[8]) {
  sts4(a, pack2(r[0], r[1]), pack2(r[2], r[3]), pack2(r[4], r[5]), pack2(r[6], r[7]));
  sts4(a + 1024, pack2(i[0], i[1]), pack2(i[2], i[3]), pack2(i[4], i[5]), pack2(i[6], i[7]));
}
DEV void tables(const uint32_t (&pv)[8], int k4, int w, int lane) {
  PW(4 * k4 + w)
  [[maybe_unused]] const int layer = 0;
  const float dt = bfr(__expf(bflo(pv[6])));
  const float al = dt * bflo(pv[0]) * 1.4426950408889634f, bt = dt * bflo(pv[1]) * 0.15915494309189535f;
  float qr[8], qi[8], yr[8], yi[8];
  cmul(qr[0], qi[0], bflo(pv[4]), bflo(pv[5]), dt * bflo(pv[2]), dt * bflo(pv[3]));
  PROFD(2, a_par, __float_as_uint(qr[0] + al + bt));
  float e1r, e1i, eMr, eMi, eLr, eLi;
  cexp_(al, bt, 1.f, e1r, e1i); cexp_(al, -bt, 8.f, yr[1], yi[1]); cexp_(al, -bt, 64.f, eMr, eMi); cexp_(al, bt, 256.f, eLr, eLi);
  const uint32_t ad = SB + k4 * 32768 + (w & 1) * 512 + lane * 16, am = ad + (w >> 1) * KS, an = ad + (8 + 3 * (w >> 1)) * KS;
  yr[0] = 1.f; yi[0] = 0.f;
#pragma unroll
  for (int k = 1; k < 8; ++k) {
    cmul(qr[k], qi[k], qr[k - 1], qi[k - 1], e1r, e1i);
    if (k > 1) cmul(yr[k], yi[k], yr[k - 1], yi[k - 1], yr[1], yi[1]);
  }
  put8(an, qr, qi);
#pragma unroll
  for (int j = 0; j < 4; ++j) {
    put8(am + j * 2 * KS, yr, yi);
#pragma unroll
    for (int k = 0; k < 8; ++k) {
      if (j == 0 && k == 0) { yr[0] = eMr; yi[0] = eMi; } else if (j < 3) cmul(yr[k], yi[k], yr[k], yi[k], eMr, eMi);
    }
    if (j == 0) {
#pragma unroll
      for (int k = 0; k < 8; ++k) { const int o = k < 4 ? 2 * k : k < 6 ? 2 * k - 8 : k - 2; cmul(qr[k], qi[k], qr[o], qi[o], eLr, eLi); }
      put8(an + KS, qr, qi);
    } else if (j == 1) {
#pragma unroll
      for (int k = 0; k < 5; ++k) cmul(qr[k], qi[k], qr[k ? k - 1 : 6], qi[k ? k - 1 : 6], eLr, eLi);
      put8(an + 2 * KS, qr, qi);
    }
  }
  PROF(3, a_tab);
}

DEV void sts16_if(uint32_t a, uint32_t v, bool c) { asm volatile("{.reg .pred q; .reg .b16 h; setp.ne.u32 q,%2,0; cvt.u16.u32 h,%1; @q st.shared.u16 [%0],h;}" :: "r"(a), "r"(v), "r"((uint32_t)c) : "memory"); }
DEV void sts1_if(uint32_t a, uint32_t v, bool c) { asm volatile("{.reg .pred q; setp.ne.u32 q,%2,0; @q st.shared.u32 [%0],%1;}" :: "r"(a), "r"(v), "r"((uint32_t)c) : "memory"); }
DEV void taps(uint32_t dskip, int k4, int w, int lane) {
  PW(4 * k4 + w)
  [[maybe_unused]] const int layer = 0;
  fence_async_smem();
  bar_sync((k4 & 1) ? NB_WG + k4 : NB_Q, (k4 & 1) ? 128 : 448);
  float d[24];
  undef(d);
  const uint64_t da = mkdesc(SB + k4 * 32768, 1024, KS, 0);
  wg_fence();
#pragma unroll
  for (int j = 0; j < 8; ++j) wg_ss48(d, da + j * 8, da + KS / 2 + j * 8, j);
  wg_commit();
  const int b = 8 * w + (lane >> 2), t = lane & 3, id = 32 * w + lane;
  constexpr int DO = T_O - T_E;
  const uint32_t te = SM_TAP + k4 * TAP_SZ + T_E, a0 = te - 16 * b - 4 * t;
  const uint32_t a1 = a0 - 512 - 4 * t, a2 = te - 2 * (511 + b) - 64 * t, a3 = te + (T_C - T_E) - 2 * (127 + b) - 128 * t;
  wg_wait<0>();
  PROF(4, a_mma);
  {
    const uint32_t v = pack2(d[1] + d[15], d[0] + d[14] + (id ? 0.f : bflo(dskip)));
    sts1(a0 + DO - 2, v); sts16(a0 - 2, v); sts16(a0, v >> 16);
  }
  {
    const uint32_t v = pack2(d[5] + d[19], d[4] + d[18]), u = prmt(v, v, 0x3232);
    const bool lo = t < 2, k512 = id == 2;
    sts1_if(k512 ? te - 2 * 512 : a1, u, (lo && id) || k512);
    sts1_if(k512 ? te - 2 * 514 : a1 - 4, k512 ? u : v, lo || k512);
    sts1_if(k512 ? te + DO - 2 * 513 : a1 + DO - 2, u, lo || k512);
    sts16(lo ? a1 + DO - 4 : a2 + DO - 194, v);
    sts16(lo ? (id ? a1 + DO + 2 : a1) : k512 ? te + DO - 2 * 511 : a2 + DO, u);
    sts16_if(a2 - 194, v, !lo);
    sts16_if(k512 ? te + DO - 2 * 514 : a2, u, !lo);
  }
  {
    const uint32_t v = pack2(d[8] + d[22], d[9] + d[23]);
    sts16_if(id ? a3 : te - 2 * 639, v, t < 2 || id == 2);
    sts16_if(a3 - 64, v >> 16, t < 2);
    sts16_if(te + DO - 2 * 639, v, id == 0);
  }
  bar_sync(NB_WG + k4, 128);
  mbar_arrive1_if(B_K, w == 0);
}

DEV uint32_t cpy(uint32_t v, uint32_t id) {
  uint32_t d; asm volatile("prmt.b32 %0,%1,%1,%2;" : "=r"(d) : "r"(v), "r"(id)); return d;
}
DEV uint32_t uoff(int s) { return (s ^ ((s >> 3) & 3)) * 16; }
template <bool FULL> DEV void boxes(const uint32_t (&u)[10], uint32_t a, uint32_t a9, uint32_t a7, uint32_t (&pv)[4]) {
  uint32_t v[8], p[8], x[4], y[4];
#pragma unroll
  for (int j = 0; j < 8; ++j) { v[j] = prmt(u[j], u[j + 1], 0x5432); p[j] = hadd2(u[j], v[j]); }
#pragma unroll
  for (int j = 0; j < 4; ++j) { x[j] = hadd2(hadd2(p[j + 1], p[j + 2]), u[j + 3]); y[j] = hadd2(v[j + 3], p[j + 4]); }
  sts4(a + R_A5, x[0], x[1], x[2], x[3]);
  sts4(a + R_A3, y[0], y[1], y[2], y[3]);
  if (FULL) {
#pragma unroll
    for (int j = 0; j < 4; ++j) { x[j] = hadd2(x[j], hadd2(v[j], v[j + 3])); y[j] = hadd2(x[j], hadd2(u[j], u[j + 4])); pv[j] = p[j + 4]; }
    sts4(a7, x[0], x[1], x[2], x[3]);
    sts4(a9, y[0], y[1], y[2], y[3]);
  }
}
DEV void halo(uint32_t (&u)[10], uint32_t a, int lane) {
  asm volatile("{.reg .pred p,q; setp.eq.s32 p,%8,0; setp.lt.s32 q,%8,2;\n@p ld.shared.v4.u32 {%2,%3,%4,%5},[%6];\n@q ld.shared.v2.u32 {%0,%1},[%7];}"
    : "+r"(u[0]), "+r"(u[1]), "+r"(u[2]), "+r"(u[3]), "+r"(u[4]), "+r"(u[5]) : "r"(a), "r"(a + 24 - 16 * lane), "r"(lane));
}
#define ROT 2
#define G1 -1
#define G2 0
#define G3 1
#define TPS 0x9135
#define GMASK ((G1 >= 0 ? 2 : 0) | (G2 >= 0 ? 4 : 0) | (G3 >= 0 ? 8 : 0))
#define GATE1(g, n, p) if (g >= 0 && (g & 3) == p) mbar_arrive1_if(B_G + 8 * n, k4 == (g >> 2));
#define GATE(p) GATE1(G1, 0, p) GATE1(G2, 1, p) GATE1(G3, 2, p)
#define TMASK(p) (((TPS & 15) == p) | ((((TPS >> 4) & 15) == p) << 1) | ((((TPS >> 8) & 15) == p) << 2) | ((((TPS >> 12) & 15) == p) << 3))
#define TURN(p) if (TMASK(p) == 15) bar_arrive(NB_T + 1 + k4, 256); else if (TMASK(p)) { if ((TMASK(p) >> k4) & 1) bar_arrive(NB_T + 1 + k4, 256); }
DEV void w_load(const CUtensorMap* mW, int cg, int h) {
  mbar_expect1(B_W + 8 * h, 24576);
  tma3(SM_S0 + (h & 3) * 24576, mW, 64 * cg, 64 * h, B_W + 8 * h);
}

DEV void conv(const Params& P, const CUtensorMap* mW, int c, int k4, int w, int layer) {
  const uint32_t zero = P.zero;
  PW(4 * k4 + w)
  int lane = lane_here(zero);
  const int g = lane >> 2, t = lane & 3, v = w ^ (ROT * (k4 & 1)), tid = 32 * v + lane;
  const uint32_t reg = SM_R + k4 * 16384, tp = SM_TAP + k4 * TAP_SZ;
  const uint32_t g0 = tp + ((g & 1) ? T_O : T_E) + 2 * (2 * t - g);
  uint32_t F[18][4], U[20], qc[4][4];
#define LO(q, a) q[0] = lds1(a); q[2] = lds1(a + 16);
#define HI(q, a) q[1] = lds1(a - 128); q[3] = lds1(a - 112);
  {
    const uint32_t ga = g0 - 32 * (w & 1) - 576 * (w >> 1), g2 = tp + T_C - 258 - 32 * w + 4 * (t - g);
    F[0][2] = lds1(ga + 48);
#pragma unroll
    for (int j = 0; j < 8; ++j) { F[j][0] = lds1(ga + 32 - 32 * j); F[j][1] = lds1(ga + 16 - 32 * j); }
#pragma unroll
    for (int j = 0; j < 20; ++j) U[j] = lds1(ga - 224 - 16 * j);
#pragma unroll
    for (int j = 0; j < 4; ++j) { LO(qc[j], g2 + 32 * j) HI(qc[j], g2 + 32 * j) }
  }
  if (layer) { mbar_wait(B_ED, 0); mbar_wait(B_ED + 8, 0); }
  sts4z_if(reg + lane * 16 + (w ? w * 3584 + 1024 : 0), w < 3);
  PROF(5, a_pre);
  if (k4 == 3 && w == 3) {
    mbar_wait(B_E, layer);
    mbar_wait(B_K, 0);
#pragma unroll
    for (int h = 0; h < 4; ++h) w_load(mW, c & 7, h);
  }
  mbar_wait(k4 && ((GMASK >> k4) & 1) ? B_G - 8 + 8 * k4 : B_E, layer);
  PROF(6, a_x);
  const uint32_t ua = reg + R_U + uoff(tid);
  uint4 x[2];
  uint32_t pv[4];
  {
    uint4 s[4];
#pragma unroll
    for (int z = 0; z < 2; ++z) x[z] = lds4(reg + R_B + tid * 16 + z * 2048);
#pragma unroll
    for (int z = 0; z < 4; ++z) s[z] = lds4(SM_RES + tid * 16 + (z >> 1) * 2048 + (z & 1) * 4096);
    for (int it = 0;; ++it) {
      uint32_t m = min(x[0].x, x[1].x);
#pragma unroll
      for (int z = 0; z < 4; ++z) m = min(m, min(s[z].x, s[z].z));
      if (m) break;
#pragma unroll
      for (int z = 0; z < 2; ++z) x[z] = ldr4(&P.S->XG[layer][(128 * k4 + c) * 256 + opq(tid) + z * 128]);
#pragma unroll
      for (int z = 0; z < 4; ++z) s[z] = ldr4(&P.S->SR[layer][c >> 4][opq(tid) + (z >> 1) * 128 + (z & 1) * 256]);
#pragma unroll
      for (int z = 0; z < 4; ++z) sts4(SM_RES + tid * 16 + (z >> 1) * 2048 + (z & 1) * 4096, s[z].x, s[z].y, s[z].z, s[z].w);
      spin_guard(it);
    }
    __syncwarp();
    uint32_t u[2][10];
#pragma unroll
    for (int z = 0; z < 2; ++z) {
      u[z][6] = hmul2(hsub2(x[z].x, s[2 * z].y), s[2 * z].x); u[z][7] = hmul2(hsub2(x[z].y, s[2 * z].w), s[2 * z].z);
      u[z][8] = hmul2(hsub2(x[z].z, s[2 * z + 1].y), s[2 * z + 1].x); u[z][9] = hmul2(hsub2(x[z].w, s[2 * z + 1].w), s[2 * z + 1].z);
      sts4(ua + z * 2048, u[z][6], u[z][7], u[z][8], u[z][9]);
    }
#pragma unroll
    for (int j = 0; j < 6; ++j) u[0][j] = __shfl_up_sync(0xffffffffu, u[0][j < 2 ? 8 + j : 4 + j], j < 2 ? 2 : 1);
    bar_sync(NB_WG + k4, 128);
    GATE(0)
    PROF(7, a_u);
    const uint32_t h1 = reg + R_U + v * 512 - 64;
    halo(u[0], h1, lane);
    if (v < 2) {
      u[1][0] = 0;
#pragma unroll
      for (int j = 1; j < 6; ++j) u[1][j] = __shfl_up_sync(0xffffffffu, u[1][j < 2 ? 8 + j : 4 + j], j < 2 ? 2 : 1);
      halo(u[1], h1 + 2048, lane);
      boxes<false>(u[1], reg + tid * 16 + 2048, 0, 0, pv);
    }
    const uint32_t bo = reg + R_B + tid * 16 + (v >> 1) * 1056;
    const uint32_t be = tid == 127 ? reg + R_B + 1024 : bo + (tid == 63 ? 2112 : 1056);
    boxes<true>(u[0], reg + tid * 16, (lane & 1) ? be : bo, (lane & 1) ? bo : be, pv);
    sts4z_if(reg + R_B + 1040, tid == 0);
  }
  GATE(1)
  fence_async_smem();
  if (k4 == 3 && w < 3) {
    const uint32_t src = SM_RES + 8192 + w * 2048, f = (w >> 1) - 1;
#pragma unroll
    for (int z = 0; z < 4; ++z) sts4(src + lane * 16 + z * 512, f, f, f, f);
    fence_async_smem();
    __syncwarp();
    if (w < 2) {
#pragma unroll
      for (int z = 0; z < 4; ++z) bulk_store(&P.S->O[((c >> 3) * 16 + w * 8 + (c & 7)) * 512] + z * 128, src, 2048);
    } else {
#pragma unroll
      for (int z = 0; z < 2; ++z) {
        bulk_store(&P.S->H[(c + 8) * 256] + z * 128, src, 2048);
        bulk_store(P.S->F + ((c >> 3) * 64 + 4 * (c & 7)) + z * 32, src, 16);
      }
      bulk_store(&P.S->PS[c * 64], src, 1024);
      bulk_store(&P.S->ST[c * 4], src, 64);
      if (c < 5) bulk_store(P.S->C + (c + 5 - 5 * layer) * 1024, src, 128 * NCOPY * NSUB);
    }
    asm volatile("cp.async.bulk.commit_group;" ::: "memory");
  }
  const uint32_t id = opq(0x3210u);
#pragma unroll
  for (int j = 0; j < 8; ++j) { F[j][3] = cpy(F[j][0], id); if (j) F[j][2] = cpy(F[j - 1][1], id); }
  PROF(8, a_box);
  bar_sync(NB_T + k4, k4 ? 256 : 128);
  PROF(9, a_turn);
  float acc[32], f1[24], f3[16];
  uint32_t qa[4][4], qb[4][4], fp[4];
  const uint64_t db = mkdesc(reg + R_U, 16, 512, 2) + 2;
#define STEP(mm) wg_fence(); mm; wg_commit(); wg_wait<2>();
#define D(j) STEP(wg_rs64k(acc, F[j], db - 2 * j, j))
#define C(j) STEP(wg_rs32t(f3, qc[j], mkdesc(reg + R_B, 128, 1040, 0) + 16 * j, j))
#define NIL(q) { const uint32_t z = here(zero); q[2][1] = cpy(z, 0); q[2][3] = cpy(z, 1); q[3][1] = cpy(z, 2); q[3][3] = cpy(z, 3); }
#define X(j) F[j][0] = cpy(U[2 * j - 16], ix); F[j][1] = cpy(U[2 * j - 15], ix); F[j][3] = cpy(F[j][0], ix); F[j][2] = cpy(F[j - 1][1], ix);
#define PIN ix = 0x3210u | here(zero);
  const uint32_t g1 = g0 - 2 * 576 - 16 * w;
  const uint64_t d1 = mkdesc(reg + R_A5, 128, 512, 0);
  constexpr int O3 = (R_A3 - R_A5) / 16;
  uint32_t ix;
  undef(acc);
  D(0) TURN(0) D(1) D(2) D(3) D(4) D(5)
  undef(f3);
  C(0) C(1) TURN(1) PIN X(8) X(9) C(2) C(3) LO(qa[0], g1)
  D(6) HI(qa[0], g1) PIN X(10) D(7) LO(qa[1], g1 + 32) X(11)
  fp[0] = pack2(f3[0], f3[1]); fp[1] = pack2(f3[4], f3[5]); fp[2] = pack2(f3[8] + f3[2], f3[9] + f3[3]); fp[3] = pack2(f3[12] + f3[6], f3[13] + f3[7]);
  D(8) HI(qa[1], g1 + 32) PIN ix |= fp[0] & fp[1] & fp[2] & fp[3] & zero; X(12) D(9) LO(qa[2], g1 - 64) X(13)
  D(10) TURN(2) LO(qa[3], g1 - 32) X(14) D(11) LO(qb[0], g1 - 192) PIN X(15) D(12) HI(qb[0], g1 - 192) X(16)
  D(13) LO(qb[1], g1 - 160) X(17) D(14) TURN(3) HI(qb[1], g1 - 160) NIL(qa)
  D(15) LO(qb[2], g1 - 256) D(16) LO(qb[3], g1 - 224) NIL(qb) D(17) TURN(4)
  PROF(10, a_den);
  undef(f1);
  wg_fence();
#pragma unroll
  for (int j = 0; j < 4; ++j) wg_rs48t(f1, qa[j], d1 + 16 * (j & 1) - 32 * (j >> 1), j);
  wg_commit();
  wg_wait<1>();
  TURN(5)
  wg_fence();
#pragma unroll
  for (int j = 0; j < 4; ++j) wg_rs48t(f1, qb[j], d1 + O3 + 16 * (j & 1) - 32 * (j >> 1), 1);
  wg_commit();
  TURN(6)
  lane = lane_here(zero);
  bar_sync(NB_WG + k4, 128);
  {
    const int p = (lane + 9 * (w >> 1)) & 31;
    const uint32_t ya = reg + ((w >> 1) ? R_B : R_U) + p * 64 + (((2 * (w & 1)) ^ ((p >> 1) & 3)) * 16), up = p < lane ? 2048 : 0;
#pragma unroll
    for (int z = 0; z < 4; ++z) {
      const float* a = acc + 16 * (z >> 1) + 2 * (z & 1);
      stsm4t((ya + (up ^ ((z >> 1) * 2048))) ^ ((z & 1) * 16), pack2(a[0], a[1]), pack2(a[4], a[5]), pack2(a[8], a[9]), pack2(a[12], a[13]));
    }
  }
  asm volatile("cp.async.bulk.wait_group 0;" ::: "memory");
  const uint32_t fa = reg + R_A5 + (lane >> 3) * 512 + w * 128 + (lane & 7) * 16;
  const uint32_t fc = reg + R_A3 + uoff(64 * (lane >> 4) + 16 * w + 2 * (lane & 7) + 1 - ((lane >> 3) & 1));
  uint32_t k1024 = lds16(tp + T_E - 2 * 639 + (fa & fc & zero));
  wg_wait<0>();
  GATE(2)
  PROF(11, a_far);
  bar_sync(NB_WG + k4, 128);
  stsm4(fc, fp[0], fp[1], fp[2], fp[3]);
  stsm4(fa, pack2(f1[0], f1[1]), pack2(f1[4], f1[5]), pack2(f1[8] + f1[2], f1[9] + f1[3]), pack2(f1[12] + f1[6], f1[13] + f1[7]));
  stsm2(fa + 2048, pack2(f1[16] + f1[10], f1[17] + f1[11]), pack2(f1[20] + f1[14], f1[21] + f1[15]));
  {
    const int o = 32 * v + lane;
    const uint32_t a = reg + uoff(o), b = reg + R_A5 + o * 16;
    uint4 y[2] = {hadd8(lds4(a + R_U), lds4(o >= 36 ? a + R_B : reg)), hadd8(lds4(a + R_U + 2048), lds4(a + R_B + 2048))};
    bar_sync(NB_WG + k4, 128);
    TURN(7)
    PROF(12, a_sts);
    const uint4 f = lds4(v >= 2 ? b - 1024 : reg), f2 = lds4(b + 1024);
    uint4 h = lds4(a + R_A3);
    const int e0 = (o >> 3) * 8192 + (128 * k4 + c) * 16 + (((o & 4) + ((o >> 1) & 1)) ^ (c & 7)) * 2 + (o & 1);
    const uint32_t me = (e0 & 3) == ((c >> 1) & 3), m0 = me & ~c, m1 = me & c, tag = 1 - layer;
    uint32_t* cp = cnt_at(P, 1 + 5 * layer + k4, c, lane);
    keep(cp, zero);
    k1024 = prmt(k1024, k1024, 0x1010);
    h = make_uint4(hfma2(pv[0], k1024, h.x), hfma2(pv[1], k1024, h.y), hfma2(pv[2], k1024, h.z), hfma2(pv[3], k1024, h.w));
    y[0] = hadd8(y[0], f); y[1] = hadd8(y[1], hadd8(f2, h));
    cnt_add(cp, 1 | (y[0].x & y[1].x & zero), (o ^ 96) < NCOPY);
#pragma unroll
    for (int z = 0; z < 2; ++z) {
      const uint4 r = hadd8(x[z], y[z]);
      str2((uint2*)P.S->XF + e0 + z * 131072, tagged(prmt(r.x, r.y, 0x5410), m0, tag), tagged(prmt(r.z, r.w, 0x5410), m1, tag));
      str2((uint2*)P.S->XF + (e0 ^ 4) + z * 131072, tagged(prmt(r.x, r.y, 0x7632), m0, tag), tagged(prmt(r.z, r.w, 0x7632), m1, tag));
    }
  }
  TURN(9)
  GATE(3)
  PROF(13, a_out);
}

#define WGATE 1
#define FH 1
#define QPIN 1
#define XORD 1
DEV void x_load(const Params& P, int c, int q, int layer) {
#pragma unroll
  for (int z = 0; z < 2; ++z) {
    const int e = z ^ (XORD && q == 3 && !(c & 4));
    mbar_expect1(B_X + 16 * q + 8 * e, 16384);
    bulk(xstage(q, e), P.S->XF + ((2 * (c >> 3) + 1 - e) * 4096 + q * 1024), 16384, B_X + 16 * q + 8 * e);
  }
}

DEV void means(uint32_t (&m)[4], int row, int lane, int layer, uint32_t zero) {
  mbar_wait(B_CS, 0);
  mbar_wait(B_ST, layer);
  const uint32_t a = SM_MISC + row * 4 + (lane & 28), k = (lane & 3) ? 0u : ~0u;
  m[0] = lds1(a) & k; m[1] = lds1(a + 32) & k; m[2] = m[0] & zero; m[3] = m[1] & zero;
}

DEV void attn_phase(const Params& P, int c, int e, int w, int lane, int layer) {
  PW(4 * e + w)
  const int cg = c & 7, J = 2 * (c >> 3) + 1 - e;
  float acc[96];
  zerov(acc);
  uint32_t m[4] = {0, 0, 0, 0};
#pragma unroll 1
  for (int q = 0;; ++q) {
    const uint64_t da = mkdesc(xstage(q, e), 16, 1024, 1), db = mkdesc(SM_S0 + (q & 1) * 49152, 8192, 1024, 1);
    const uint32_t wr = mbar_test2(B_W + 16 * q, layer), xa = xstage(q, e) + w * 4096 + lane * 132;
    mbar_wait(B_X + 16 * q + 8 * e, layer);
    for (int it = 0;; ++it) {
      const uint32_t ok = both(lds1(xa), lds1(xa ^ 32), layer) & both(lds1(xa ^ 64), lds1(xa ^ 96), layer);
      if (__all_sync(0xffffffffu, ok & 1)) break;
      EVENT(8 * layer + 2 * q + e);
#pragma unroll 1
      for (int j = 0; j < 8; ++j) cp16(xstage(q, e) + w * 4096 + j * 512 + lane * 16, P.S->XF + (J * 4096 + q * 1024 + w * 256 + j * 32 + lane));
      asm volatile("cp.async.wait_all;" ::: "memory");
      fence_async_smem();
      __syncwarp();
      spin_guard(it);
    }
    bool all = __all_sync(0xffffffffu, wr);
    if (q == 0 && e && w == 0) {
      bar_sync(NB_H, 256);
      cnt_wait(P, 2 + 5 * layer, c, lane);
      x_load(P, c, 1, layer);
      PROF(27, m_xi);
    }
    if (q == 3 && e) means(m, 16 * w, lane, layer, P.zero);
    if (!all) { mbar_wait(B_W + 16 * q, layer); all = mbar_test(B_W + 16 * q + 8, layer); }
    bar_sync(e ? NB_Q : q ? NB_T : NB_T + 4, 256);
    PROF(14 + q, m_q);
    wg_fence();
#pragma unroll
    for (int k = 0; k < 8; ++k) {
      if (k == 4) { wg_commit(); if (!all) mbar_wait(B_W + 16 * q + 8, layer); wg_fence(); }
      wg_ss192(acc, da + k * 128, db + (k >> 2) * 1536 + (k & 3) * 128, 1);
    }
    wg_commit();
    if (q == 3) break;
    bar_arrive(e ? NB_T : NB_Q, 256);
    if (FH) { wg_wait<1>(); mbar_arrive1_if(B_FH + 8 * q, e && q < 2); }
    wg_wait<0>();
    mbar_arrive1(B_F + 8 * q);
  }
  const int pos = 2 - 2 * e + (w >> 1);
  uint4* h = P.S->H + ((c + 8) * 256 + (w & 1) * 128 + lane);
  {
    if (!e) means(m, 64 + 16 * w, lane, layer, P.zero);
    PROF(28, m_sub);
    wg_fence();
    wg_rs192t(acc, m, mkdesc(SM_CS, 0, 32, 0));
    wg_commit();
    bar_arrive_if(NB_Q, 256, !e);
    keep(h, P.zero);
    wg_wait<0>();
    mbar_arrive1(B_F + 24);
  }
  PROF(18, m_qkv);
  lane = opq(lane);
  const int g = lane >> 2, t = lane & 3;
  uint32_t Q[4][4], K[4][3][2], V[4][3][2];
  const uint32_t ra = SM_STAT + 256 + (32 - 32 * e + 8 * w) * 16;
  float r0, r1;
  uint4 k0, k1, k2;
  {
#pragma unroll
    for (int z = 0; z < 4; ++z) {
      K[z][2][0] = nz(pack2(acc[34 + 8 * z], acc[35 + 8 * z])); K[z][2][1] = pack2(acc[38 + 8 * z], acc[39 + 8 * z]);
      V[z][2][0] = pack2(acc[66 + 8 * z], acc[67 + 8 * z]); V[z][2][1] = pack2(acc[70 + 8 * z], acc[71 + 8 * z]);
      str4_if(h + z * 32, K[z][2][0], K[z][2][1], V[z][2][0], V[z][2][1], pos == 3);
    }
    bar_arrive_if(NB_RL, 128, pos == 3);
#pragma unroll
    for (int z = 0; z < 8; ++z) {
      V[z >> 1][2][z & 1] = movm(V[z >> 1][2][z & 1]);
      K[z >> 1][1][z & 1] = pack2(acc[32 + 4 * z], acc[33 + 4 * z]);
      V[z >> 1][1][z & 1] = pack2(acc[64 + 4 * z], acc[65 + 4 * z]);
    }
    const uint32_t kv = (w & 1) * 2048 + lane * 16;
    if (pos < 3) {
      mbar_wait(B_F + 16 + 8 * e, layer);
#pragma unroll
      for (int z = 0; z < 4; ++z) sts4(kvslot(cg, pos + 1) + kv + z * 512, K[z][2][0], K[z][2][1], V[z][2][0], V[z][2][1]);
      bar_arrive(NB_H + pos + 1, 128);
    }
    r0 = lds1f(ra + (g >> 1) * 16 + (g & 1) * 4); r1 = lds1f(ra + 64 + (g >> 1) * 16 + (g & 1) * 4);
    k1 = lds4(ra + 16 * t); k2 = lds4(ra + 64 + 16 * t);
    PROF(19, m_kv);
    uint32_t pin = QPIN ? P.zero : 0;
#pragma unroll
    for (int z = 0; z < 8; ++z) {
      V[z >> 1][1][z & 1] = movm(V[z >> 1][1][z & 1]);
      Q[z >> 1][2 * (z & 1)] = pack2(acc[4 * z], acc[4 * z + 1]);
      Q[z >> 1][2 * (z & 1) + 1] = pack2(acc[4 * z + 2], acc[4 * z + 3]);
      if (QPIN) pin &= Q[z >> 1][2 * (z & 1)] & Q[z >> 1][2 * (z & 1) + 1];
    }
    mbar_wait(B_F + 24, layer);
    bar_sync(NB_H + pos + pin, pos ? 128 : 160);
    k0 = lds4(ra - 192 + 16 * t);
#pragma unroll
    for (int z = 0; z < 4; ++z) {
      const uint4 hv = lds4(kvslot(cg, pos) + kv + z * 512);
      K[z][0][0] = hv.x; K[z][0][1] = hv.y; V[z][0][0] = hv.z; V[z][0][1] = hv.w;
    }
  }
  PROF(20, m_halo);
  const uint32_t ob = e ? SM_S1 : SM_XA;
  {
    const bool p0 = 2 * t > g, p1 = 2 * t + 1 > g, first = c < 8 && pos == 0;
    const uint32_t M = (p0 ? 0xFFFFu : 0u) | (p1 ? 0xFFFF0000u : 0u);
    const float sc0 = r0 * (0.25f * 1.4426950408889634f), sc1 = r1 * (0.25f * 1.4426950408889634f);
    const float sk[4] = {__uint_as_float(p0 ? k0.x : k1.x) * sc0, __uint_as_float(p1 ? k0.y : k1.y) * sc0,
                         __uint_as_float(p0 ? k1.x : k2.x) * sc1, __uint_as_float(p1 ? k1.y : k2.y) * sc1};
    const uint32_t rm[4] = {k0.z & M, k1.z & ~M, k1.z & M, k2.z & ~M}, s0 = k0.w | P.zero, s1 = k1.w | P.zero;
    const int oo = cg * 512 + (2 * (w & 2) + (w & 1)) * 64 + (lane ^ (g >> 1));
    uint4* O = P.S->O + (J * 4096 + oo);
#pragma unroll
    for (int h2 = 0; h2 < 2; ++h2) {
      uint32_t A[2], B[2], mx[2];
#pragma unroll
      for (int z = 0; z < 2; ++z) {
        const int h = 2 * h2 + z;
        float S[3][4];
#pragma unroll
        for (int n = 0; n < 3; ++n) mma16z(S[n], Q[h][0], Q[h][1], Q[h][2], Q[h][3], K[h][n][0], K[h][n][1]);
        if (first) { S[0][0] = __uint_as_float(0xFF800000u); S[0][1] = S[0][0]; }
        A[z] = pack2((p0 ? S[0][0] : S[1][0]) * sk[0], (p0 ? S[1][2] : S[2][2]) * sk[2]);
        B[z] = pack2((p1 ? S[0][1] : S[1][1]) * sk[1], (p1 ? S[1][3] : S[2][3]) * sk[3]);
      }
#pragma unroll
      for (int z = 0; z < 2; ++z) mx[z] = hmax2(A[z], B[z]);
#pragma unroll
      for (int z = 0; z < 2; ++z) mx[z] = hmax2(mx[z], __shfl_xor_sync(0xffffffffu, mx[z], 1));
#pragma unroll
      for (int z = 0; z < 2; ++z) mx[z] = hmax2(mx[z], __shfl_xor_sync(0xffffffffu, mx[z], 2));
      float Oa[2][3][4];
#pragma unroll
      for (int z = 0; z < 2; ++z) {
        const int h = 2 * h2 + z;
        const uint32_t a = hsub2(A[z], mx[z]), b = hsub2(B[z], mx[z]);
        const uint32_t w0 = pack2(ex2(bflo(a)), ex2(bflo(b))), w1 = pack2(ex2(bfhi(a)), ex2(bfhi(b)));
        const uint32_t u0 = hmul2(w0, rm[0]), u1 = hmul2(w0, rm[1]), u2 = hmul2(w1, rm[2]), u3 = hmul2(w1, rm[3]);
        const uint32_t z0 = w0 & P.zero, z1 = w1 & P.zero;
        mma16z(Oa[z][2], u0, z0, u1, u2, s0, s1);
#pragma unroll
        for (int d = 0; d < 2; ++d) mma16z(Oa[z][d], u0, z0, u1, u2, V[h][0][d], V[h][1][d]);
        mma8(Oa[z][2], z1, u3, k2.w);
#pragma unroll
        for (int d = 0; d < 2; ++d) mma8(Oa[z][d], z1, u3, V[h][2][d]);
      }
#pragma unroll
      for (int r = 0; r < 4; r += 2) {
        const float i0 = rcp(Oa[0][2][r]), i1 = rcp(Oa[1][2][r]);
        const uint32_t o0 = pack2(Oa[0][0][r] * i0, Oa[0][0][r + 1] * i0), o1 = pack2(Oa[0][1][r] * i0, Oa[0][1][r + 1] * i0);
        const uint32_t o2 = pack2(Oa[1][0][r] * i1, Oa[1][0][r + 1] * i1), o3 = pack2(Oa[1][1][r] * i1, Oa[1][1][r + 1] * i1);
        str4(O + h2 * 32 + r * 64, o0, o1, o2, o3);
        sts4(ob + oo * 16 + h2 * 512 + r * 1024, o0, o1, o2, o3);
      }
    }
  }
  bar_arrive(NB_T + 1 + e, 160);
  fence_async_smem();
  PROF(21, m_att);
  uint32_t res[8][2];
  mbar_wait(B_RES, layer);
  {
    const uint32_t a = SM_RES + e * 8192 + (lane >> 4) * 1024 + (lane & 7) * 128 + (((2 * (w & 2) + ((lane >> 2) & 2) + (w & 1)) ^ (lane & 7)) * 16);
#pragma unroll
    for (int j = 0; j < 8; j += 2) ldsm4t(res[j][0], res[j][1], res[j + 1][0], res[j + 1][1], a + j * 1024);
  }
  PROF(26, m_res);
  if (WGATE) bar_sync(NB_T, 256); else bar_sync(NB_WG + e, 128);
  XgAddr xa = xg_addr<true>(P.S->XG[1] + (64 * cg * 256 + 8 * J), ob, w, lane, P.zero);
  uint4* ps = &P.S->PS[((4 * J + w) * 8 + cg) * 8 + g];
  keep(ps, P.zero);
  if (layer) {
    xa.a = ob + w * 2048 + (lane & 15) * 128 + (((lane >> 4) ^ (lane & 7)) * 16);
    xa.b = ob + w * 2048 + (lane >> 3) * 128 + (((lane & 7) ^ (lane >> 3)) * 16);
    xa.dst = (uint4*)P.out + ((64 * J + 16 * w + 2 * (lane >> 3)) * 64 + 8 * cg + (lane & 7));
  }
  uint32_t y[8][2];
#pragma unroll 1
  for (int it = 0;; ++it) {
    float ac[32];
    zerov(ac);
#pragma unroll 1
    for (int n = 0; n < 8; ++n) {
      const int s = n == 0 ? cg : n - (n <= cg);
      mbar_wait(n ? B_O + 64 * e + 8 * s : B_WO, layer);
      if (n == 1) PROF(22, m_o1);
      if (n == 7) PROF(23, m_o7);
      const uint64_t da = mkdesc(ob + s * 8192, 16, 1024, 2), db = mkdesc(SM_R + s * 8192, 16, 1024, 1);
      wg_fence();
#pragma unroll
      for (int k = 0; k < 4; ++k) wg_ss64(ac, da + (k >> 1) * 32 + (k & 1) * 2, db + k * 128, 1);
      wg_commit();
    }
    wg_wait<0>();
    const bool bad = ac[0] != ac[0] || ac[2] != ac[2];
#pragma unroll
    for (int j = 0; j < 8; ++j) {
      y[j][0] = hadd2(res[j][0], pack2(ac[4 * j], ac[4 * j + 1]));
      y[j][1] = hadd2(res[j][1], pack2(ac[4 * j + 2], ac[4 * j + 3]));
    }
    if (!bar_any(NB_WG + e, 128, bad) || it == 16) break;
    EVENT(24 + 2 * layer + e);
    refetch(ob, P.S->O + J * 4096, 32768, e, w);
  }
  PROF(24, m_wo);
  if (layer == 0) {
    const float4 s = gram(y, g, P.zero);
    xg_put<true>(xa, y);
    str4_if(ps, nz(__float_as_uint(s.x)), __float_as_uint(s.y), __float_as_uint(s.z), __float_as_uint(s.w), t == (g >> 1));
    mbar_arrive1(B_ED + 8 * e);
    bar_sync(NB_WG + e, 128);
    xg_store(xa);
    bar_arrive(NB_T + 3, 288);
  } else {
#pragma unroll
    for (int j = 0; j < 8; j += 2) stsm4(xa.a ^ (j * 16), y[j][0], y[j][1], y[j + 1][0], y[j + 1][1]);
    __syncwarp();
#pragma unroll
    for (int k = 0; k < 4; ++k) {
      const uint4 v = lds4((xa.b ^ ((k & 1) * 64)) + k * 512);
      stw4(xa.dst + ((k & 1) * 8 + (k >> 1)) * 64, v.x, v.y, v.z, v.w);
    }
  }
  PROF(25, m_epi);
}

#define HDELAY 300
#define ODELAY 200
#define PDELAY 0
#define FDELAY 200
#define CSP 0
#define CSU 4
#define PHOLD 0
#define XDEL 300
#define WOQ 2
#define H5 1
#define SRDELAY 300
#define ZPACE 20

DEV void o_load(const Params& P, int c, int e, int lane, int layer) {
  PW(8 + e)
  const int J = 2 * (c >> 3) + 1 - e;
#pragma unroll 1
  for (int s = 0; s < 8; ++s) mbar_expect1(B_O + 64 * e + 8 * s, s == (c & 7) ? 0 : 8192);
  bar_sync(NB_T + 1 + e, 160);
  flag_set1(P.S->F + (J * 32 + 4 * (c & 7)));
  if (ODELAY) delay(ODELAY);
  PROF(26, a_go);
  poll(P.S->F + (J * 32 + (lane & 28)), 1);
  PROF(25, h_seen);
  bar_sync_if(NB_Q, 64, e);
#pragma unroll 1
  for (int s = 0; s < 8; ++s)
    if (s != (c & 7)) bulk((e ? SM_S1 : SM_XA) + s * 8192, P.S->O + (J * 4096 + s * 512), 8192, B_O + 64 * e + 8 * s);
  bar_arrive_if(NB_Q, 64, !e);
  PROF(28, a_o);
}

DEV void stats(const Params& P, int c, int w, int lane, int layer) {
  PW(12 + w)
  lane = opq(lane);
  const int r = (lane & 6) + ((lane >> 3) & 1), k = (2 * (c & 3) + (lane & 1)) ^ r, e = 1 - ((c >> 2) & 1);
  const uint32_t o = (32 * w + 8 * (lane >> 4) + r) * 128 + k * 16;
  const uint32_t mk = ((k & 1) == (r >> 2)) << (r & 3), tag = 1 - layer;
  float v[16];
#pragma unroll
  for (int z = 0; z < 16; ++z) v[z] = 0.f;
#pragma unroll 1
  for (int q = 0; q < 4; ++q) {
    mbar_wait(B_X + 16 * q + 8 * e, layer);
    PROF(19 + q, s_l);
    uint4 x, y;
    for (int it = 0;; ++it) {
      x = lds4v(xstage(q, e) + o); y = lds4v(xstage(q, e) + o + 2048);
      const uint32_t bad = (((x.x ^ tag) | (y.x ^ tag)) & mk) | (((x.y ^ tag) | (y.y ^ tag)) & (mk >> 1)) |
                           (((x.z ^ tag) | (y.z ^ tag)) & (mk >> 2)) | (((x.w ^ tag) | (y.w ^ tag)) & (mk >> 3));
      if (!__any_sync(0xffffffffu, bad & 1)) break;
      spin_guard(it);
    }
    mbar_arrive1(B_F + 8 * q);
    const uint32_t ws[8] = {x.x, x.y, x.z, x.w, y.x, y.y, y.z, y.w};
#pragma unroll
    for (int z = 0; z < 8; ++z) {
      const float lo = bflo(ws[z]), hi = bfhi(ws[z]);
      float* u = v + 4 * (z & 3);
      u[0] += lo; u[1] += lo * lo; u[2] += hi; u[3] += hi * hi;
    }
  }
  PROFD(14, s_part, __float_as_uint(v[0]));
  fold<8>(v, lane, 16); fold<4>(v, lane, 8); fold<2>(v, lane, 4); fold<1>(v, lane, 2);
  PROFD(16, s_fold, __float_as_uint(v[0]));
  if (w) {
    sts1(SM_MISC - 128 + w * 128 + lane * 4, __float_as_uint(v[0]));
    bar_arrive(NB_P, 128);
  } else {
    bar_sync(NB_P, 128);
    v[0] += lds1f(SM_MISC + lane * 4) + lds1f(SM_MISC + 128 + lane * 4) + lds1f(SM_MISC + 256 + lane * 4);
    float m;
    const float sd = ln_sd(v[0], __shfl_xor_sync(0xffffffffu, v[0], 2), m);
    if (!(lane & 2)) str1((uint32_t*)P.S->ST + (16 * c + 8 * (lane & 1) + (lane >> 2)), pack2(m, sd));
    sts4(SM_STAT - 32 + min(lane, 17) * 16, 0x3F800000u, 0x3F800000u, 0x3F803F80u, 0x3F803F80u);
    fence_async_smem();
    PROF(17, s_pub);
    uint4 s;
    for (int it = 0;; ++it) {
      s = ldr4(P.S->ST + ((c >> 3) * 32 + lane));
      if (__all_sync(0xffffffffu, min4(s) != 0u)) break;
      spin_guard(it);
    }
    PROF(18, s_seen);
    const float r0 = rcp(bfhi(s.x)), r1 = rcp(bfhi(s.y)), r2 = rcp(bfhi(s.z)), r3 = rcp(bfhi(s.w));
    const uint32_t sg = 0x80008000u;
    sts4(SM_MISC + lane * 16, prmt(s.x, s.x, 0x1010) ^ sg, prmt(s.y, s.y, 0x1010) ^ sg, prmt(s.z, s.z, 0x1010) ^ sg, prmt(s.w, s.w, 0x1010) ^ sg);
    sts4(SM_STAT + 256 + lane * 32, __float_as_uint(r0), __float_as_uint(r1), pack2(r0, r1), prmt(s.x, s.y, 0x7632));
    sts4(SM_STAT + 272 + lane * 32, __float_as_uint(r2), __float_as_uint(r3), pack2(r2, r3), prmt(s.z, s.w, 0x7632));
    __syncwarp();
    mbar_arrive1(B_ST);
  }
  PROF(15, s_stat);
  if (w == 1) {
    mbar_wait(B_ST, layer);
    if (c >= 8) {
      uint2 s;
      for (int it = 0;; ++it) {
        s = ldr2((const uint2*)P.S->ST + ((c >> 3) * 64 - 12 + (lane & 11)));
        if (__all_sync(0xffffffffu, min(s.x, s.y) != 0u)) break;
        spin_guard(it);
      }
      const float r0 = rcp(bfhi(s.x)), r1 = rcp(bfhi(s.y));
      sts4(SM_STAT + 64 + (lane & 11) * 16, __float_as_uint(r0), __float_as_uint(r1), pack2(r0, r1), prmt(s.x, s.y, 0x7632));
    }
    bar_arrive(NB_H, 160);
  }
  if (w >= 2) {
    const uint4* h = P.S->H + (c * 256 + (w & 1) * 128 + lane);
    uint4 hv[4];
#pragma unroll
    for (int z = 0; z < 4; ++z) hv[z] = make_uint4(0, 0, 0, 0);
    bar_sync(NB_RL, 128);
    PROFD(26, s_hb, lds1v(SM_MISC));
    delay(HDELAY);
    for (int it = 0; c >= 8; ++it) {
#pragma unroll
      for (int z = 0; z < 4; ++z) hv[z] = ldr4(h + z * 32);
      if (__all_sync(0xffffffffu, min(min(hv[0].x, hv[1].x), min(hv[2].x, hv[3].x)) != 0u)) break;
      spin_guard(it);
    }
    mbar_wait(B_F + 24, layer);
#pragma unroll
    for (int z = 0; z < 4; ++z) sts4(kvslot(c & 7, 0) + (w & 1) * 2048 + lane * 16 + z * 512, hv[z].x, hv[z].y, movm(hv[z].z), movm(hv[z].w));
    bar_arrive(NB_H, 160);
    PROF(25, s_halo);
  }
}

DEV void finalize(const Params& P, int c, int lane, int layer) {
  PW(12)
  float z[4];
  if (layer == 0) {
    bar_sync(NB_P, 256);
    z[0] = z[1] = z[2] = z[3] = 0.f;
#pragma unroll
    for (int k = 0; k < 2; ++k) { const float4 a = lds4f(SM_RES + 8192 + k * 512 + lane * 16); z[0] += a.x; z[1] += a.y; z[2] += a.z; z[3] += a.w; }
  } else {
    mbar_wait(B_ED + 8 - 2 * (c & 4), 0);
    if (FDELAY) delay(FDELAY);
    const uint4* ps = &P.S->PS[c * 64 + lane];
    uint4 a, b;
    for (int it = 0;; ++it) {
      a = ldr4(ps); b = ldr4(ps + 32);
      if (__all_sync(0xffffffffu, min(a.x, b.x) != 0u)) break;
      spin_guard(it);
    }
    z[0] = __uint_as_float(a.x) + __uint_as_float(b.x); z[1] = __uint_as_float(a.y) + __uint_as_float(b.y);
    z[2] = __uint_as_float(a.z) + __uint_as_float(b.z); z[3] = __uint_as_float(a.w) + __uint_as_float(b.w);
  }
#pragma unroll
  for (int o = 8; o < 32; o <<= 1)
#pragma unroll
    for (int k = 0; k < 4; ++k) z[k] += __shfl_xor_sync(0xffffffffu, z[k], o);
  float m0, m1;
  const float r0 = rcp(ln_sd(z[0], z[1], m0)), r1 = rcp(ln_sd(z[2], z[3], m1));
  const uint32_t wr = nz(pack2(r0, r1)), wm = pack2(m0, m1);
  uint2* so = (uint2*)P.S->SR[layer] + ((lane >> 3) * 1024 + (lane & 2) * 256 + 4 * c + ((lane >> 1) & 2) + (lane & 1));
  str2(so, wr, wm); str2(so + 4096, wr, wm);
  bar_arrive_if(NB_Q, 448, !layer);
  PROF(23, s_sr);
}

DEV void announce(const Params& P, int c, int lane, int layer) {
  PW(13)
  bar_sync(NB_T + 3, layer ? 288 : 160);
  cnt_add(P, 5 * layer, c, lane);
  bar_sync_if(NB_Q, 448, !layer);
  fence_async_smem();
  PROF(24, s_own);
}

DEV void fetch(const Params& P, int c, int lane, int layer) {
  PW(13)
  mbar_expect1(B_E, 24576);
  cnt_wait(P, 5 * layer, c, lane);
#pragma unroll
  for (int k = 0; k < 4; ++k) bulk(SM_R + k * 16384 + R_B, P.S->XG[layer] + (128 * k + c) * 256, 4096, B_E);
  if (layer) delay(SRDELAY);
  bulk(SM_RES, P.S->SR[layer][c >> 4], 8192, B_E);
  if (!layer) { if (!CSP) l2_prefetch(P.wqkv + c * 6144, 12288); l2_prefetch(P.wo + c * 2048, 4096); }
  if (PHOLD) mbar_arrive1_if(B_ST + 8, !layer);
  PROF(25, s_all);
}

DEV void cs_part(const Params& P, int c, int w, int lane, int layer) {
  float cs[8];
#pragma unroll
  for (int k = 0; k < 8; ++k) cs[k] = 0.f;
  const int col = w * 512 + 64 * (c & 7) + 8 * (lane & 7);
#pragma unroll 1
  for (int r = 8 * layer; r < 8; r += CSU) {
    uint4 v[CSU];
#pragma unroll
    for (int k = 0; k < CSU; ++k) v[k] = ldnc4(P.wqkv + ((32 * (c >> 3) + 4 * r + (lane >> 3)) * 1536 + col) + 4 * k * 1536);
#pragma unroll
    for (int k = 0; k < CSU; ++k) {
      cs[0] += bflo(v[k].x); cs[1] += bfhi(v[k].x); cs[2] += bflo(v[k].y); cs[3] += bfhi(v[k].y);
      cs[4] += bflo(v[k].z); cs[5] += bfhi(v[k].z); cs[6] += bflo(v[k].w); cs[7] += bfhi(v[k].w);
    }
  }
  fold<4>(cs, lane, 16); fold<2>(cs, lane, 8);
  str2((float*)P.S->CS + ((c >> 3) * 1536 + col + 2 * (lane >> 3)), max(__float_as_uint(cs[0]), 1u - layer), __float_as_uint(cs[1]));
}

DEV void cs_sum(const Params& P, int c, int w, int lane) {
  float a, b;
  for (int it = 0;; ++it) {
    uint32_t m = ~0u;
    a = b = 0.f;
#pragma unroll
    for (int k = 0; k < 16; ++k) {
      const uint2 u = ldr2((const float*)P.S->CS + (w * 512 + 64 * (c & 7) + 2 * lane) + k * 1536);
      a += __uint_as_float(u.x); b += __uint_as_float(u.y); m = min(m, u.x);
    }
    if (__all_sync(0xffffffffu, m != 0u)) break;
    spin_guard(it);
  }
  const uint32_t hi = pack2(a, b), ad = SM_CS + w * 256 + (lane >> 2) * 32 + (lane & 3) * 4;
  sts1(ad, hi); sts1(ad + 16, pack2(a - bflo(hi), b - bfhi(hi)));
  fence_async_smem();
  __syncwarp();
  mbar_arrive1(B_CS);
}

DEV void x0_get(uint32_t (&x)[8][2], uint32_t a) {
  asm volatile("cp.async.wait_group 0;" ::: "memory");
#pragma unroll
  for (int z = 0; z < 4; ++z) {
    const uint4 v = lds4(a + z * 512);
    x[2 * (z & 2)][z & 1] = v.x; x[2 * (z & 2) + 1][z & 1] = v.y; x[2 * (z & 2) + 2][z & 1] = v.z; x[2 * (z & 2) + 3][z & 1] = v.w;
  }
}

DEV void par_load(const Params& P, int ch, int m, uint32_t (&pv)[8]) {
  const int mo = ch * 128 + m;
  pv[0] = ldnc16(P.Are + mo); pv[1] = ldnc16(P.Aim + mo); pv[2] = ldnc16(P.Bre + mo); pv[3] = ldnc16(P.Bim + mo);
  pv[4] = ldnc16(P.Cre + mo); pv[5] = ldnc16(P.Cim + mo); pv[6] = ldnc16(P.logdt + ch); pv[7] = ldnc16(P.dskip + ch);
}

__global__ void __launch_bounds__(NTHR, 1)
fused_kernel(const __grid_constant__ Params P, const __grid_constant__ CUtensorMap mapW,
             const __grid_constant__ CUtensorMap mapWo) {
  extern __shared__ __align__(1024) uint8_t smem_raw[];
  if (s2u(smem_raw) != SB) __trap();
  const int warp0 = __shfl_sync(0xffffffffu, threadIdx.x >> 5, 0), lane0 = threadIdx.x & 31;
  uint32_t smid; asm volatile("mov.u32 %0,%%smid;" : "=r"(smid));
  const int c = __shfl_sync(0xffffffffu, P.by_sm ? P.role[smid] : blockIdx.x, 0);
  if (c == 255) {
    if (threadIdx.x < NCOPY * NSUB)
#pragma unroll 1
      for (int it = 0; it < 256 && ldr1(P.S->C + 32 * threadIdx.x) < 128 / NSUB; ++it) __nanosleep(200);
    return;
  }
  const int cg = c & 7;
  PW(warp0)
  uint32_t dskip;
  {
    [[maybe_unused]] const int layer = 0;
    const int lane = lane0, g = lane >> 2, t = lane & 3, warp = warp0, k4 = warp >> 2, w = warp & 3;
    uint32_t pv[8];
    if (k4 < 3) par_load(P, 128 * k4 + c, 32 * w + lane, pv);
    else {
#pragma unroll
      for (int n = 0; n < 8; ++n) pv[n] = 0;
    }
    __syncthreads();
    if (XDEL) delay(XDEL);
    const uint16_t* r = P.x0 + ((k4 < 2 ? 8192 * c + 64 * warp : (128 * (c >> 3) + 16 * w) * 512 + 64 * cg) + 1024 * g + 8 * t);
    const uint32_t xa = SM_R + k4 * 16384 + w * 2048 + lane * 16;
    if (k4 != 2) {
#pragma unroll
      for (int z = 0; z < 4; ++z) cp16(xa + z * 512, r + (z & 1) * 512 + (z & 2) * 16);
    }
    sts4(SM_TAP + k4 * TAP_SZ + (32 * w + lane) * 16, 0, 0, 0, 0);
    sts4z_if(SM_TAP + k4 * TAP_SZ + 2048 + (32 * w + lane) * 16, w < 3);
    uint32_t x[8][2];
    if (k4 == 3) {
#pragma unroll
      for (int z = 0; z < 4; ++z) cp16(xa - 16384 + z * 512, r + 32768 + (z & 1) * 512 + (z & 2) * 16);
      asm volatile("cp.async.commit_group;" ::: "memory");
      if (threadIdx.x == 448) {
        asm volatile("prefetch.tensormap [%0];" :: "l"(&mapW) : "memory");
        asm volatile("prefetch.tensormap [%0];" :: "l"(&mapWo) : "memory");
      }
      __syncwarp();
      if (PDELAY) delay(PDELAY);
      par_load(P, 128 * k4 + c, 32 * w + lane, pv);
      XgAddr xd = xg_addr<false>(P.S->XG[0] + (64 * cg * 256 + 16 * (c >> 3)), SM_R + 3 * 16384 + 8192, w, lane, P.zero);
      x0_get(x, xa);
      PROF(27, a_ld);
      xg_put<false>(xd, x);
      x0_get(x, xa - 16384);
      xd.a -= 16384;
      xg_put<false>(xd, x);
      bar_sync(NB_WG + 3, 128);
      xg_store(xd);
      xd.b -= 16384; xd.dst += 8;
      xg_store(xd);
      bar_arrive(NB_T + 3, 160);
      bar_sync(NB_Q, 448);
    } else asm volatile("cp.async.commit_group;" ::: "memory");
    tables(pv, k4, w, lane);
    if (k4 < 2) {
      x0_get(x, xa);
      const float4 s = gram(x, g, P.zero);
      if (t == (g >> 1)) sts4f(SM_RES + 8192 + (warp * 8 + g) * 16, s.x, s.y, s.z, s.w);
      __syncwarp();
      bar_arrive_if(NB_P, 256, warp != 7);
    }
    if (k4 == 2) {
#pragma unroll
      for (int n = 0; n < 14; ++n) mbar_init1(SM_BAR + (n < 10 ? w * 80 : 240 + w * 32) + n * 8, n < 10 ? 1 : (CNT >> (8 * w + 2 * (n - 10 & 2))) & 15);
    }
    dskip = pv[7];
    PROF(1, a_x0);
  }
#pragma unroll 1
  for (int layer = 0; layer < 2; ++layer) {
    int lane = lane_here(P.zero);
    const int warp = warp0 | (layer & P.zero), k4 = warp >> 2, w = warp & 3;
    if (warp == (layer ? 12 : 7)) finalize(P, c, lane, layer);
    if (warp == (layer ? 13 : 6)) { announce(P, c, lane, layer); fetch(P, c, lane, layer); }
    if (layer == 0) {
      if (CSP && k4 == 1 && w != 2) { if (CSP > 1) delay(CSP); cs_part(P, c, w - (w >> 1), lane, 0); }
      taps(dskip, k4, w, lane);
    }
    if (!layer && ((PHOLD >> k4) & 1)) mbar_wait(B_ST + 8, 0);
    conv(P, &mapW, c, k4, w, layer);
    lane = lane_here(P.zero);
    if (k4 < 2) {
      bar_arrive_if(NB_H, 256, warp != 4);
      if (warp == 0) {
        mbar_wait(B_K, 0);
        cnt_wait(P, 1 + 5 * layer, c, lane);
        x_load(P, c, 0, layer);
        PROF(27, m_xi);
      } else if (k4 == 0 && (CSP == 0 || layer)) cs_part(P, c, w - 1, lane, CSP ? 1 : layer);
      attn_phase(P, c, k4, w, lane, layer);
    } else {
      bar_arrive_if(NB_RL, 256, warp >= 10);
      if (k4 == 3) {
        stats(P, c, w, lane, layer);
      } else if (w < 2) {
        bar_sync_if(NB_RL, 256, w);
        cnt_wait(P, 3 + 5 * layer + w, c, lane);
        bar_sync_if(NB_RL, 256, !w);
        if (w) mbar_wait(B_F, layer);
        x_load(P, c, 2 + w, layer);
        if (H5 && w) w_load(&mapW, cg, 5);
        PROF(14, h_xi);
        if (w == 1) str4(&P.S->SR[layer][lane >> 2][4 * c + (lane & 3)], 0, 0, 0, 0);
      } else if (w == 2) {
        mbar_expect1(B_WO, 65536);
        mbar_expect1(B_RES, 16384);
#pragma unroll 1
        for (int q = 0; q < 4; ++q) {
          if (FH && q < 2) { mbar_wait(B_FH + 8 * q, layer); w_load(&mapW, cg, 4 + 2 * q); }
          mbar_wait(B_F + 8 * q, layer);
          if (!FH && q < 2) w_load(&mapW, cg, 4 + 2 * q);
          if (q == 1 || (q == 0 && !H5)) w_load(&mapW, cg, 5 + 2 * q);
          if (WOQ == 0 && ((q + 1) & 2)) tma5(SM_R + (q & 2) * 16384, &mapWo, 64 * cg, 4 * (q & 2), B_WO);
          if (WOQ && q == 2) {
            if (WOQ >= 2) mbar_wait(B_ST, layer);
            tma5(SM_R, &mapWo, 64 * cg, 0, B_WO);
            if (WOQ < 3) tma5(SM_R + 32768, &mapWo, 64 * cg, 8, B_WO);
          }
          if (q == 3) {
#pragma unroll
            for (int e = 0; e < 2; ++e) bulk(SM_RES + e * 8192, P.S->XF + ((2 * (c >> 3) + 1 - e) * 4096 + cg * 512), 8192, B_RES);
          }
          PROF(15 + q, h_w);
        }
      }
      if (k4 == 2 && w != 2) {
        if (layer == 0) cs_sum(P, c, w - (w >> 1), lane);
        if (w == 3) {
          uint4* xz = P.S->XG[layer] + (c * 256 + lane);
          mbar_wait(B_F, layer);
#pragma unroll 1
          for (int k = 0; k < 32; ++k) {
            str4(xz + ((k >> 3) * 32768 + (k & 7) * 32), 0, 0, 0, 0);
            if (ZPACE) __nanosleep(ZPACE);
          }
          PROF(19, h_z);
        }
      }
      if (warp < 10) o_load(P, c, w, lane, layer);
    }
    asm volatile("mov.b32 %0,0;" : "=r"(dskip));
  }
}

typedef CUresult (*EncodeFn)(CUtensorMap*, CUtensorMapDataType, cuuint32_t, void*, const cuuint64_t*, const cuuint64_t*,
                             const cuuint32_t*, const cuuint32_t*, CUtensorMapInterleave, CUtensorMapSwizzle,
                             CUtensorMapL2promotion, CUtensorMapFloatOOBfill);

#define POOL 0
#define GOFF 0
static int place_roles(uint8_t* role) {
  int dev = 0, nsm = 0;
  cudaGetDevice(&dev);
  cudaDeviceGetAttribute(&nsm, cudaDevAttrMultiProcessorCount, dev);
  if (nsm < 128 || nsm > 144 || (nsm & 1)) return 0;
  cudaFuncSetAttribute(fused_kernel, cudaFuncAttributeNonPortableClusterSizeAllowed, 1);
  int occ[9] = {0};
  for (int k = 2; k <= 8; ++k) {
    cudaLaunchConfig_t cfg = {};
    cudaLaunchAttribute at[1];
    at[0].id = cudaLaunchAttributeClusterDimension;
    at[0].val.clusterDim.x = 2 * k; at[0].val.clusterDim.y = 1; at[0].val.clusterDim.z = 1;
    cfg.gridDim = dim3(2 * k); cfg.blockDim = dim3(NTHR); cfg.dynamicSmemBytes = SM_TOTAL; cfg.attrs = at; cfg.numAttrs = 1;
    if (cudaOccupancyMaxActiveClusters(&occ[k], fused_kernel, &cfg) != cudaSuccess) { cudaGetLastError(); occ[k] = 0; }
  }
  int n[10];
  n[7] = occ[8]; n[6] = occ[7]; n[5] = occ[6] - 0; n[4] = occ[5];
  n[3] = occ[4] - n[7]; n[1] = occ[2] - n[3] - n[5] - n[7]; n[0] = n[2] = n[1];
  n[8] = occ[3] - n[2] - n[5];
  const int ntpc = nsm / 2;
  int sum = 0;
  bool ok = n[0] > 0 && n[0] <= 8;
  for (int r = 0; r < 9; ++r) { ok = ok && n[r] >= 0 && (r == 0 || n[r] <= n[r - 1]); sum += n[r]; }
  if (!ok || sum > ntpc) { for (int r = 0; r < 9; ++r) n[r] = r < 8 ? 8 : 0; sum = 64; }
  int tp[8][9], cnt[8] = {0}, pool[72], np = 0, id = 0;
  for (int r = 0; r < 9; ++r)
    for (int g = n[0] - n[r]; g < n[0]; ++g) tp[g][cnt[g]++] = id++;
  for (; id < ntpc; ++id) pool[np++] = id;
  int order[72], no = 0;
  for (int g = 0; g < n[0]; ++g) {
    const int full = cnt[g] / 4 * 4;
    for (int k = 0; k < cnt[g]; ++k) { if (k < full) order[no++] = tp[g][k]; else pool[np++] = tp[g][k]; }
  }
  for (int k = 0; k < np; ++k) order[no++] = pool[POOL == 1 ? np - 1 - k : POOL == 2 ? (k + np - 2) % np : k];
  for (int k = 0; k < 144; ++k) role[k] = 255;
  for (int k = 0; k < 64; ++k) { role[2 * order[k]] = (2 * k + GOFF) & 127; role[2 * order[k] + 1] = (2 * k + 1 + GOFF) & 127; }
  return nsm;
}

extern "C" void kernel_launch(void* const* d_in, const int* in_sizes, int n_in, void* d_out, int out_size) {
  (void)in_sizes; (void)n_in; (void)out_size;
  static EncodeFn enc = nullptr;
  static uint8_t role[144];
  static int nsm = 0;
  static void* scratch = nullptr;
  if (!enc) {
    void* fn = nullptr;
    cudaDriverEntryPointQueryResult qr;
    cudaGetDriverEntryPoint("cuTensorMapEncodeTiled", &fn, cudaEnableDefault, &qr);
    enc = (EncodeFn)fn;
    cudaFuncSetAttribute(fused_kernel, cudaFuncAttributeMaxDynamicSharedMemorySize, SM_TOTAL);
    nsm = place_roles(role);
    cudaGetSymbolAddress(&scratch, g_S);
  }
  CUtensorMap mW, mWo;
  {
    cuuint64_t dim[3] = {512, 512, 3}, str[2] = {3072, 1024};
    cuuint32_t box[3] = {64, 64, 3}, es[3] = {1, 1, 1};
    enc(&mW, CU_TENSOR_MAP_DATA_TYPE_BFLOAT16, 3, d_in[10], dim, str, box, es, CU_TENSOR_MAP_INTERLEAVE_NONE,
        CU_TENSOR_MAP_SWIZZLE_128B, CU_TENSOR_MAP_L2_PROMOTION_NONE, CU_TENSOR_MAP_FLOAT_OOB_FILL_NONE);
  }
  {
    cuuint64_t dim[5] = {512, 2, 4, 4, 16}, str[4] = {1024, 8192, 2048, 32768};
    cuuint32_t box[5] = {64, 2, 4, 4, 8}, es[5] = {1, 1, 1, 1, 1};
    enc(&mWo, CU_TENSOR_MAP_DATA_TYPE_BFLOAT16, 5, d_in[11], dim, str, box, es, CU_TENSOR_MAP_INTERLEAVE_NONE,
        CU_TENSOR_MAP_SWIZZLE_128B, CU_TENSOR_MAP_L2_PROMOTION_NONE, CU_TENSOR_MAP_FLOAT_OOB_FILL_NONE);
  }
  Params P;
  P.x0 = (const uint16_t*)d_in[0]; P.Are = (const uint16_t*)d_in[1]; P.Aim = (const uint16_t*)d_in[2];
  P.Bre = (const uint16_t*)d_in[3]; P.Bim = (const uint16_t*)d_in[4]; P.Cre = (const uint16_t*)d_in[5];
  P.Cim = (const uint16_t*)d_in[6]; P.logdt = (const uint16_t*)d_in[7]; P.dskip = (const uint16_t*)d_in[8];
  P.wqkv = (const uint16_t*)d_in[10]; P.wo = (const uint16_t*)d_in[11]; P.out = (uint16_t*)d_out;
  for (int k = 0; k < 144; ++k) P.role[k] = role[k];
  P.by_sm = nsm > 0;
  P.zero = 0;
  P.S = (Scratch*)scratch;
  fused_kernel<<<nsm > 0 ? nsm : 128, NTHR, SM_TOTAL, cudaStreamPerThread>>>(P, mW, mWo);
}
```

```cpp
#include <cuda_runtime.h>
#include <cuda_bf16.h>
#include <cuda.h>
#include <stdint.h>

#define DEV __device__ __forceinline__

#define NCOPY 4
#define NSUB 1
constexpr int NTHR = 512;
constexpr int SPIN_LIMIT = 1 << 22;

constexpr uint32_t SB = 1024;
constexpr uint32_t SM_XA   = SB;
constexpr uint32_t SM_S0   = SM_XA + 16384;
constexpr uint32_t SM_S1   = SM_S0 + 49152;
constexpr uint32_t SM_XB   = SM_S1 + 49152;
constexpr uint32_t SM_R    = SM_XB + 16384;
constexpr uint32_t SM_RES  = SM_R + 65536;
constexpr uint32_t SM_TAP  = SM_RES + 16384;
constexpr int TAP_SZ = 3584;
constexpr uint32_t SM_CS   = SM_TAP + 4 * TAP_SZ;
constexpr uint32_t SM_STAT = SM_CS + 800;
constexpr uint32_t SM_MISC = SM_STAT + 1280;
constexpr uint32_t SM_BAR  = SM_MISC + 512;
constexpr int SM_TOTAL = SM_BAR + 448 - SB;
constexpr int R_U = 512, R_A5 = 5120, R_A3 = 8704, R_B = 11776;
constexpr int T_E = 1536, T_O = T_E + 1602, T_C = 3714;
constexpr uint32_t B_W = SM_BAR, B_X = SM_BAR + 64, B_O = SM_BAR + 128, B_WO = SM_BAR + 256, B_RES = SM_BAR + 264;
constexpr uint32_t B_ST = SM_BAR + 272, B_R = SM_BAR + 288, B_E = SM_BAR + 304;
constexpr uint32_t B_F = SM_BAR + 320, B_G = SM_BAR + 352, B_K = SM_BAR + 376, B_ED = SM_BAR + 384, B_CS = SM_BAR + 400, B_FH = SM_BAR + 416;
constexpr uint32_t CNT = 0x143444CC;
constexpr int NB_WG = 1, NB_T = 5, NB_Q = 10, NB_H = 11, NB_P = 14, NB_RL = 15;

struct Scratch {
  uint32_t F[32 * 32];
  uint4    H[17 * 8 * 256];
  uint4    SR[2][8][512];
  uint4    ST[32 * 16];
  uint4    PS[128 * 64];
  float4   CS[16 * 1536 / 4];
  uint32_t C[10 * 32 * 32];
  uint4    XF[32 * 4096];
  uint4    O[32 * 8 * 512];
  uint4    XG[2][512 * 256];
};
__device__ __align__(1024) Scratch g_S;

struct Params {
  int by_sm;
  uint32_t zero;
  Scratch* S;
  const uint16_t *x0, *Are, *Aim, *Bre, *Bim, *Cre, *Cim, *logdt, *dskip, *wqkv, *wo;
  uint16_t* out;
  uint8_t role[144];
};
#define EVENT(n) do {} while (0)
#define PROFD(slot, name, v) do {} while (0)
#define PROF(slot, name) do {} while (0)
#define PW(x)

DEV uint32_t s2u(const void* p) { return (uint32_t)__cvta_generic_to_shared(p); }
template <class T> DEV T opq(T x) { asm volatile("" : "+r"(x)); return x; }
DEV uint32_t pack2(float lo, float hi) { uint32_t d; asm("cvt.rn.bf16x2.f32 %0,%1,%2;" : "=r"(d) : "f"(hi), "f"(lo)); return d; }
DEV float bflo(uint32_t v) { return __uint_as_float(v << 16); }
DEV float bfhi(uint32_t v) { return __uint_as_float(v & 0xFFFF0000u); }
DEV float bfr(float x) { return bflo(pack2(x, 0.f)); }
DEV uint32_t hadd2(uint32_t a, uint32_t b) { uint32_t d; asm("add.rn.bf16x2 %0,%1,%2;" : "=r"(d) : "r"(a), "r"(b)); return d; }
DEV uint32_t hsub2(uint32_t a, uint32_t b) { uint32_t d; asm("sub.rn.bf16x2 %0,%1,%2;" : "=r"(d) : "r"(a), "r"(b)); return d; }
DEV uint32_t hmul2(uint32_t a, uint32_t b) { uint32_t d; asm("mul.rn.bf16x2 %0,%1,%2;" : "=r"(d) : "r"(a), "r"(b)); return d; }
DEV uint32_t hfma2(uint32_t a, uint32_t b, uint32_t c) { uint32_t d; asm("fma.rn.bf16x2 %0,%1,%2,%3;" : "=r"(d) : "r"(a), "r"(b), "r"(c)); return d; }
DEV uint32_t hmax2(uint32_t a, uint32_t b) { uint32_t d; asm("max.bf16x2 %0,%1,%2;" : "=r"(d) : "r"(a), "r"(b)); return d; }
DEV uint32_t prmt(uint32_t a, uint32_t b, uint32_t s) { uint32_t d; asm("prmt.b32 %0,%1,%2,%3;" : "=r"(d) : "r"(a), "r"(b), "r"(s)); return d; }
DEV uint32_t nz(uint32_t v) { uint32_t d; asm("max.u32 %0,%1,1;" : "=r"(d) : "r"(v)); return d; }
DEV uint32_t tagged(uint32_t v, uint32_t m, uint32_t tag) { uint32_t d; asm("lop3.b32 %0,%1,%2,%3,0xB8;" : "=r"(d) : "r"(v), "r"(m), "r"(tag)); return d; }
DEV uint32_t both(uint32_t a, uint32_t b, uint32_t x) { uint32_t d; asm("lop3.b32 %0,%1,%2,%3,0x42;" : "=r"(d) : "r"(a), "r"(b), "r"(x)); return d; }
DEV uint4 hadd8(const uint4& a, const uint4& b) { return make_uint4(hadd2(a.x, b.x), hadd2(a.y, b.y), hadd2(a.z, b.z), hadd2(a.w, b.w)); }
DEV uint32_t min4(const uint4& v) { return min(min(v.x, v.y), min(v.z, v.w)); }
DEV float rcp(float x) { float y; asm("rcp.approx.ftz.f32 %0,%1;" : "=f"(y) : "f"(x)); return y; }
DEV float sqrt_(float x) { float y; asm("sqrt.approx.ftz.f32 %0,%1;" : "=f"(y) : "f"(x)); return y; }
DEV float rsq(float x) { float y; asm("rsqrt.approx.ftz.f32 %0,%1;" : "=f"(y) : "f"(x)); return y; }
DEV float ex2(float x) { float y; asm("ex2.approx.ftz.f32 %0,%1;" : "=f"(y) : "f"(x)); return y; }

DEV uint4 ldr4(const void* p) { uint4 v; asm volatile("ld.relaxed.gpu.global.v4.u32 {%0,%1,%2,%3},[%4];" : "=r"(v.x), "=r"(v.y), "=r"(v.z), "=r"(v.w) : "l"(p) : "memory"); return v; }
DEV void ldr4_if(uint4& v, const void* p, bool c) {
  asm volatile("{.reg .pred q; setp.ne.u32 q,%5,0; @q ld.relaxed.gpu.global.v4.u32 {%0,%1,%2,%3},[%4];}"
    : "+r"(v.x), "+r"(v.y), "+r"(v.z), "+r"(v.w) : "l"(p), "r"((uint32_t)c) : "memory");
}
DEV uint2 ldr2(const void* p) { uint2 v; asm volatile("ld.relaxed.gpu.global.v2.u32 {%0,%1},[%2];" : "=r"(v.x), "=r"(v.y) : "l"(p) : "memory"); return v; }
DEV uint32_t ldr1(const void* p) { uint32_t v; asm volatile("ld.relaxed.gpu.global.u32 %0,[%1];" : "=r"(v) : "l"(p) : "memory"); return v; }
DEV void str4(void* p, uint32_t a, uint32_t b, uint32_t c, uint32_t d) { asm volatile("st.relaxed.gpu.global.v4.u32 [%0],{%1,%2,%3,%4};" :: "l"(p), "r"(a), "r"(b), "r"(c), "r"(d) : "memory"); }
DEV void str4_if(void* p, uint32_t a, uint32_t b, uint32_t c, uint32_t d, bool q) {
  asm volatile("{.reg .pred q; setp.ne.u32 q,%5,0; @q st.relaxed.gpu.global.v4.u32 [%0],{%1,%2,%3,%4};}" :: "l"(p), "r"(a), "r"(b), "r"(c), "r"(d), "r"((uint32_t)q) : "memory");
}
DEV void str2(void* p, uint32_t a, uint32_t b) { asm volatile("st.relaxed.gpu.global.v2.u32 [%0],{%1,%2};" :: "l"(p), "r"(a), "r"(b) : "memory"); }
DEV void str1(void* p, uint32_t a) { asm volatile("st.relaxed.gpu.global.u32 [%0],%1;" :: "l"(p), "r"(a) : "memory"); }
DEV void stw4(void* p, uint32_t a, uint32_t b, uint32_t c, uint32_t d) { asm volatile("st.global.v4.u32 [%0],{%1,%2,%3,%4};" :: "l"(p), "r"(a), "r"(b), "r"(c), "r"(d) : "memory"); }
DEV uint4 ldnc4(const void* p) { uint4 v; asm volatile("ld.global.nc.v4.u32 {%0,%1,%2,%3},[%4];" : "=r"(v.x), "=r"(v.y), "=r"(v.z), "=r"(v.w) : "l"(p)); return v; }
DEV uint4 ldw4(const void* p) { uint4 v; asm volatile("ld.global.v4.u32 {%0,%1,%2,%3},[%4];" : "=r"(v.x), "=r"(v.y), "=r"(v.z), "=r"(v.w) : "l"(p) : "memory"); return v; }
DEV void cp16(uint32_t d, const void* p) { asm volatile("cp.async.cg.shared.global [%0],[%1],16;" :: "r"(d), "l"(p) : "memory"); }
DEV uint32_t ldnc16(const void* p) { uint32_t v; asm volatile("ld.global.u16 %0,[%1];" : "=r"(v) : "l"(p) : "memory"); return v; }

DEV uint32_t lds1v(uint32_t a) { uint32_t v; asm volatile("ld.volatile.shared.u32 %0,[%1];" : "=r"(v) : "r"(a) : "memory"); return v; }
DEV uint4 lds4v(uint32_t a) { uint4 v; asm volatile("ld.volatile.shared.v4.u32 {%0,%1,%2,%3},[%4];" : "=r"(v.x), "=r"(v.y), "=r"(v.z), "=r"(v.w) : "r"(a) : "memory"); return v; }
DEV uint32_t lds1(uint32_t a) { uint32_t v; asm volatile("ld.shared.u32 %0,[%1];" : "=r"(v) : "r"(a)); return v; }
DEV uint2 lds2(uint32_t a) { uint2 v; asm volatile("ld.shared.v2.u32 {%0,%1},[%2];" : "=r"(v.x), "=r"(v.y) : "r"(a)); return v; }
DEV uint4 lds4(uint32_t a) { uint4 v; asm volatile("ld.shared.v4.u32 {%0,%1,%2,%3},[%4];" : "=r"(v.x), "=r"(v.y), "=r"(v.z), "=r"(v.w) : "r"(a)); return v; }
DEV uint32_t lds16(uint32_t a) { uint32_t v; asm volatile("ld.shared.u16 %0,[%1];" : "=r"(v) : "r"(a)); return v; }
DEV float lds1f(uint32_t a) { float v; asm volatile("ld.shared.f32 %0,[%1];" : "=f"(v) : "r"(a)); return v; }
DEV float2 lds2f(uint32_t a) { float2 v; asm volatile("ld.shared.v2.f32 {%0,%1},[%2];" : "=f"(v.x), "=f"(v.y) : "r"(a)); return v; }
DEV float4 lds4f(uint32_t a) { float4 v; asm volatile("ld.shared.v4.f32 {%0,%1,%2,%3},[%4];" : "=f"(v.x), "=f"(v.y), "=f"(v.z), "=f"(v.w) : "r"(a)); return v; }
DEV void sts1(uint32_t a, uint32_t v) { asm volatile("st.shared.u32 [%0],%1;" :: "r"(a), "r"(v) : "memory"); }
DEV void sts16(uint32_t a, uint32_t v) { asm volatile("{.reg .b16 h; cvt.u16.u32 h,%1; st.shared.u16 [%0],h;}" :: "r"(a), "r"(v) : "memory"); }
DEV void sts2f(uint32_t a, float x, float y) { asm volatile("st.shared.v2.f32 [%0],{%1,%2};" :: "r"(a), "f"(x), "f"(y) : "memory"); }
DEV void sts4f(uint32_t a, float x, float y, float z, float w) { asm volatile("st.shared.v4.f32 [%0],{%1,%2,%3,%4};" :: "r"(a), "f"(x), "f"(y), "f"(z), "f"(w) : "memory"); }
DEV void sts4(uint32_t a, uint32_t x, uint32_t y, uint32_t z, uint32_t w) { asm volatile("st.shared.v4.u32 [%0],{%1,%2,%3,%4};" :: "r"(a), "r"(x), "r"(y), "r"(z), "r"(w) : "memory"); }
DEV void sts4_if(uint32_t a, uint32_t x, uint32_t y, uint32_t z, uint32_t w, bool c) {
  asm volatile("{.reg .pred q; setp.ne.u32 q,%5,0; @q st.shared.v4.u32 [%0],{%1,%2,%3,%4};}" :: "r"(a), "r"(x), "r"(y), "r"(z), "r"(w), "r"((uint32_t)c) : "memory");
}
DEV void sts4z_if(uint32_t a, bool c) { asm volatile("{.reg .pred q; setp.ne.u32 q,%1,0; @q st.shared.v4.u32 [%0],{%2,%2,%2,%2};}" :: "r"(a), "r"((uint32_t)c), "r"(0) : "memory"); }

DEV void ldsm4t(uint32_t& r0, uint32_t& r1, uint32_t& r2, uint32_t& r3, uint32_t a) { asm volatile("ldmatrix.sync.aligned.m8n8.x4.trans.shared.b16 {%0,%1,%2,%3},[%4];" : "=r"(r0), "=r"(r1), "=r"(r2), "=r"(r3) : "r"(a) : "memory"); }
DEV void stsm4(uint32_t a, uint32_t r0, uint32_t r1, uint32_t r2, uint32_t r3) { asm volatile("stmatrix.sync.aligned.m8n8.x4.shared.b16 [%0],{%1,%2,%3,%4};" :: "r"(a), "r"(r0), "r"(r1), "r"(r2), "r"(r3) : "memory"); }
DEV void stsm2(uint32_t a, uint32_t r0, uint32_t r1) { asm volatile("stmatrix.sync.aligned.m8n8.x2.shared.b16 [%0],{%1,%2};" :: "r"(a), "r"(r0), "r"(r1) : "memory"); }
DEV void stsm4t(uint32_t a, uint32_t r0, uint32_t r1, uint32_t r2, uint32_t r3) { asm volatile("stmatrix.sync.aligned.m8n8.x4.trans.shared.b16 [%0],{%1,%2,%3,%4};" :: "r"(a), "r"(r0), "r"(r1), "r"(r2), "r"(r3) : "memory"); }
DEV uint32_t movm(uint32_t a) { uint32_t d; asm volatile("movmatrix.sync.aligned.m8n8.trans.b16 %0,%1;" : "=r"(d) : "r"(a)); return d; }
DEV void mma16(float (&d)[4], uint32_t a0, uint32_t a1, uint32_t a2, uint32_t a3, uint32_t b0, uint32_t b1) {
  asm volatile("mma.sync.aligned.m16n8k16.row.col.f32.bf16.bf16.f32 {%0,%1,%2,%3},{%4,%5,%6,%7},{%8,%9},{%0,%1,%2,%3};"
    : "+f"(d[0]), "+f"(d[1]), "+f"(d[2]), "+f"(d[3]) : "r"(a0), "r"(a1), "r"(a2), "r"(a3), "r"(b0), "r"(b1));
}
DEV void mma16z(float (&d)[4], uint32_t a0, uint32_t a1, uint32_t a2, uint32_t a3, uint32_t b0, uint32_t b1) {
  asm volatile("mma.sync.aligned.m16n8k16.row.col.f32.bf16.bf16.f32 {%0,%1,%2,%3},{%4,%5,%6,%7},{%8,%9},{%10,%10,%10,%10};"
    : "=f"(d[0]), "=f"(d[1]), "=f"(d[2]), "=f"(d[3]) : "r"(a0), "r"(a1), "r"(a2), "r"(a3), "r"(b0), "r"(b1), "f"(0.f));
}
DEV void mma8z(float (&d)[4], uint32_t a0, uint32_t a1, uint32_t b0) {
  asm volatile("mma.sync.aligned.m16n8k8.row.col.f32.bf16.bf16.f32 {%0,%1,%2,%3},{%4,%5},{%6},{%7,%7,%7,%7};"
    : "=f"(d[0]), "=f"(d[1]), "=f"(d[2]), "=f"(d[3]) : "r"(a0), "r"(a1), "r"(b0), "f"(0.f));
}
DEV void mma8(float (&d)[4], uint32_t a0, uint32_t a1, uint32_t b0) {
  asm volatile("mma.sync.aligned.m16n8k8.row.col.f32.bf16.bf16.f32 {%0,%1,%2,%3},{%4,%5},{%6},{%0,%1,%2,%3};"
    : "+f"(d[0]), "+f"(d[1]), "+f"(d[2]), "+f"(d[3]) : "r"(a0), "r"(a1), "r"(b0));
}

DEV void bar_sync(int id, int n) { asm volatile("bar.sync %0,%1;" :: "r"(id), "r"(n) : "memory"); }
DEV void bar_arrive(int id, int n) { asm volatile("bar.arrive %0,%1;" :: "r"(id), "r"(n) : "memory"); }
DEV void bar_sync_if(int id, int n, int c) { asm volatile("{.reg .pred q; setp.ne.s32 q,%2,0; @q bar.sync %0,%1;}" :: "r"(id), "r"(n), "r"(c) : "memory"); }
DEV void bar_arrive_if(int id, int n, int c) { asm volatile("{.reg .pred q; setp.ne.s32 q,%2,0; @q bar.arrive %0,%1;}" :: "r"(id), "r"(n), "r"(c) : "memory"); }
DEV bool bar_any(int id, int n, bool c) {
  uint32_t r; asm volatile("{.reg .pred p,q; setp.ne.u32 q,%3,0; bar.red.or.pred p,%1,%2,q; selp.u32 %0,1,0,p;}" : "=r"(r) : "r"(id), "r"(n), "r"((uint32_t)c) : "memory");
  return __any_sync(0xffffffffu, r);
}
DEV void fence_async_glob() { asm volatile("fence.proxy.async.global;" ::: "memory"); }
DEV void fence_async_smem() { asm volatile("fence.proxy.async.shared::cta;" ::: "memory"); }
DEV void fence_gpu() { asm volatile("fence.acq_rel.gpu;" ::: "memory"); }
DEV void mbar_wait(uint32_t b, uint32_t ph) {
  asm volatile("{\n.reg .pred p;\nW: mbarrier.try_wait.parity.shared::cta.b64 p,[%0],%1;\n@!p bra W;\n}" :: "r"(b), "r"(ph) : "memory");
}
DEV bool mbar_test(uint32_t b, uint32_t ph) {
  uint32_t r; asm volatile("{.reg .pred p; mbarrier.test_wait.parity.shared::cta.b64 p,[%1],%2; selp.u32 %0,1,0,p;}" : "=r"(r) : "r"(b), "r"(ph) : "memory");
  return __all_sync(0xffffffffu, r);
}
DEV uint32_t mbar_test2(uint32_t b, uint32_t ph) {
  uint32_t r; asm volatile("{.reg .pred p,q; mbarrier.test_wait.parity.shared::cta.b64 p,[%1],%2; mbarrier.test_wait.parity.shared::cta.b64 q,[%1+8],%2;\n"
                           "and.pred p,p,q; selp.u32 %0,1,0,p;}" : "=r"(r) : "r"(b), "r"(ph) : "memory");
  return r;
}
DEV void spin_guard(int it) { asm volatile("{.reg .pred p; setp.gt.s32 p,%0,%1; @p trap;}" :: "r"(it), "n"(SPIN_LIMIT)); }
DEV uint32_t here(uint32_t zero) {
  uint32_t d; asm volatile("mov.u32 %0,%%clock;" : "=r"(d) :: "memory"); return d & zero;
}
DEV int lane_here(uint32_t zero) {
  uint32_t d; asm volatile("mov.u32 %0,%%laneid;" : "=r"(d)); return d | here(zero);
}
DEV void delay(uint32_t n) { const uint32_t t0 = clock(); while ((uint32_t)clock() - t0 < n); __syncwarp(); }
DEV void poll(const uint32_t* p, uint32_t n) {
  for (int it = 0; !__all_sync(0xffffffffu, ldr1(p) >= n); ++it) spin_guard(it);
}
DEV void cnt_add(const Params& P, int n, int c, int lane) { asm volatile("{.reg .pred p; setp.lt.s32 p,%1,%2; @p red.relaxed.gpu.global.add.u32 [%0],1;}" :: "l"(P.S->C + (32 * (NSUB * lane + c % NSUB) + n * 1024)), "r"(lane), "n"(NCOPY) : "memory"); }
DEV uint32_t* cnt_at(const Params& P, int n, int c, int lane) { return P.S->C + (32 * (NSUB * lane + c % NSUB) + n * 1024); }
DEV void cnt_add(uint32_t* p, uint32_t one, bool q) { asm volatile("{.reg .pred p; setp.ne.u32 p,%2,0; @p red.relaxed.gpu.global.add.u32 [%0],%1;}" :: "l"(p), "r"(one), "r"((uint32_t)q) : "memory"); }
DEV void cnt_wait(const Params& P, int n, int c, int lane) { poll(P.S->C + (32 * (NSUB * (c / (128 / NCOPY)) + lane % NSUB) + n * 1024), 128 / NSUB); }
DEV void mbar_init1(uint32_t b, int n) { asm volatile("{.reg .pred p; elect.sync _|p,0xffffffff; @p mbarrier.init.shared::cta.b64 [%0],%1;}" :: "r"(b), "r"(n) : "memory"); }
DEV void mbar_arrive1(uint32_t b) { asm volatile("{.reg .pred p; elect.sync _|p,0xffffffff; @p mbarrier.arrive.shared::cta.b64 _,[%0];}" :: "r"(b) : "memory"); }
DEV void mbar_arrive1_if(uint32_t b, int c) {
  asm volatile("{.reg .pred p,q; setp.ne.s32 q,%1,0; elect.sync _|p,0xffffffff; and.pred p,p,q; @p mbarrier.arrive.shared::cta.b64 _,[%0];}" :: "r"(b), "r"(c) : "memory");
}
DEV void mbar_expect1(uint32_t b, int bytes) { asm volatile("{.reg .pred p; elect.sync _|p,0xffffffff; @p mbarrier.arrive.expect_tx.shared::cta.b64 _,[%0],%1;}" :: "r"(b), "r"(bytes) : "memory"); }
DEV void flag_set1(uint32_t* q) { asm volatile("{.reg .pred p; elect.sync _|p,0xffffffff; @p st.relaxed.gpu.global.u32 [%0],1;}" :: "l"(q) : "memory"); }
DEV void tma3(uint32_t dst, const CUtensorMap* m, int c0, int c1, uint32_t bar) {
  asm volatile("{.reg .pred p; elect.sync _|p,0xffffffff;\n"
    "@p cp.async.bulk.tensor.3d.shared::cluster.global.mbarrier::complete_tx::bytes [%0],[%1,{%2,%3,%5}],[%4];}"
    :: "r"(dst), "l"(m), "r"(c0), "r"(c1), "r"(bar), "r"(0) : "memory");
}
DEV void tma5(uint32_t dst, const CUtensorMap* m, int c0, int c4, uint32_t bar) {
  asm volatile("{.reg .pred p; elect.sync _|p,0xffffffff;\n"
    "@p cp.async.bulk.tensor.5d.shared::cluster.global.mbarrier::complete_tx::bytes [%0],[%1,{%2,%5,%5,%5,%3}],[%4];}"
    :: "r"(dst), "l"(m), "r"(c0), "r"(c4), "r"(bar), "r"(0) : "memory");
}
DEV void bulk(uint32_t dst, const void* src, int bytes, uint32_t bar) {
  asm volatile("{.reg .pred p; elect.sync _|p,0xffffffff;\n@p cp.async.bulk.shared::cluster.global.mbarrier::complete_tx::bytes [%0],[%1],%2,[%3];}" :: "r"(dst), "l"(src), "r"(bytes), "r"(bar) : "memory");
}
DEV void bulk_store(void* dst, uint32_t src, int bytes) {
  asm volatile("{.reg .pred p; elect.sync _|p,0xffffffff;\n@p cp.async.bulk.global.shared::cta.bulk_group [%0],[%1],%2;}" :: "l"(dst), "r"(src), "r"(bytes) : "memory");
}
DEV void l2_prefetch(const void* src, int bytes) {
  asm volatile("{.reg .pred p; elect.sync _|p,0xffffffff;\n@p cp.async.bulk.prefetch.L2.global [%0],%1;}" :: "l"(src), "r"(bytes) : "memory");
}

DEV uint64_t mkdesc(uint32_t addr, uint32_t lbo, uint32_t sbo, uint32_t swz) {
  return (uint64_t)((addr >> 4) | ((lbo >> 4) << 16)) | ((uint64_t)((sbo >> 4) | (swz << 30)) << 32);
}
DEV void wg_fence() { asm volatile("wgmma.fence.sync.aligned;" ::: "memory"); }
DEV void wg_commit() { asm volatile("wgmma.commit_group.sync.aligned;" ::: "memory"); }
template <int N> DEV void wg_wait() { asm volatile("wgmma.wait_group.sync.aligned %0;" :: "n"(N) : "memory"); }
template <int N> DEV void zerov(float (&d)[N]) {
#pragma unroll
  for (int i = 0; i < N; ++i) asm volatile("mov.b32 %0,0;" : "=f"(d[i]));
}
template <int N> DEV void undef(float (&d)[N]) {
#pragma unroll
  for (int i = 0; i < N; ++i) asm volatile("" : "=f"(d[i]));
}
#define R4(d, o) "+f"(d[o]), "+f"(d[o + 1]), "+f"(d[o + 2]), "+f"(d[o + 3])
#define R8(d, o) R4(d, o), R4(d, o + 4)
#define R16(d, o) R8(d, o), R8(d, o + 8)
#define R32(d, o) R16(d, o), R16(d, o + 16)
#define L0 "%0,%1,%2,%3,%4,%5,%6,%7,%8,%9,"
#define L10(a) "%" #a "0,%" #a "1,%" #a "2,%" #a "3,%" #a "4,%" #a "5,%" #a "6,%" #a "7,%" #a "8,%" #a "9,"
#define WG_HEAD(pr, n) "{.reg .pred p; setp.ne.s32 p,%" #pr ",0;\nwgmma.mma_async.sync.aligned.m64n" #n "k16.f32.bf16.bf16 {"
DEV void wg_rs64k(float (&d)[32], const uint32_t (&a)[4], uint64_t db, int acc) {
  asm volatile(WG_HEAD(37, 64) L0 L10(1) L10(2) "%30,%31},{%32,%33,%34,%35},%36,p,1,1,0;}"
    : R32(d, 0) : "r"(a[0]), "r"(a[1]), "r"(a[2]), "r"(a[3]), "l"(db), "r"(acc));
}
DEV void wg_rs48t(float (&d)[24], const uint32_t (&a)[4], uint64_t db, int acc) {
  asm volatile(WG_HEAD(29, 48) L0 L10(1) "%20,%21,%22,%23},{%24,%25,%26,%27},%28,p,1,1,1;}"
    : R16(d, 0), R8(d, 16) : "r"(a[0]), "r"(a[1]), "r"(a[2]), "r"(a[3]), "l"(db), "r"(acc));
}
DEV void wg_rs32t(float (&d)[16], const uint32_t (&a)[4], uint64_t db, int acc) {
  asm volatile(WG_HEAD(21, 32) L0 "%10,%11,%12,%13,%14,%15},{%16,%17,%18,%19},%20,p,1,1,1;}"
    : R16(d, 0) : "r"(a[0]), "r"(a[1]), "r"(a[2]), "r"(a[3]), "l"(db), "r"(acc));
}
DEV void wg_ss48(float (&d)[24], uint64_t da, uint64_t db, int acc) {
  asm volatile(WG_HEAD(26, 48) L0 L10(1) "%20,%21,%22,%23},%24,%25,p,1,1,1,1;}" : R16(d, 0), R8(d, 16) : "l"(da), "l"(db), "r"(acc));
}
DEV void wg_ss64(float (&d)[32], uint64_t da, uint64_t db, int acc) {
  asm volatile(WG_HEAD(34, 64) L0 L10(1) L10(2) "%30,%31},%32,%33,p,1,1,0,1;}" : R32(d, 0) : "l"(da), "l"(db), "r"(acc));
}
DEV void wg_ss192(float (&d)[96], uint64_t da, uint64_t db, int acc) {
  asm volatile(WG_HEAD(98, 192) L0 L10(1) L10(2) L10(3) L10(4) L10(5) L10(6) L10(7) L10(8) "%90,%91,%92,%93,%94,%95},%96,%97,p,1,1,1,1;}"
    : R32(d, 0), R32(d, 32), R32(d, 64) : "l"(da), "l"(db), "r"(acc));
}

DEV void wg_rs192t(float (&d)[96], const uint32_t (&a)[4], uint64_t db) {
  asm volatile("wgmma.mma_async.sync.aligned.m64n192k16.f32.bf16.bf16 {" L0 L10(1) L10(2) L10(3) L10(4) L10(5) L10(6) L10(7) L10(8) "%90,%91,%92,%93,%94,%95},{%96,%97,%98,%99},%100,1,1,1,1;"
    : R32(d, 0), R32(d, 32), R32(d, 64) : "r"(a[0]), "r"(a[1]), "r"(a[2]), "r"(a[3]), "l"(db));
}

DEV float ln_sd(float s, float q, float& m) {
  m = s * (1.f / 512.f);
  return bfr(sqrt_(bfr(bfr(fmaxf(q * (1.f / 512.f) - m * m, 0.f)) + 1e-5f)));
}
DEV float4 gram(const uint32_t (&w)[8][2], int g, uint32_t zero) {
  float s[4], q[4][4];
  const uint32_t o0 = 0x3F803F80u | zero, o1 = 0x3F803F80u ^ zero;
#pragma unroll
  for (int j = 0; j < 8; ++j) {
#pragma unroll
    for (int h = 0; h < 2; ++h) { if (j < 2) mma8z(q[2 * j + h], w[j][0], w[j][1], w[j][h]); else mma8(q[2 * (j & 1) + h], w[j][0], w[j][1], w[j][h]); }
    if (j == 1) mma16z(s, w[0][0], w[0][1], w[1][0], w[1][1], o0, o1);
    else if (j & 1) mma16(s, w[j - 1][0], w[j - 1][1], w[j][0], w[j][1], o0, o1);
  }
  const bool od = g & 1;
  return make_float4(s[0], od ? q[0][1] + q[2][1] : q[0][0] + q[2][0], s[2], od ? q[1][3] + q[3][3] : q[1][2] + q[3][2]);
}
DEV void keep(uint32_t v, uint32_t zero) {
  asm volatile("{.reg .pred p; setp.ne.u32 p,%1,0; @p st.shared.u32 [%0],%0;}" :: "r"(v), "r"(zero) : "memory");
}
DEV void keep(const void* v, uint32_t zero) { asm volatile("{.reg .pred p; setp.ne.u32 p,%1,0; @p st.global.u32 [%0],%1;}" :: "l"(v), "r"(zero) : "memory"); }
struct XgAddr { uint32_t a, b; uint4* dst; };
template <bool FRAG> DEV XgAddr xg_addr(uint4* dst, uint32_t stg, int wp, int lane, uint32_t zero) {
  const int t = lane & 3, r = 4 * wp + (lane >> 3);
  XgAddr x = {stg + t * (FRAG ? 256 : 1024) + ((wp ^ t) * 32) + (lane >> 2) * 4,
              stg + r * 128 + (((lane & 7) ^ (2 * (((r >> 1) ^ (r >> 3)) & 3))) * 16), dst + (r * 256 + (lane & 7))};
  keep(x.a, zero); keep(x.b, zero); keep(x.dst, zero);
  return x;
}
template <bool FRAG> DEV void xg_put(const XgAddr& x, const uint32_t (&w)[8][2]) {
#pragma unroll
  for (int n = 0; n < 8; ++n) {
    const uint32_t b = (x.a ^ ((n & 3) * 32)) + (FRAG ? n * 1024 : (n >> 2) * 4096 + (n & 3) * 256);
    sts1(b, prmt(w[n][0], w[n][1], 0x5410)); sts1(b + 128, prmt(w[n][0], w[n][1], 0x7632));
  }
}
DEV void xg_store(const XgAddr& x) {
#pragma unroll
  for (int k = 0; k < 4; ++k) {
    const uint4 v = lds4((x.b ^ ((k & 1) * 64)) + k * 2048);
    str4(x.dst + k * 4096, nz(v.x), v.y, v.z, v.w);
  }
}
template <int N, int M> DEV void fold(float (&v)[M], int lane, int bit) {
  const bool b = lane & bit;
#pragma unroll
  for (int k = 0; k < N; ++k) { const float sn = b ? v[k] : v[k + N], kp = b ? v[k + N] : v[k]; v[k] = kp + __shfl_xor_sync(0xffffffffu, sn, bit); }
}
DEV void refetch(uint32_t dst, const uint4* src, int half, int e, int w) {
#pragma unroll 1
  for (int r = 0; r < 2; ++r) {
    if (w == 0) { mbar_expect1(B_R + 8 * e, half); bulk(dst + r * half, src + r * (half >> 4), half, B_R + 8 * e); }
    mbar_wait(B_R + 8 * e, r);
    bar_sync(NB_WG + e, 128);
  }
}
DEV uint32_t kvslot(int cg, int pos) { return (pos & 2 ? SM_XA : SM_S1) + (cg < 4 ? 5 : 2) * 8192 + (pos & 1) * 4096; }
DEV uint32_t xstage(int q, int e) { return ((q + 1) & 2) ? SM_R + ((q & 2) + e) * 16384 : e ? SM_XB : SM_XA; }
DEV void cmul(float& orr, float& oi, float ar, float ai, float br, float bi) {
  float r = ar * br - ai * bi, i = ar * bi + ai * br; orr = r; oi = i;
}
DEV void cexp_(float al, float bt, float s, float& er, float& ei) {
  float mag = ex2(al * s), ph = bt * s;
  ph -= rintf(ph);
  float ang = ph * 6.283185307179586f;
  er = mag * __cosf(ang); ei = mag * __sinf(ang);
}

#define KS 2048
DEV void put8(uint32_t a, const float (&r)[8], const float (&i)[8]) {
  sts4(a, pack2(r[0], r[1]), pack2(r[2], r[3]), pack2(r[4], r[5]), pack2(r[6], r[7]));
  sts4(a + 1024, pack2(i[0], i[1]), pack2(i[2], i[3]), pack2(i[4], i[5]), pack2(i[6], i[7]));
}
DEV void tables(const uint32_t (&pv)[8], int k4, int w, int lane) {
  PW(4 * k4 + w)
  [[maybe_unused]] const int layer = 0;
  const float dt = bfr(__expf(bflo(pv[6])));
  const float al = dt * bflo(pv[0]) * 1.4426950408889634f, bt = dt * bflo(pv[1]) * 0.15915494309189535f;
  float qr[8], qi[8], yr[8], yi[8];
  cmul(qr[0], qi[0], bflo(pv[4]), bflo(pv[5]), dt * bflo(pv[2]), dt * bflo(pv[3]));
  PROFD(2, a_par, __float_as_uint(qr[0] + al + bt));
  float e1r, e1i, eMr, eMi, eLr, eLi;
  cexp_(al, bt, 1.f, e1r, e1i); cexp_(al, -bt, 8.f, yr[1], yi[1]); cexp_(al, -bt, 64.f, eMr, eMi); cexp_(al, bt, 256.f, eLr, eLi);
  const uint32_t ad = SB + k4 * 32768 + (w & 1) * 512 + lane * 16, am = ad + (w >> 1) * KS, an = ad + (8 + 3 * (w >> 1)) * KS;
  yr[0] = 1.f; yi[0] = 0.f;
#pragma unroll
  for (int k = 1; k < 8; ++k) {
    cmul(qr[k], qi[k], qr[k - 1], qi[k - 1], e1r, e1i);
    if (k > 1) cmul(yr[k], yi[k], yr[k - 1], yi[k - 1], yr[1], yi[1]);
  }
  put8(an, qr, qi);
#pragma unroll
  for (int j = 0; j < 4; ++j) {
    put8(am + j * 2 * KS, yr, yi);
#pragma unroll
    for (int k = 0; k < 8; ++k) {
      if (j == 0 && k == 0) { yr[0] = eMr; yi[0] = eMi; } else if (j < 3) cmul(yr[k], yi[k], yr[k], yi[k], eMr, eMi);
    }
    if (j == 0) {
#pragma unroll
      for (int k = 0; k < 8; ++k) { const int o = k < 4 ? 2 * k : k < 6 ? 2 * k - 8 : k - 2; cmul(qr[k], qi[k], qr[o], qi[o], eLr, eLi); }
      put8(an + KS, qr, qi);
    } else if (j == 1) {
#pragma unroll
      for (int k = 0; k < 5; ++k) cmul(qr[k], qi[k], qr[k ? k - 1 : 6], qi[k ? k - 1 : 6], eLr, eLi);
      put8(an + 2 * KS, qr, qi);
    }
  }
  PROF(3, a_tab);
}

DEV void sts16_if(uint32_t a, uint32_t v, bool c) { asm volatile("{.reg .pred q; .reg .b16 h; setp.ne.u32 q,%2,0; cvt.u16.u32 h,%1; @q st.shared.u16 [%0],h;}" :: "r"(a), "r"(v), "r"((uint32_t)c) : "memory"); }
DEV void sts1_if(uint32_t a, uint32_t v, bool c) { asm volatile("{.reg .pred q; setp.ne.u32 q,%2,0; @q st.shared.u32 [%0],%1;}" :: "r"(a), "r"(v), "r"((uint32_t)c) : "memory"); }
DEV void taps(uint32_t dskip, int k4, int w, int lane) {
  PW(4 * k4 + w)
  [[maybe_unused]] const int layer = 0;
  fence_async_smem();
  bar_sync((k4 & 1) ? NB_WG + k4 : NB_Q, (k4 & 1) ? 128 : 448);
  float d[24];
  undef(d);
  const uint64_t da = mkdesc(SB + k4 * 32768, 1024, KS, 0);
  wg_fence();
#pragma unroll
  for (int j = 0; j < 8; ++j) wg_ss48(d, da + j * 8, da + KS / 2 + j * 8, j);
  wg_commit();
  const int b = 8 * w + (lane >> 2), t = lane & 3, id = 32 * w + lane;
  constexpr int DO = T_O - T_E;
  const uint32_t te = SM_TAP + k4 * TAP_SZ + T_E, a0 = te - 16 * b - 4 * t;
  const uint32_t a1 = a0 - 512 - 4 * t, a2 = te - 2 * (511 + b) - 64 * t, a3 = te + (T_C - T_E) - 2 * (127 + b) - 128 * t;
  wg_wait<0>();
  PROF(4, a_mma);
  {
    const uint32_t v = pack2(d[1] + d[15], d[0] + d[14] + (id ? 0.f : bflo(dskip)));
    sts1(a0 + DO - 2, v); sts16(a0 - 2, v); sts16(a0, v >> 16);
  }
  {
    const uint32_t v = pack2(d[5] + d[19], d[4] + d[18]), u = prmt(v, v, 0x3232);
    const bool lo = t < 2, k512 = id == 2;
    sts1_if(k512 ? te - 2 * 512 : a1, u, (lo && id) || k512);
    sts1_if(k512 ? te - 2 * 514 : a1 - 4, k512 ? u : v, lo || k512);
    sts1_if(k512 ? te + DO - 2 * 513 : a1 + DO - 2, u, lo || k512);
    sts16(lo ? a1 + DO - 4 : a2 + DO - 194, v);
    sts16(lo ? (id ? a1 + DO + 2 : a1) : k512 ? te + DO - 2 * 511 : a2 + DO, u);
    sts16_if(a2 - 194, v, !lo);
    sts16_if(k512 ? te + DO - 2 * 514 : a2, u, !lo);
  }
  {
    const uint32_t v = pack2(d[8] + d[22], d[9] + d[23]);
    sts16_if(id ? a3 : te - 2 * 639, v, t < 2 || id == 2);
    sts16_if(a3 - 64, v >> 16, t < 2);
    sts16_if(te + DO - 2 * 639, v, id == 0);
  }
  bar_sync(NB_WG + k4, 128);
  mbar_arrive1_if(B_K, w == 0);
}

DEV uint32_t cpy(uint32_t v, uint32_t id) {
  uint32_t d; asm volatile("prmt.b32 %0,%1,%1,%2;" : "=r"(d) : "r"(v), "r"(id)); return d;
}
DEV uint32_t uoff(int s) { return (s ^ ((s >> 3) & 3)) * 16; }
template <bool FULL> DEV void boxes(const uint32_t (&u)[10], uint32_t a, uint32_t a9, uint32_t a7, uint32_t (&pv)[4]) {
  uint32_t v[8], p[8], x[4], y[4];
#pragma unroll
  for (int j = 0; j < 8; ++j) { v[j] = prmt(u[j], u[j + 1], 0x5432); p[j] = hadd2(u[j], v[j]); }
#pragma unroll
  for (int j = 0; j < 4; ++j) { x[j] = hadd2(hadd2(p[j + 1], p[j + 2]), u[j + 3]); y[j] = hadd2(v[j + 3], p[j + 4]); }
  sts4(a + R_A5, x[0], x[1], x[2], x[3]);
  sts4(a + R_A3, y[0], y[1], y[2], y[3]);
  if (FULL) {
#pragma unroll
    for (int j = 0; j < 4; ++j) { x[j] = hadd2(x[j], hadd2(v[j], v[j + 3])); y[j] = hadd2(x[j], hadd2(u[j], u[j + 4])); pv[j] = p[j + 4]; }
    sts4(a7, x[0], x[1], x[2], x[3]);
    sts4(a9, y[0], y[1], y[2], y[3]);
  }
}
DEV uint32_t shfl_up(uint32_t v, int d) { uint32_t r; asm volatile("shfl.sync.up.b32 %0,%1,%2,0,0xffffffff;" : "=r"(r) : "r"(v), "r"(d) : "memory"); return r; }
DEV void halo(uint32_t (&u)[10], uint32_t a, uint32_t b, int lane) {
  asm volatile("{.reg .pred p,q; setp.eq.s32 p,%8,0; setp.lt.s32 q,%8,2;\n@p ld.shared.v4.u32 {%2,%3,%4,%5},[%6];\n@q ld.shared.v2.u32 {%0,%1},[%7];}"
    : "+r"(u[0]), "+r"(u[1]), "+r"(u[2]), "+r"(u[3]), "+r"(u[4]), "+r"(u[5]) : "r"(a), "r"(b), "r"(lane));
}
#define ROT 2
#define G1 -1
#define G2 0
#define G3 1
#define TPS 0x9135
#define GMASK ((G1 >= 0 ? 2 : 0) | (G2 >= 0 ? 4 : 0) | (G3 >= 0 ? 8 : 0))
#define GATE1(g, n, p) if (g >= 0 && (g & 3) == p) mbar_arrive1_if(B_G + 8 * n, k4 == (g >> 2));
#define GATE(p) GATE1(G1, 0, p) GATE1(G2, 1, p) GATE1(G3, 2, p)
#define TMASK(p) (((TPS & 15) == p) | ((((TPS >> 4) & 15) == p) << 1) | ((((TPS >> 8) & 15) == p) << 2) | ((((TPS >> 12) & 15) == p) << 3))
#define TURN(p) if (TMASK(p) == 15) bar_arrive(NB_T + 1 + k4, 256); else if (TMASK(p)) { if ((TMASK(p) >> k4) & 1) bar_arrive(NB_T + 1 + k4, 256); }
DEV void w_load(const CUtensorMap* mW, int cg, int h) {
  mbar_expect1(B_W + 8 * h, 24576);
  tma3(SM_S0 + (h & 3) * 24576, mW, 64 * cg, 64 * h, B_W + 8 * h);
}

DEV void conv(const Params& P, const CUtensorMap* mW, int c, int k4, int w, int layer) {
  const uint32_t zero = P.zero;
  PW(4 * k4 + w)
  int lane = lane_here(zero);
  const int g = lane >> 2, t = lane & 3, v = w ^ (ROT * (k4 & 1)), tid = 32 * v + lane;
  const uint32_t reg = SM_R + k4 * 16384, tp = SM_TAP + k4 * TAP_SZ;
  const uint32_t g0 = tp + ((g & 1) ? T_O : T_E) + 2 * (2 * t - g);
  uint32_t F[18][4], U[20], qc[4][4];
#define LO(q, a) q[0] = lds1(a); q[2] = lds1(a + 16);
#define HI(q, a) q[1] = lds1(a - 128); q[3] = lds1(a - 112);
  {
    const uint32_t ga = g0 - 32 * (w & 1) - 576 * (w >> 1), g2 = tp + T_C - 258 - 32 * w + 4 * (t - g);
    F[0][2] = lds1(ga + 48);
#pragma unroll
    for (int j = 0; j < 8; ++j) { F[j][0] = lds1(ga + 32 - 32 * j); F[j][1] = lds1(ga + 16 - 32 * j); }
#pragma unroll
    for (int j = 0; j < 20; ++j) U[j] = lds1(ga - 224 - 16 * j);
#pragma unroll
    for (int j = 0; j < 4; ++j) { LO(qc[j], g2 + 32 * j) HI(qc[j], g2 + 32 * j) }
  }
  if (layer) { mbar_wait(B_ED, 0); mbar_wait(B_ED + 8, 0); }
  sts4z_if(reg + lane * 16 + (w ? w * 3584 + 1024 : 0), w < 3);
  PROF(5, a_pre);
  if (k4 == 3 && w == 3) {
    mbar_wait(B_E, layer);
    mbar_wait(B_K, 0);
#pragma unroll
    for (int h = 0; h < 4; ++h) w_load(mW, c & 7, h);
  }
  const uint32_t bo = reg + R_B + tid * 16 + (v >> 1) * 1056, be = tid == 127 ? reg + R_B + 1024 : bo + (tid == 63 ? 2112 : 1056);
  const uint32_t a9 = (lane & 1) ? be : bo, a7 = (lane & 1) ? bo : be, ua = reg + R_U + uoff(tid);
  const uint32_t h1 = reg + R_U + v * 512 - 64, h2 = h1 + 24 - 16 * lane;
  keep(a9 & a7 & ua & h2, zero);
  mbar_wait(k4 && ((GMASK >> k4) & 1) ? B_G - 8 + 8 * k4 : B_E, layer);
  PROF(6, a_x);
  uint4 x[2];
  uint32_t pv[4];
  {
    uint4 s[4];
    uint32_t u[2][10];
#pragma unroll
    for (int z = 0; z < 2; ++z) { x[z] = lds4(reg + R_B + tid * 16 + z * 2048); s[2 * z] = lds4(SM_RES + tid * 16 + z * 2048); s[2 * z + 1] = lds4(SM_RES + tid * 16 + z * 2048 + 4096); }
    for (int it = 0;; ++it) {
      const uint32_t m = min(min(min(x[0].x, min(s[0].x, s[0].z)), min(s[1].x, s[1].z)), min(min(x[1].x, min(s[2].x, s[2].z)), min(s[3].x, s[3].z)));
      if (__builtin_expect(__all_sync(0xffffffffu, m != 0u), 1)) break;
      EVENT(16 + layer * 4 + k4);
      const int o = tid | here(zero);
#pragma unroll
      for (int z = 0; z < 2; ++z) x[z] = ldr4(&P.S->XG[layer][(128 * k4 + c) * 256 + o] + z * 128);
#pragma unroll
      for (int z = 0; z < 4; ++z) {
        s[z] = ldr4(&P.S->SR[layer][c >> 4][o] + ((z >> 1) * 128 + (z & 1) * 256));
        sts4(SM_RES + tid * 16 + (z >> 1) * 2048 + (z & 1) * 4096, s[z].x, s[z].y, s[z].z, s[z].w);
      }
      spin_guard(it);
    }
#pragma unroll
    for (int z = 0; z < 2; ++z) {
      u[z][6] = hmul2(hsub2(x[z].x, s[2 * z].y), s[2 * z].x); u[z][7] = hmul2(hsub2(x[z].y, s[2 * z].w), s[2 * z].z);
      u[z][8] = hmul2(hsub2(x[z].z, s[2 * z + 1].y), s[2 * z + 1].x); u[z][9] = hmul2(hsub2(x[z].w, s[2 * z + 1].w), s[2 * z + 1].z);
      sts4(ua + z * 2048, u[z][6], u[z][7], u[z][8], u[z][9]);
    }
    u[1][0] = 0; u[1][1] = s[3].x; u[1][2] = s[2].x; u[1][3] = s[2].y; u[1][4] = s[2].z; u[1][5] = s[2].w;
    if (v < 2) {
#pragma unroll
      for (int j = 1; j < 6; ++j) u[1][j] = shfl_up(u[1][j < 2 ? 8 + j : 4 + j], j < 2 ? 2 : 1);
    }
#pragma unroll
    for (int j = 0; j < 6; ++j) u[0][j] = shfl_up(u[0][j < 2 ? 8 + j : 4 + j], j < 2 ? 2 : 1);
    bar_sync(NB_WG + k4, 128);
    GATE(0)
    PROF(7, a_u);
    halo(u[0], h1, h2, lane);
    halo(u[1], h1 + 2048, h2 + 2048, lane + 16 * (v & 2));
    sts4z_if(reg + R_B + 1040, tid == 0);
    boxes<true>(u[0], reg + tid * 16, a9, a7, pv);
    if (v < 2) boxes<false>(u[1], reg + tid * 16 + 2048, 0, 0, pv);
  }
  GATE(1)
  fence_async_smem();
  if (k4 == 3 && w < 3) {
    const uint32_t src = SM_RES + 8192 + w * 2048, f = (w >> 1) - 1;
#pragma unroll
    for (int z = 0; z < 4; ++z) sts4(src + lane * 16 + z * 512, f, f, f, f);
    fence_async_smem();
    __syncwarp();
    if (w < 2) {
#pragma unroll
      for (int z = 0; z < 4; ++z) bulk_store(&P.S->O[((c >> 3) * 16 + w * 8 + (c & 7)) * 512] + z * 128, src, 2048);
    } else {
#pragma unroll
      for (int z = 0; z < 2; ++z) {
        bulk_store(&P.S->H[(c + 8) * 256] + z * 128, src, 2048);
        bulk_store(P.S->F + ((c >> 3) * 64 + 4 * (c & 7)) + z * 32, src, 16);
      }
      bulk_store(&P.S->PS[c * 64], src, 1024);
      bulk_store(&P.S->ST[c * 4], src, 64);
      if (c < 5) bulk_store(P.S->C + (c + 5 - 5 * layer) * 1024, src, 128 * NCOPY * NSUB);
    }
    asm volatile("cp.async.bulk.commit_group;" ::: "memory");
  }
  const uint32_t id = opq(0x3210u);
#pragma unroll
  for (int j = 0; j < 8; ++j) { F[j][3] = cpy(F[j][0], id); if (j) F[j][2] = cpy(F[j - 1][1], id); }
  PROF(8, a_box);
  bar_sync(NB_T + k4, k4 ? 256 : 128);
  PROF(9, a_turn);
  float acc[32], f1[24], f3[16];
  uint32_t qa[4][4], qb[4][4], fp[4];
  const uint64_t db = mkdesc(reg + R_U, 16, 512, 2) + 2;
#define STEP(mm) wg_fence(); mm; wg_commit(); wg_wait<2>();
#define D(j) STEP(wg_rs64k(acc, F[j], db - 2 * j, j))
#define C(j) STEP(wg_rs32t(f3, qc[j], mkdesc(reg + R_B, 128, 1040, 0) + 16 * j, j))
#define NIL(q) { const uint32_t z = here(zero); q[2][1] = cpy(z, 0); q[2][3] = cpy(z, 1); q[3][1] = cpy(z, 2); q[3][3] = cpy(z, 3); }
#define X(j) F[j][0] = cpy(U[2 * j - 16], ix); F[j][1] = cpy(U[2 * j - 15], ix); F[j][3] = cpy(F[j][0], ix); F[j][2] = cpy(F[j - 1][1], ix);
#define PIN ix = 0x3210u | here(zero);
  const uint32_t g1 = g0 - 2 * 576 - 16 * w;
  const uint64_t d1 = mkdesc(reg + R_A5, 128, 512, 0);
  constexpr int O3 = (R_A3 - R_A5) / 16;
  uint32_t ix;
  undef(acc);
  D(0) TURN(0) D(1) D(2) D(3) D(4) D(5)
  undef(f3);
  C(0) C(1) TURN(1) PIN X(8) X(9) C(2) C(3) LO(qa[0], g1)
  D(6) HI(qa[0], g1) PIN X(10) D(7) LO(qa[1], g1 + 32) X(11)
  fp[0] = pack2(f3[0], f3[1]); fp[1] = pack2(f3[4], f3[5]); fp[2] = pack2(f3[8] + f3[2], f3[9] + f3[3]); fp[3] = pack2(f3[12] + f3[6], f3[13] + f3[7]);
  D(8) HI(qa[1], g1 + 32) PIN ix |= fp[0] & fp[1] & fp[2] & fp[3] & zero; X(12) D(9) LO(qa[2], g1 - 64) X(13)
  D(10) TURN(2) LO(qa[3], g1 - 32) X(14) D(11) LO(qb[0], g1 - 192) PIN X(15) D(12) HI(qb[0], g1 - 192) X(16)
  D(13) LO(qb[1], g1 - 160) X(17) D(14) TURN(3) HI(qb[1], g1 - 160) NIL(qa)
  D(15) LO(qb[2], g1 - 256) D(16) LO(qb[3], g1 - 224) NIL(qb) D(17) TURN(4)
  PROF(10, a_den);
  undef(f1);
  wg_fence();
#pragma unroll
  for (int j = 0; j < 4; ++j) wg_rs48t(f1, qa[j], d1 + 16 * (j & 1) - 32 * (j >> 1), j);
  wg_commit();
  wg_wait<1>();
  TURN(5)
  wg_fence();
#pragma unroll
  for (int j = 0; j < 4; ++j) wg_rs48t(f1, qb[j], d1 + O3 + 16 * (j & 1) - 32 * (j >> 1), 1);
  wg_commit();
  TURN(6)
  lane = lane_here(zero);
  bar_sync(NB_WG + k4, 128);
  {
    const int p = (lane + 9 * (w >> 1)) & 31;
    const uint32_t ya = reg + ((w >> 1) ? R_B : R_U) + p * 64 + (((2 * (w & 1)) ^ ((p >> 1) & 3)) * 16), up = p < lane ? 2048 : 0;
#pragma unroll
    for (int z = 0; z < 4; ++z) {
      const float* a = acc + 16 * (z >> 1) + 2 * (z & 1);
      stsm4t((ya + (up ^ ((z >> 1) * 2048))) ^ ((z & 1) * 16), pack2(a[0], a[1]), pack2(a[4], a[5]), pack2(a[8], a[9]), pack2(a[12], a[13]));
    }
  }
  asm volatile("cp.async.bulk.wait_group 0;" ::: "memory");
  const uint32_t fa = reg + R_A5 + (lane >> 3) * 512 + w * 128 + (lane & 7) * 16;
  const uint32_t fc = reg + R_A3 + uoff(64 * (lane >> 4) + 16 * w + 2 * (lane & 7) + 1 - ((lane >> 3) & 1));
  uint32_t k1024 = lds16(tp + T_E - 2 * 639 + (fa & fc & zero));
  wg_wait<0>();
  GATE(2)
  PROF(11, a_far);
  bar_sync(NB_WG + k4, 128);
  stsm4(fc, fp[0], fp[1], fp[2], fp[3]);
  stsm4(fa, pack2(f1[0], f1[1]), pack2(f1[4], f1[5]), pack2(f1[8] + f1[2], f1[9] + f1[3]), pack2(f1[12] + f1[6], f1[13] + f1[7]));
  stsm2(fa + 2048, pack2(f1[16] + f1[10], f1[17] + f1[11]), pack2(f1[20] + f1[14], f1[21] + f1[15]));
  {
    const int o = 32 * v + lane;
    const uint32_t a = reg + uoff(o), b = reg + R_A5 + o * 16;
    uint4 y[2] = {hadd8(lds4(a + R_U), lds4(o >= 36 ? a + R_B : reg)), hadd8(lds4(a + R_U + 2048), lds4(a + R_B + 2048))};
    bar_sync(NB_WG + k4, 128);
    TURN(7)
    PROF(12, a_sts);
    const uint4 f = lds4(v >= 2 ? b - 1024 : reg), f2 = lds4(b + 1024);
    uint4 h = lds4(a + R_A3);
    const int e0 = (o >> 3) * 8192 + (128 * k4 + c) * 16 + (((o & 4) + ((o >> 1) & 1)) ^ (c & 7)) * 2 + (o & 1);
    const uint32_t me = (e0 & 3) == ((c >> 1) & 3), m0 = me & ~c, m1 = me & c, tag = 1 - layer;
    uint32_t* cp = cnt_at(P, 1 + 5 * layer + k4, c, lane);
    keep(cp, zero);
    k1024 = prmt(k1024, k1024, 0x1010);
    h = make_uint4(hfma2(pv[0], k1024, h.x), hfma2(pv[1], k1024, h.y), hfma2(pv[2], k1024, h.z), hfma2(pv[3], k1024, h.w));
    y[0] = hadd8(y[0], f); y[1] = hadd8(y[1], hadd8(f2, h));
    cnt_add(cp, 1 | (y[0].x & y[1].x & zero), (o ^ 96) < NCOPY);
#pragma unroll
    for (int z = 0; z < 2; ++z) {
      const uint4 r = hadd8(x[z], y[z]);
      str2((uint2*)P.S->XF + e0 + z * 131072, tagged(prmt(r.x, r.y, 0x5410), m0, tag), tagged(prmt(r.z, r.w, 0x5410), m1, tag));
      str2((uint2*)P.S->XF + (e0 ^ 4) + z * 131072, tagged(prmt(r.x, r.y, 0x7632), m0, tag), tagged(prmt(r.z, r.w, 0x7632), m1, tag));
    }
  }
  TURN(9)
  GATE(3)
  PROF(13, a_out);
}

#define WGATE 1
#define FH 1
#define QPIN 1
#define XORD 1
DEV void x_load(const Params& P, int c, int q, int layer) {
#pragma unroll
  for (int z = 0; z < 2; ++z) {
    const int e = z ^ (XORD && q == 3 && !(c & 4));
    mbar_expect1(B_X + 16 * q + 8 * e, 16384);
    bulk(xstage(q, e), P.S->XF + ((2 * (c >> 3) + 1 - e) * 4096 + q * 1024), 16384, B_X + 16 * q + 8 * e);
  }
}

DEV void means(uint32_t (&m)[4], int row, int lane, int layer, uint32_t zero) {
  mbar_wait(B_CS, 0);
  mbar_wait(B_ST, layer);
  const uint32_t a = SM_MISC + row * 4 + (lane & 28), k = (lane & 3) ? 0u : ~0u;
  m[0] = lds1(a) & k; m[1] = lds1(a + 32) & k; m[2] = m[0] & zero; m[3] = m[1] & zero;
}

DEV void attn_phase(const Params& P, int c, int e, int w, int lane, int layer) {
  PW(4 * e + w)
  const int cg = c & 7, J = 2 * (c >> 3) + 1 - e;
  float acc[96];
  zerov(acc);
  uint32_t m[4] = {0, 0, 0, 0};
#pragma unroll 1
  for (int q = 0;; ++q) {
    const uint64_t da = mkdesc(xstage(q, e), 16, 1024, 1), db = mkdesc(SM_S0 + (q & 1) * 49152, 8192, 1024, 1);
    const uint32_t wr = mbar_test2(B_W + 16 * q, layer), xa = xstage(q, e) + w * 4096 + lane * 132;
    mbar_wait(B_X + 16 * q + 8 * e, layer);
    for (int it = 0;; ++it) {
      const uint32_t ok = both(lds1(xa), lds1(xa ^ 32), layer) & both(lds1(xa ^ 64), lds1(xa ^ 96), layer);
      if (__all_sync(0xffffffffu, ok & 1)) break;
      EVENT(8 * layer + 2 * q + e);
#pragma unroll 1
      for (int j = 0; j < 8; ++j) cp16(xstage(q, e) + w * 4096 + j * 512 + lane * 16, P.S->XF + (J * 4096 + q * 1024 + w * 256 + j * 32 + lane));
      asm volatile("cp.async.wait_all;" ::: "memory");
      fence_async_smem();
      __syncwarp();
      spin_guard(it);
    }
    bool all = __all_sync(0xffffffffu, wr);
    if (q == 0 && e && w == 0) {
      bar_sync(NB_H, 256);
      cnt_wait(P, 2 + 5 * layer, c, lane);
      x_load(P, c, 1, layer);
      PROF(27, m_xi);
    }
    if (q == 3 && e) means(m, 16 * w, lane, layer, P.zero);
    if (!all) { mbar_wait(B_W + 16 * q, layer); all = mbar_test(B_W + 16 * q + 8, layer); }
    bar_sync(e ? NB_Q : q ? NB_T : NB_T + 4, 256);
    PROF(14 + q, m_q);
    wg_fence();
#pragma unroll
    for (int k = 0; k < 8; ++k) {
      if (k == 4) { wg_commit(); if (!all) mbar_wait(B_W + 16 * q + 8, layer); wg_fence(); }
      wg_ss192(acc, da + k * 128, db + (k >> 2) * 1536 + (k & 3) * 128, 1);
    }
    wg_commit();
    if (q == 3) break;
    bar_arrive(e ? NB_T : NB_Q, 256);
    if (FH) { wg_wait<1>(); mbar_arrive1_if(B_FH + 8 * q, e && q < 2); }
    wg_wait<0>();
    mbar_arrive1(B_F + 8 * q);
  }
  const int pos = 2 - 2 * e + (w >> 1);
  uint4* h = P.S->H + ((c + 8) * 256 + (w & 1) * 128 + lane);
  const uint32_t kw = kvslot(cg, pos + 1) + (w & 1) * 2048 + lane * 16;
  {
    if (!e) means(m, 64 + 16 * w, lane, layer, P.zero);
    PROF(28, m_sub);
    wg_fence();
    wg_rs192t(acc, m, mkdesc(SM_CS, 0, 32, 0));
    wg_commit();
    bar_arrive_if(NB_Q, 256, !e);
    keep(h, kw & P.zero);
    mbar_wait(B_F + 16, layer);
    wg_wait<0>();
    mbar_arrive1(B_F + 24);
  }
  PROF(18, m_qkv);
  uint32_t Q[4][4], K[4][3][2], V[4][3][2];
  uint32_t pin = P.zero;
#pragma unroll
  for (int z = 0; z < 4; ++z) {
    V[z][1][0] = pack2(acc[64 + 8 * z], acc[65 + 8 * z]); V[z][1][1] = pack2(acc[68 + 8 * z], acc[69 + 8 * z]);
    K[z][1][0] = pack2(acc[32 + 8 * z], acc[33 + 8 * z]); K[z][1][1] = pack2(acc[36 + 8 * z], acc[37 + 8 * z]);
    pin &= V[z][1][0] & V[z][1][1];
    K[z][2][0] = nz(pack2(acc[34 + 8 * z], acc[35 + 8 * z])); K[z][2][1] = pack2(acc[38 + 8 * z], acc[39 + 8 * z]);
    V[z][2][0] = pack2(acc[66 + 8 * z], acc[67 + 8 * z]); V[z][2][1] = pack2(acc[70 + 8 * z], acc[71 + 8 * z]);
    str4_if(h + z * 32, K[z][2][0], K[z][2][1], V[z][2][0], V[z][2][1], pos == 3);
  }
#pragma unroll
  for (int z = 0; z < 8; ++z) V[z >> 1][2][z & 1] = movm(z < 7 ? V[z >> 1][2][z & 1] : V[3][2][1] | pin);
  if (pos == 0) mbar_wait(B_F + 24, layer);
#pragma unroll
  for (int z = 0; z < 4; ++z) sts4_if(kw + z * 512, K[z][2][0], K[z][2][1], V[z][2][0], V[z][2][1], pos < 3);
  bar_arrive(NB_H + pos + 1, 128);
  PROF(19, m_kv);
  lane |= here(P.zero);
  int g = lane >> 2, t = lane & 3;
  const uint32_t ra = SM_STAT + 256 + (32 - 32 * e + 8 * w) * 16, ob = e ? SM_S1 : SM_XA;
  const float r0 = lds1f(ra + (g >> 1) * 16 + (g & 1) * 4), r1 = lds1f(ra + 64 + (g >> 1) * 16 + (g & 1) * 4);
  const uint4 k1 = lds4(ra + 16 * t), k2 = lds4(ra + 64 + 16 * t);
#pragma unroll
  for (int z = 0; z < 8; ++z) {
    V[z >> 1][1][z & 1] = movm(V[z >> 1][1][z & 1]);
    Q[z >> 1][2 * (z & 1)] = pack2(acc[4 * z], acc[4 * z + 1]);
    Q[z >> 1][2 * (z & 1) + 1] = pack2(acc[4 * z + 2], acc[4 * z + 3]);
    pin &= Q[z >> 1][2 * (z & 1)] & Q[z >> 1][2 * (z & 1) + 1];
  }
  {
    const bool p0 = 2 * t > g, p1 = 2 * t + 1 > g, first = c < 8 && pos == 0;
    const uint32_t M = (p0 ? 0xFFFFu : 0u) | (p1 ? 0xFFFF0000u : 0u);
    const float sc0 = r0 * (0.25f * 1.4426950408889634f), sc1 = r1 * (0.25f * 1.4426950408889634f);
    const float sk2 = __uint_as_float(p0 ? k1.x : k2.x) * sc1, sk3 = __uint_as_float(p1 ? k1.y : k2.y) * sc1;
    const int oo = cg * 512 + (2 * (w & 2) + (w & 1)) * 64 + (lane ^ (g >> 1));
    uint4* O = P.S->O + (J * 4096 + oo);
    keep(oo, pin & M & __float_as_uint(sk2) & __float_as_uint(sk3) & __float_as_uint(sc0));
    mbar_wait(B_F + 24, layer);
    float L[4][4];
#pragma unroll
    for (int z = 0; z < 4; ++z) {
      float S[4];
      mma16z(L[z], Q[z][0], Q[z][1], Q[z][2], Q[z][3], K[z][1][0], K[z][1][1]);
      mma16z(S, Q[z][0], Q[z][1], Q[z][2], Q[z][3], K[z][2][0], K[z][2][1]);
      L[z][2] = (p0 ? L[z][2] : S[2]) * sk2; L[z][3] = (p1 ? L[z][3] : S[3]) * sk3;
      if (QPIN) pin &= __float_as_uint(L[z][2]) & __float_as_uint(L[z][3]);
    }
    bar_sync(NB_H + pos + pin, pos ? 128 : 160);
    const uint4 k0 = lds4(ra - 192 + 16 * t);
#pragma unroll
    for (int z = 0; z < 4; ++z) {
      const uint4 hv = lds4(kvslot(cg, pos) + (w & 1) * 2048 + lane * 16 + z * 512);
      K[z][0][0] = hv.x; K[z][0][1] = hv.y; V[z][0][0] = hv.z; V[z][0][1] = hv.w;
    }
    PROF(20, m_halo);
    const float sk0 = __uint_as_float(p0 ? k0.x : k1.x) * sc0, sk1 = __uint_as_float(p1 ? k0.y : k1.y) * sc0;
    const uint32_t rm[4] = {k0.z & M, k1.z & ~M, k1.z & M, k2.z & ~M}, s0 = k0.w | P.zero, s1 = k1.w | P.zero;
#pragma unroll
    for (int h2 = 0; h2 < 2; ++h2) {
      uint32_t A[2], B[2], mx[2];
#pragma unroll
      for (int z = 0; z < 2; ++z) {
        const int h = 2 * h2 + z;
        float S[4];
        mma16z(S, Q[h][0], Q[h][1], Q[h][2], Q[h][3], K[h][0][0], K[h][0][1]);
        if (first) { S[0] = __uint_as_float(0xFF800000u); S[1] = S[0]; }
        A[z] = pack2((p0 ? S[0] : L[h][0]) * sk0, L[h][2]);
        B[z] = pack2((p1 ? S[1] : L[h][1]) * sk1, L[h][3]);
      }
#pragma unroll
      for (int z = 0; z < 2; ++z) mx[z] = hmax2(A[z], B[z]);
#pragma unroll
      for (int z = 0; z < 2; ++z) mx[z] = hmax2(mx[z], __shfl_xor_sync(0xffffffffu, mx[z], 1));
#pragma unroll
      for (int z = 0; z < 2; ++z) mx[z] = hmax2(mx[z], __shfl_xor_sync(0xffffffffu, mx[z], 2));
      float Oa[2][3][4];
#pragma unroll
      for (int z = 0; z < 2; ++z) {
        const int h = 2 * h2 + z;
        const uint32_t a = hsub2(A[z], mx[z]), b = hsub2(B[z], mx[z]);
        const uint32_t w0 = pack2(ex2(bflo(a)), ex2(bflo(b))), w1 = pack2(ex2(bfhi(a)), ex2(bfhi(b)));
        const uint32_t u0 = hmul2(w0, rm[0]), u1 = hmul2(w0, rm[1]), u2 = hmul2(w1, rm[2]), u3 = hmul2(w1, rm[3]);
        const uint32_t z0 = w0 & P.zero, z1 = w1 & P.zero;
        mma16z(Oa[z][2], u0, z0, u1, u2, s0, s1);
#pragma unroll
        for (int d = 0; d < 2; ++d) mma16z(Oa[z][d], u0, z0, u1, u2, V[h][0][d], V[h][1][d]);
        mma8(Oa[z][2], z1, u3, k2.w);
#pragma unroll
        for (int d = 0; d < 2; ++d) mma8(Oa[z][d], z1, u3, V[h][2][d]);
      }
#pragma unroll
      for (int r = 0; r < 4; r += 2) {
        const float i0 = rcp(Oa[0][2][r]), i1 = rcp(Oa[1][2][r]);
        const uint32_t o0 = pack2(Oa[0][0][r] * i0, Oa[0][0][r + 1] * i0), o1 = pack2(Oa[0][1][r] * i0, Oa[0][1][r + 1] * i0);
        const uint32_t o2 = pack2(Oa[1][0][r] * i1, Oa[1][0][r + 1] * i1), o3 = pack2(Oa[1][1][r] * i1, Oa[1][1][r + 1] * i1);
        str4(O + h2 * 32 + r * 64, o0, o1, o2, o3);
        sts4(ob + oo * 16 + h2 * 512 + r * 1024, o0, o1, o2, o3);
      }
    }
  }
  bar_arrive(NB_T + 1 + e, 160);
  fence_async_smem();
  PROF(21, m_att);
  lane = lane_here(P.zero); g = lane >> 2; t = lane & 3;
  uint32_t res[8][2];
  mbar_wait(B_RES, layer);
  {
    const uint32_t a = SM_RES + e * 8192 + (lane >> 4) * 1024 + (lane & 7) * 128 + (((2 * (w & 2) + ((lane >> 2) & 2) + (w & 1)) ^ (lane & 7)) * 16);
#pragma unroll
    for (int j = 0; j < 8; j += 2) ldsm4t(res[j][0], res[j][1], res[j + 1][0], res[j + 1][1], a + j * 1024);
  }
  PROF(26, m_res);
  if (WGATE) bar_sync(NB_T, 256); else bar_sync(NB_WG + e, 128);
  XgAddr xa = xg_addr<true>(P.S->XG[1] + (64 * cg * 256 + 8 * J), ob, w, lane, P.zero);
  uint4* ps = &P.S->PS[((4 * J + w) * 8 + cg) * 8 + g];
  keep(ps, P.zero);
  if (layer) {
    xa.a = ob + w * 2048 + (lane & 15) * 128 + (((lane >> 4) ^ (lane & 7)) * 16);
    xa.b = ob + w * 2048 + (lane >> 3) * 128 + (((lane & 7) ^ (lane >> 3)) * 16);
    xa.dst = (uint4*)P.out + ((64 * J + 16 * w + 2 * (lane >> 3)) * 64 + 8 * cg + (lane & 7));
  }
  uint32_t y[8][2];
#pragma unroll 1
  for (int it = 0;; ++it) {
    float ac[32];
#pragma unroll
    for (int j = 0; j < 16; ++j) {
      asm volatile("shl.b32 %0,%1,16;" : "=f"(ac[2 * j]) : "r"(res[j >> 1][j & 1]));
      asm volatile("and.b32 %0,%1,0xFFFF0000;" : "=f"(ac[2 * j + 1]) : "r"(res[j >> 1][j & 1]));
    }
#pragma unroll 1
    for (int n = 0; n < 8; ++n) {
      const int s = n == 0 ? cg : n - (n <= cg);
      mbar_wait(n ? B_O + 64 * e + 8 * s : B_WO, layer);
      if (n == 1) PROF(22, m_o1);
      if (n == 7) PROF(23, m_o7);
      const uint64_t da = mkdesc(ob + s * 8192, 16, 1024, 2), db = mkdesc(SM_R + s * 8192, 16, 1024, 1);
      wg_fence();
#pragma unroll
      for (int k = 0; k < 4; ++k) wg_ss64(ac, da + (k >> 1) * 32 + (k & 1) * 2, db + k * 128, 1);
      wg_commit();
    }
    wg_wait<0>();
    const bool bad = ac[0] != ac[0] || ac[2] != ac[2];
#pragma unroll
    for (int j = 0; j < 8; ++j) {
      y[j][0] = pack2(ac[4 * j], ac[4 * j + 1]); y[j][1] = pack2(ac[4 * j + 2], ac[4 * j + 3]);
    }
    if (!bar_any(NB_WG + e, 128, bad) || it == 16) break;
    EVENT(24 + 2 * layer + e);
    refetch(ob, P.S->O + J * 4096, 32768, e, w);
  }
  PROF(24, m_wo);
  if (layer == 0) {
    const float4 s = gram(y, g, P.zero);
    xg_put<true>(xa, y);
    str4_if(ps, nz(__float_as_uint(s.x)), __float_as_uint(s.y), __float_as_uint(s.z), __float_as_uint(s.w), t == (g >> 1));
    mbar_arrive1(B_ED + 8 * e);
    bar_sync(NB_WG + e, 128);
    xg_store(xa);
    bar_arrive(NB_T + 3, 288);
  } else {
#pragma unroll
    for (int j = 0; j < 8; j += 2) stsm4(xa.a ^ (j * 16), y[j][0], y[j][1], y[j + 1][0], y[j + 1][1]);
    __syncwarp();
#pragma unroll
    for (int k = 0; k < 4; ++k) {
      const uint4 v = lds4((xa.b ^ ((k & 1) * 64)) + k * 512);
      stw4(xa.dst + ((k & 1) * 8 + (k >> 1)) * 64, v.x, v.y, v.z, v.w);
    }
  }
  PROF(25, m_epi);
}

#define HDELAY 300
#define ODELAY 200
#define PDELAY 0
#define FDELAY 300
#define CSP 0
#define CSU 4
#define PHOLD 0
#define XDEL 300
#define WOQ 2
#define H5 1
#define SRDELAY 350
#define ZPACE 20

DEV void o_load(const Params& P, int c, int e, int lane, int layer) {
  PW(8 + e)
  const int J = 2 * (c >> 3) + 1 - e;
#pragma unroll 1
  for (int s = 0; s < 8; ++s) mbar_expect1(B_O + 64 * e + 8 * s, s == (c & 7) ? 0 : 8192);
  bar_sync(NB_T + 1 + e, 160);
  flag_set1(P.S->F + (J * 32 + 4 * (c & 7)));
  if (ODELAY) delay(ODELAY);
  PROF(26, a_go);
  poll(P.S->F + (J * 32 + (lane & 28)), 1);
  PROF(25, h_seen);
  bar_sync_if(NB_Q, 64, e);
#pragma unroll 1
  for (int s = 0; s < 8; ++s)
    if (s != (c & 7)) bulk((e ? SM_S1 : SM_XA) + s * 8192, P.S->O + (J * 4096 + s * 512), 8192, B_O + 64 * e + 8 * s);
  bar_arrive_if(NB_Q, 64, !e);
  PROF(28, a_o);
}

DEV void stats(const Params& P, int c, int w, int lane, int layer) {
  PW(12 + w)
  lane = opq(lane);
  const int r = (lane & 6) + ((lane >> 3) & 1), k = (2 * (c & 3) + (lane & 1)) ^ r, e = 1 - ((c >> 2) & 1);
  const uint32_t o = (32 * w + 8 * (lane >> 4) + r) * 128 + k * 16;
  const uint32_t mk = ((k & 1) == (r >> 2)) << (r & 3), tag = 1 - layer;
  float v[16];
#pragma unroll
  for (int z = 0; z < 16; ++z) v[z] = 0.f;
#pragma unroll 1
  for (int q = 0; q < 4; ++q) {
    mbar_wait(B_X + 16 * q + 8 * e, layer);
    PROF(19 + q, s_l);
    uint4 x, y;
    for (int it = 0;; ++it) {
      x = lds4v(xstage(q, e) + o); y = lds4v(xstage(q, e) + o + 2048);
      const uint32_t bad = (((x.x ^ tag) | (y.x ^ tag)) & mk) | (((x.y ^ tag) | (y.y ^ tag)) & (mk >> 1)) |
                           (((x.z ^ tag) | (y.z ^ tag)) & (mk >> 2)) | (((x.w ^ tag) | (y.w ^ tag)) & (mk >> 3));
      if (!__any_sync(0xffffffffu, bad & 1)) break;
      spin_guard(it);
    }
    mbar_arrive1(B_F + 8 * q);
    const uint32_t ws[8] = {x.x, x.y, x.z, x.w, y.x, y.y, y.z, y.w};
#pragma unroll
    for (int z = 0; z < 8; ++z) {
      const float lo = bflo(ws[z]), hi = bfhi(ws[z]);
      float* u = v + 4 * (z & 3);
      u[0] += lo; u[1] += lo * lo; u[2] += hi; u[3] += hi * hi;
    }
  }
  PROFD(14, s_part, __float_as_uint(v[0]));
  fold<8>(v, lane, 16); fold<4>(v, lane, 8); fold<2>(v, lane, 4); fold<1>(v, lane, 2);
  PROFD(16, s_fold, __float_as_uint(v[0]));
  if (w) {
    sts1(SM_MISC - 128 + w * 128 + lane * 4, __float_as_uint(v[0]));
    bar_arrive(NB_P, 128);
  } else {
    bar_sync(NB_P, 128);
    v[0] += lds1f(SM_MISC + lane * 4) + lds1f(SM_MISC + 128 + lane * 4) + lds1f(SM_MISC + 256 + lane * 4);
    float m;
    const float sd = ln_sd(v[0], __shfl_xor_sync(0xffffffffu, v[0], 2), m);
    if (!(lane & 2)) str1((uint32_t*)P.S->ST + (16 * c + 8 * (lane & 1) + (lane >> 2)), pack2(m, sd));
    sts4(SM_STAT - 32 + min(lane, 17) * 16, 0x3F800000u, 0x3F800000u, 0x3F803F80u, 0x3F803F80u);
    fence_async_smem();
    PROF(17, s_pub);
    uint4 s;
    for (int it = 0;; ++it) {
      s = ldr4(P.S->ST + ((c >> 3) * 32 + lane));
      if (__all_sync(0xffffffffu, min4(s) != 0u)) break;
      spin_guard(it);
    }
    PROF(18, s_seen);
    const float r0 = rcp(bfhi(s.x)), r1 = rcp(bfhi(s.y)), r2 = rcp(bfhi(s.z)), r3 = rcp(bfhi(s.w));
    const uint32_t sg = 0x80008000u;
    sts4(SM_MISC + lane * 16, prmt(s.x, s.x, 0x1010) ^ sg, prmt(s.y, s.y, 0x1010) ^ sg, prmt(s.z, s.z, 0x1010) ^ sg, prmt(s.w, s.w, 0x1010) ^ sg);
    sts4(SM_STAT + 256 + lane * 32, __float_as_uint(r0), __float_as_uint(r1), pack2(r0, r1), prmt(s.x, s.y, 0x7632));
    sts4(SM_STAT + 272 + lane * 32, __float_as_uint(r2), __float_as_uint(r3), pack2(r2, r3), prmt(s.z, s.w, 0x7632));
    __syncwarp();
    mbar_arrive1(B_ST);
  }
  PROF(15, s_stat);
  if (w == 1) {
    mbar_wait(B_ST, layer);
    if (c >= 8) {
      uint2 s;
      for (int it = 0;; ++it) {
        s = ldr2((const uint2*)P.S->ST + ((c >> 3) * 64 - 12 + (lane & 11)));
        if (__all_sync(0xffffffffu, min(s.x, s.y) != 0u)) break;
        spin_guard(it);
      }
      const float r0 = rcp(bfhi(s.x)), r1 = rcp(bfhi(s.y));
      sts4(SM_STAT + 64 + (lane & 11) * 16, __float_as_uint(r0), __float_as_uint(r1), pack2(r0, r1), prmt(s.x, s.y, 0x7632));
    }
    bar_arrive(NB_H, 160);
  }
  if (w >= 2) {
    const uint4* h = P.S->H + (c * 256 + (w & 1) * 128 + lane);
    uint4 hv[4];
#pragma unroll
    for (int z = 0; z < 4; ++z) hv[z] = make_uint4(0, 0, 0, 0);
    bar_sync(NB_RL, 128);
    PROFD(26, s_hb, lds1v(SM_MISC));
    delay(HDELAY);
    for (int it = 0; c >= 8; ++it) {
#pragma unroll
      for (int z = 0; z < 4; ++z) hv[z] = ldr4(h + z * 32);
      if (__all_sync(0xffffffffu, min(min(hv[0].x, hv[1].x), min(hv[2].x, hv[3].x)) != 0u)) break;
      spin_guard(it);
    }
    mbar_wait(B_F + 24, layer);
#pragma unroll
    for (int z = 0; z < 4; ++z) sts4(kvslot(c & 7, 0) + (w & 1) * 2048 + lane * 16 + z * 512, hv[z].x, hv[z].y, movm(hv[z].z), movm(hv[z].w));
    bar_arrive(NB_H, 160);
    PROF(25, s_halo);
  }
}

DEV void finalize(const Params& P, int c, int lane, int layer) {
  PW(12)
  uint2* so = (uint2*)P.S->SR[layer] + ((lane >> 3) * 1024 + (lane & 2) * 256 + 4 * c + ((lane >> 1) & 2) + (lane & 1));
  const uint4* ps = &P.S->PS[c * 64 + lane];
  keep(so, P.zero); keep(ps, P.zero);
  uint4 a, b;
  if (layer == 0) {
    bar_sync(NB_P, 256);
    a = lds4(SM_RES + 8192 + lane * 16); b = lds4(SM_RES + 8704 + lane * 16);
  } else {
    mbar_wait(B_ED + 8 - 2 * (c & 4), 0);
    delay(FDELAY);
    for (int it = 0;; ++it) {
      a = ldr4(ps); b = ldr4(ps + 32);
      if (__all_sync(0xffffffffu, min(a.x, b.x) != 0u)) break;
      spin_guard(it);
    }
  }
  float z[4] = {__uint_as_float(a.x) + __uint_as_float(b.x), __uint_as_float(a.y) + __uint_as_float(b.y),
                __uint_as_float(a.z) + __uint_as_float(b.z), __uint_as_float(a.w) + __uint_as_float(b.w)};
#pragma unroll
  for (int o = 8; o < 32; o <<= 1)
#pragma unroll
    for (int k = 0; k < 4; ++k) z[k] += __shfl_xor_sync(0xffffffffu, z[k], o);
  const float m0 = z[0] * (1.f / 512.f), m1 = z[2] * (1.f / 512.f);
  const float r0 = rsq(fmaxf(z[1] * (1.f / 512.f) - m0 * m0, 0.f) + 1e-5f), r1 = rsq(fmaxf(z[3] * (1.f / 512.f) - m1 * m1, 0.f) + 1e-5f);
  const uint32_t wr = nz(pack2(r0, r1)), wm = pack2(m0, m1);
  str2(so, wr, wm); str2(so + 4096, wr, wm);
  bar_arrive_if(NB_Q, 448, !layer);
  PROF(23, s_sr);
}

DEV void announce(const Params& P, int c, int lane, int layer) {
  PW(13)
  bar_sync(NB_T + 3, layer ? 288 : 160);
  cnt_add(P, 5 * layer, c, lane);
  bar_sync_if(NB_Q, 448, !layer);
  fence_async_smem();
  PROF(24, s_own);
}

DEV void fetch(const Params& P, int c, int lane, int layer) {
  PW(13)
  mbar_expect1(B_E, 24576);
  cnt_wait(P, 5 * layer, c, lane);
#pragma unroll
  for (int k = 0; k < 4; ++k) bulk(SM_R + k * 16384 + R_B, P.S->XG[layer] + (128 * k + c) * 256, 4096, B_E);
  if (layer) delay(SRDELAY);
  bulk(SM_RES, P.S->SR[layer][c >> 4], 8192, B_E);
  if (!layer) { if (!CSP) l2_prefetch(P.wqkv + c * 6144, 12288); l2_prefetch(P.wo + c * 2048, 4096); }
  if (PHOLD) mbar_arrive1_if(B_ST + 8, !layer);
  PROF(25, s_all);
}

DEV void cs_part(const Params& P, int c, int w, int lane, int layer) {
  float cs[8];
#pragma unroll
  for (int k = 0; k < 8; ++k) cs[k] = 0.f;
  const int col = w * 512 + 64 * (c & 7) + 8 * (lane & 7);
#pragma unroll 1
  for (int r = 8 * layer; r < 8; r += CSU) {
    uint4 v[CSU];
#pragma unroll
    for (int k = 0; k < CSU; ++k) v[k] = ldnc4(P.wqkv + ((32 * (c >> 3) + 4 * r + (lane >> 3)) * 1536 + col) + 4 * k * 1536);
#pragma unroll
    for (int k = 0; k < CSU; ++k) {
      cs[0] += bflo(v[k].x); cs[1] += bfhi(v[k].x); cs[2] += bflo(v[k].y); cs[3] += bfhi(v[k].y);
      cs[4] += bflo(v[k].z); cs[5] += bfhi(v[k].z); cs[6] += bflo(v[k].w); cs[7] += bfhi(v[k].w);
    }
  }
  fold<4>(cs, lane, 16); fold<2>(cs, lane, 8);
  str2((float*)P.S->CS + ((c >> 3) * 1536 + col + 2 * (lane >> 3)), max(__float_as_uint(cs[0]), 1u - layer), __float_as_uint(cs[1]));
}

DEV void cs_sum(const Params& P, int c, int w, int lane) {
  float a, b;
  for (int it = 0;; ++it) {
    uint32_t m = ~0u;
    a = b = 0.f;
#pragma unroll
    for (int k = 0; k < 16; ++k) {
      const uint2 u = ldr2((const float*)P.S->CS + (w * 512 + 64 * (c & 7) + 2 * lane) + k * 1536);
      a += __uint_as_float(u.x); b += __uint_as_float(u.y); m = min(m, u.x);
    }
    if (__all_sync(0xffffffffu, m != 0u)) break;
    spin_guard(it);
  }
  const uint32_t hi = pack2(a, b), ad = SM_CS + w * 256 + (lane >> 2) * 32 + (lane & 3) * 4;
  sts1(ad, hi); sts1(ad + 16, pack2(a - bflo(hi), b - bfhi(hi)));
  fence_async_smem();
  __syncwarp();
  mbar_arrive1(B_CS);
}

DEV void x0_get(uint32_t (&x)[8][2], uint32_t a) {
  asm volatile("cp.async.wait_group 0;" ::: "memory");
#pragma unroll
  for (int z = 0; z < 4; ++z) {
    const uint4 v = lds4(a + z * 512);
    x[2 * (z & 2)][z & 1] = v.x; x[2 * (z & 2) + 1][z & 1] = v.y; x[2 * (z & 2) + 2][z & 1] = v.z; x[2 * (z & 2) + 3][z & 1] = v.w;
  }
}

DEV void par_load(const Params& P, int ch, int m, uint32_t (&pv)[8]) {
  const int mo = ch * 128 + m;
  pv[0] = ldnc16(P.Are + mo); pv[1] = ldnc16(P.Aim + mo); pv[2] = ldnc16(P.Bre + mo); pv[3] = ldnc16(P.Bim + mo);
  pv[4] = ldnc16(P.Cre + mo); pv[5] = ldnc16(P.Cim + mo); pv[6] = ldnc16(P.logdt + ch); pv[7] = ldnc16(P.dskip + ch);
}

__global__ void __launch_bounds__(NTHR, 1)
fused_kernel(const __grid_constant__ Params P, const __grid_constant__ CUtensorMap mapW,
             const __grid_constant__ CUtensorMap mapWo) {
  extern __shared__ __align__(1024) uint8_t smem_raw[];
  if (s2u(smem_raw) != SB) __trap();
  const int warp0 = __shfl_sync(0xffffffffu, threadIdx.x >> 5, 0), lane0 = threadIdx.x & 31;
  uint32_t smid; asm volatile("mov.u32 %0,%%smid;" : "=r"(smid));
  const int c = __shfl_sync(0xffffffffu, P.by_sm ? P.role[smid] : blockIdx.x, 0);
  if (c == 255) {
    if (threadIdx.x < NCOPY * NSUB)
#pragma unroll 1
      for (int it = 0; it < 256 && ldr1(P.S->C + 32 * threadIdx.x) < 128 / NSUB; ++it) __nanosleep(200);
    return;
  }
  const int cg = c & 7;
  PW(warp0)
  uint32_t dskip;
  {
    [[maybe_unused]] const int layer = 0;
    const int lane = lane0, g = lane >> 2, t = lane & 3, warp = warp0, k4 = warp >> 2, w = warp & 3;
    uint32_t pv[8];
    if (k4 < 3) par_load(P, 128 * k4 + c, 32 * w + lane, pv);
    else {
#pragma unroll
      for (int n = 0; n < 8; ++n) pv[n] = 0;
    }
    __syncthreads();
    if (XDEL) delay(XDEL);
    const uint16_t* r = P.x0 + ((k4 < 2 ? 8192 * c + 64 * warp : (128 * (c >> 3) + 16 * w) * 512 + 64 * cg) + 1024 * g + 8 * t);
    const uint32_t xa = SM_R + k4 * 16384 + w * 2048 + lane * 16;
    if (k4 != 2) {
#pragma unroll
      for (int z = 0; z < 4; ++z) cp16(xa + z * 512, r + (z & 1) * 512 + (z & 2) * 16);
    }
    sts4(SM_TAP + k4 * TAP_SZ + (32 * w + lane) * 16, 0, 0, 0, 0);
    sts4z_if(SM_TAP + k4 * TAP_SZ + 2048 + (32 * w + lane) * 16, w < 3);
    uint32_t x[8][2];
    if (k4 == 3) {
#pragma unroll
      for (int z = 0; z < 4; ++z) cp16(xa - 16384 + z * 512, r + 32768 + (z & 1) * 512 + (z & 2) * 16);
      asm volatile("cp.async.commit_group;" ::: "memory");
      if (threadIdx.x == 448) {
        asm volatile("prefetch.tensormap [%0];" :: "l"(&mapW) : "memory");
        asm volatile("prefetch.tensormap [%0];" :: "l"(&mapWo) : "memory");
      }
      __syncwarp();
      if (PDELAY) delay(PDELAY);
      par_load(P, 128 * k4 + c, 32 * w + lane, pv);
      XgAddr xd = xg_addr<false>(P.S->XG[0] + (64 * cg * 256 + 16 * (c >> 3)), SM_R + 3 * 16384 + 8192, w, lane, P.zero);
      x0_get(x, xa);
      PROF(27, a_ld);
      xg_put<false>(xd, x);
      x0_get(x, xa - 16384);
      xd.a -= 16384;
      xg_put<false>(xd, x);
      bar_sync(NB_WG + 3, 128);
      xg_store(xd);
      xd.b -= 16384; xd.dst += 8;
      xg_store(xd);
      bar_arrive(NB_T + 3, 160);
      bar_sync(NB_Q, 448);
    } else asm volatile("cp.async.commit_group;" ::: "memory");
    tables(pv, k4, w, lane);
    if (k4 < 2) {
      x0_get(x, xa);
      const float4 s = gram(x, g, P.zero);
      if (t == (g >> 1)) sts4f(SM_RES + 8192 + (warp * 8 + g) * 16, s.x, s.y, s.z, s.w);
      __syncwarp();
      bar_arrive_if(NB_P, 256, warp != 7);
    }
    if (k4 == 2) {
#pragma unroll
      for (int n = 0; n < 14; ++n) mbar_init1(SM_BAR + (n < 10 ? w * 80 : 240 + w * 32) + n * 8, n < 10 ? 1 : (CNT >> (8 * w + 2 * (n - 10 & 2))) & 15);
    }
    dskip = pv[7];
    PROF(1, a_x0);
  }
#pragma unroll 1
  for (int layer = 0; layer < 2; ++layer) {
    int lane = lane_here(P.zero);
    const int warp = warp0 | (layer & P.zero), k4 = warp >> 2, w = warp & 3;
    if (warp == (layer ? 12 : 7)) finalize(P, c, lane, layer);
    if (warp == (layer ? 13 : 6)) { announce(P, c, lane, layer); fetch(P, c, lane, layer); }
    if (layer == 0) {
      if (CSP && k4 == 1 && w != 2) { if (CSP > 1) delay(CSP); cs_part(P, c, w - (w >> 1), lane, 0); }
      taps(dskip, k4, w, lane);
    }
    if (!layer && ((PHOLD >> k4) & 1)) mbar_wait(B_ST + 8, 0);
    conv(P, &mapW, c, k4, w, layer);
    lane = lane_here(P.zero);
    if (k4 < 2) {
      bar_arrive_if(NB_H, 256, warp != 4);
      if (warp == 0) {
        mbar_wait(B_K, 0);
        cnt_wait(P, 1 + 5 * layer, c, lane);
        x_load(P, c, 0, layer);
        PROF(27, m_xi);
      } else if (k4 == 0 && (CSP == 0 || layer)) cs_part(P, c, w - 1, lane, CSP ? 1 : layer);
      attn_phase(P, c, k4, w, lane, layer);
    } else {
      bar_arrive_if(NB_RL, 256, warp >= 10);
      if (k4 == 3) {
        stats(P, c, w, lane, layer);
      } else if (w < 2) {
        bar_sync_if(NB_RL, 256, w);
        cnt_wait(P, 3 + 5 * layer + w, c, lane);
        bar_sync_if(NB_RL, 256, !w);
        if (w) mbar_wait(B_F, layer);
        x_load(P, c, 2 + w, layer);
        if (H5 && w) w_load(&mapW, cg, 5);
        PROF(14, h_xi);
        if (w == 1) str4(&P.S->SR[layer][lane >> 2][4 * c + (lane & 3)], 0, 0, 0, 0);
      } else if (w == 2) {
        mbar_expect1(B_WO, 65536);
        mbar_expect1(B_RES, 16384);
#pragma unroll 1
        for (int q = 0; q < 4; ++q) {
          if (FH && q < 2) { mbar_wait(B_FH + 8 * q, layer); w_load(&mapW, cg, 4 + 2 * q); }
          mbar_wait(B_F + 8 * q, layer);
          if (!FH && q < 2) w_load(&mapW, cg, 4 + 2 * q);
          if (q == 1 || (q == 0 && !H5)) w_load(&mapW, cg, 5 + 2 * q);
          if (WOQ == 0 && ((q + 1) & 2)) tma5(SM_R + (q & 2) * 16384, &mapWo, 64 * cg, 4 * (q & 2), B_WO);
          if (WOQ && q == 2) {
            if (WOQ >= 2) mbar_wait(B_ST, layer);
            tma5(SM_R, &mapWo, 64 * cg, 0, B_WO);
            if (WOQ < 3) tma5(SM_R + 32768, &mapWo, 64 * cg, 8, B_WO);
          }
          if (q == 3) {
#pragma unroll
            for (int e = 0; e < 2; ++e) bulk(SM_RES + e * 8192, P.S->XF + ((2 * (c >> 3) + 1 - e) * 4096 + cg * 512), 8192, B_RES);
          }
          PROF(15 + q, h_w);
        }
      }
      if (k4 == 2 && w != 2) {
        if (layer == 0) cs_sum(P, c, w - (w >> 1), lane);
        if (w == 3) {
          uint4* xz = P.S->XG[layer] + (c * 256 + lane);
          mbar_wait(B_F, layer);
#pragma unroll 1
          for (int k = 0; k < 32; ++k) {
            str4(xz + ((k >> 3) * 32768 + (k & 7) * 32), 0, 0, 0, 0);
            if (ZPACE) __nanosleep(ZPACE);
          }
          PROF(19, h_z);
        }
      }
      if (warp < 10) o_load(P, c, w, lane, layer);
    }
    asm volatile("mov.b32 %0,0;" : "=r"(dskip));
  }
}

typedef CUresult (*EncodeFn)(CUtensorMap*, CUtensorMapDataType, cuuint32_t, void*, const cuuint64_t*, const cuuint64_t*,
                             const cuuint32_t*, const cuuint32_t*, CUtensorMapInterleave, CUtensorMapSwizzle,
                             CUtensorMapL2promotion, CUtensorMapFloatOOBfill);

#define POOL 0
#define GOFF 0
static int place_roles(uint8_t* role) {
  int dev = 0, nsm = 0;
  cudaGetDevice(&dev);
  cudaDeviceGetAttribute(&nsm, cudaDevAttrMultiProcessorCount, dev);
  if (nsm < 128 || nsm > 144 || (nsm & 1)) return 0;
  cudaFuncSetAttribute(fused_kernel, cudaFuncAttributeNonPortableClusterSizeAllowed, 1);
  int occ[9] = {0};
  for (int k = 2; k <= 8; ++k) {
    cudaLaunchConfig_t cfg = {};
    cudaLaunchAttribute at[1];
    at[0].id = cudaLaunchAttributeClusterDimension;
    at[0].val.clusterDim.x = 2 * k; at[0].val.clusterDim.y = 1; at[0].val.clusterDim.z = 1;
    cfg.gridDim = dim3(2 * k); cfg.blockDim = dim3(NTHR); cfg.dynamicSmemBytes = SM_TOTAL; cfg.attrs = at; cfg.numAttrs = 1;
    if (cudaOccupancyMaxActiveClusters(&occ[k], fused_kernel, &cfg) != cudaSuccess) { cudaGetLastError(); occ[k] = 0; }
  }
  int n[10];
  n[7] = occ[8]; n[6] = occ[7]; n[5] = occ[6] - 0; n[4] = occ[5];
  n[3] = occ[4] - n[7]; n[1] = occ[2] - n[3] - n[5] - n[7]; n[0] = n[2] = n[1];
  n[8] = occ[3] - n[2] - n[5];
  const int ntpc = nsm / 2;
  int sum = 0;
  bool ok = n[0] > 0 && n[0] <= 8;
  for (int r = 0; r < 9; ++r) { ok = ok && n[r] >= 0 && (r == 0 || n[r] <= n[r - 1]); sum += n[r]; }
  if (!ok || sum > ntpc) { for (int r = 0; r < 9; ++r) n[r] = r < 8 ? 8 : 0; sum = 64; }
  int tp[8][9], cnt[8] = {0}, pool[72], np = 0, id = 0;
  for (int r = 0; r < 9; ++r)
    for (int g = n[0] - n[r]; g < n[0]; ++g) tp[g][cnt[g]++] = id++;
  for (; id < ntpc; ++id) pool[np++] = id;
  int order[72], no = 0;
  for (int g = 0; g < n[0]; ++g) {
    const int full = cnt[g] / 4 * 4;
    for (int k = 0; k < cnt[g]; ++k) { if (k < full) order[no++] = tp[g][k]; else pool[np++] = tp[g][k]; }
  }
  for (int k = 0; k < np; ++k) order[no++] = pool[POOL == 1 ? np - 1 - k : POOL == 2 ? (k + np - 2) % np : k];
  for (int k = 0; k < 144; ++k) role[k] = 255;
  for (int k = 0; k < 64; ++k) { role[2 * order[k]] = (2 * k + GOFF) & 127; role[2 * order[k] + 1] = (2 * k + 1 + GOFF) & 127; }
  return nsm;
}

extern "C" void kernel_launch(void* const* d_in, const int* in_sizes, int n_in, void* d_out, int out_size) {
  (void)in_sizes; (void)n_in; (void)out_size;
  static EncodeFn enc = nullptr;
  static uint8_t role[144];
  static int nsm = 0;
  static void* scratch = nullptr;
  if (!enc) {
    void* fn = nullptr;
    cudaDriverEntryPointQueryResult qr;
    cudaGetDriverEntryPoint("cuTensorMapEncodeTiled", &fn, cudaEnableDefault, &qr);
    enc = (EncodeFn)fn;
    cudaFuncSetAttribute(fused_kernel, cudaFuncAttributeMaxDynamicSharedMemorySize, SM_TOTAL);
    nsm = place_roles(role);
    cudaGetSymbolAddress(&scratch, g_S);
  }
  CUtensorMap mW, mWo;
  {
    cuuint64_t dim[3] = {512, 512, 3}, str[2] = {3072, 1024};
    cuuint32_t box[3] = {64, 64, 3}, es[3] = {1, 1, 1};
    enc(&mW, CU_TENSOR_MAP_DATA_TYPE_BFLOAT16, 3, d_in[10], dim, str, box, es, CU_TENSOR_MAP_INTERLEAVE_NONE,
        CU_TENSOR_MAP_SWIZZLE_128B, CU_TENSOR_MAP_L2_PROMOTION_NONE, CU_TENSOR_MAP_FLOAT_OOB_FILL_NONE);
  }
  {
    cuuint64_t dim[5] = {512, 2, 4, 4, 16}, str[4] = {1024, 8192, 2048, 32768};
    cuuint32_t box[5] = {64, 2, 4, 4, 8}, es[5] = {1, 1, 1, 1, 1};
    enc(&mWo, CU_TENSOR_MAP_DATA_TYPE_BFLOAT16, 5, d_in[11], dim, str, box, es, CU_TENSOR_MAP_INTERLEAVE_NONE,
        CU_TENSOR_MAP_SWIZZLE_128B, CU_TENSOR_MAP_L2_PROMOTION_NONE, CU_TENSOR_MAP_FLOAT_OOB_FILL_NONE);
  }
  Params P;
  P.x0 = (const uint16_t*)d_in[0]; P.Are = (const uint16_t*)d_in[1]; P.Aim = (const uint16_t*)d_in[2];
  P.Bre = (const uint16_t*)d_in[3]; P.Bim = (const uint16_t*)d_in[4]; P.Cre = (const uint16_t*)d_in[5];
  P.Cim = (const uint16_t*)d_in[6]; P.logdt = (const uint16_t*)d_in[7]; P.dskip = (const uint16_t*)d_in[8];
  P.wqkv = (const uint16_t*)d_in[10]; P.wo = (const uint16_t*)d_in[11]; P.out = (uint16_t*)d_out;
  for (int k = 0; k < 144; ++k) P.role[k] = role[k];
  P.by_sm = nsm > 0;
  P.zero = 0;
  P.S = (Scratch*)scratch;
  fused_kernel<<<nsm > 0 ? nsm : 128, NTHR, SM_TOTAL, cudaStreamPerThread>>>(P, mW, mWo);
}
```

```cpp
#include <cuda_runtime.h>
#include <cuda_bf16.h>
#include <cuda.h>
#include <stdint.h>

#define DEV __device__ __forceinline__

#define NCOPY 4
#define NSUB 1
constexpr int NTHR = 512;
constexpr int SPIN_LIMIT = 1 << 22;

constexpr uint32_t SB = 1024;
constexpr uint32_t SM_XA   = SB;
constexpr uint32_t SM_S0   = SM_XA + 16384;
constexpr uint32_t SM_S1   = SM_S0 + 49152;
constexpr uint32_t SM_XB   = SM_S1 + 49152;
constexpr uint32_t SM_R    = SM_XB + 16384;
constexpr uint32_t SM_RES  = SM_R + 65536;
constexpr uint32_t SM_TAP  = SM_RES + 16384;
constexpr int TAP_SZ = 3584;
constexpr uint32_t SM_CS   = SM_TAP + 4 * TAP_SZ;
constexpr uint32_t SM_STAT = SM_CS + 800;
constexpr uint32_t SM_MISC = SM_STAT + 1280;
constexpr uint32_t SM_BAR  = SM_MISC + 512;
constexpr int SM_TOTAL = SM_BAR + 448 - SB;
constexpr int R_U = 512, R_A5 = 5120, R_A3 = 8704, R_B = 11776;
constexpr int T_E = 1536, T_O = T_E + 1602, T_C = 3714;
constexpr uint32_t B_W = SM_BAR, B_X = SM_BAR + 64, B_O = SM_BAR + 128, B_WO = SM_BAR + 256, B_RES = SM_BAR + 264;
constexpr uint32_t B_ST = SM_BAR + 272, B_R = SM_BAR + 288, B_E = SM_BAR + 304;
constexpr uint32_t B_F = SM_BAR + 320, B_G = SM_BAR + 352, B_K = SM_BAR + 376, B_ED = SM_BAR + 384, B_CS = SM_BAR + 400, B_FH = SM_BAR + 416;
constexpr uint32_t CNT = 0x143444CC;
constexpr int NB_WG = 1, NB_T = 5, NB_Q = 10, NB_H = 11, NB_P = 14, NB_RL = 15;

struct Scratch {
  uint32_t F[32 * 32];
  uint4    H[17 * 8 * 256];
  uint4    SR[2][8][512];
  uint4    ST[32 * 16];
  uint4    PS[128 * 64];
  float4   CS[16 * 1536 / 4];
  uint32_t C[10 * 32 * 32];
  uint4    XF[32 * 4096];
  uint4    O[32 * 8 * 512];
  uint4    XG[2][512 * 256];
};
__device__ __align__(1024) Scratch g_S;

struct Params {
  int by_sm;
  uint32_t zero;
  Scratch* S;
  const uint16_t *x0, *Are, *Aim, *Bre, *Bim, *Cre, *Cim, *logdt, *dskip, *wqkv, *wo;
  uint16_t* out;
  uint8_t role[144];
};
#define EVENT(n) do {} while (0)
#define PROFD(slot, name, v) do {} while (0)
#define PROF(slot, name) do {} while (0)
#define PW(x)

DEV uint32_t s2u(const void* p) { return (uint32_t)__cvta_generic_to_shared(p); }
template <class T> DEV T opq(T x) { asm volatile("" : "+r"(x)); return x; }
DEV uint32_t pack2(float lo, float hi) { uint32_t d; asm("cvt.rn.bf16x2.f32 %0,%1,%2;" : "=r"(d) : "f"(hi), "f"(lo)); return d; }
DEV float bflo(uint32_t v) { return __uint_as_float(v << 16); }
DEV float bfhi(uint32_t v) { return __uint_as_float(v & 0xFFFF0000u); }
DEV float bfr(float x) { return bflo(pack2(x, 0.f)); }
DEV uint32_t hadd2(uint32_t a, uint32_t b) { uint32_t d; asm("add.rn.bf16x2 %0,%1,%2;" : "=r"(d) : "r"(a), "r"(b)); return d; }
DEV uint32_t hsub2(uint32_t a, uint32_t b) { uint32_t d; asm("sub.rn.bf16x2 %0,%1,%2;" : "=r"(d) : "r"(a), "r"(b)); return d; }
DEV uint32_t hmul2(uint32_t a, uint32_t b) { uint32_t d; asm("mul.rn.bf16x2 %0,%1,%2;" : "=r"(d) : "r"(a), "r"(b)); return d; }
DEV uint32_t hfma2(uint32_t a, uint32_t b, uint32_t c) { uint32_t d; asm("fma.rn.bf16x2 %0,%1,%2,%3;" : "=r"(d) : "r"(a), "r"(b), "r"(c)); return d; }
DEV uint32_t hmax2(uint32_t a, uint32_t b) { uint32_t d; asm("max.bf16x2 %0,%1,%2;" : "=r"(d) : "r"(a), "r"(b)); return d; }
DEV uint32_t prmt(uint32_t a, uint32_t b, uint32_t s) { uint32_t d; asm("prmt.b32 %0,%1,%2,%3;" : "=r"(d) : "r"(a), "r"(b), "r"(s)); return d; }
DEV uint32_t nz(uint32_t v) { uint32_t d; asm("max.u32 %0,%1,1;" : "=r"(d) : "r"(v)); return d; }
DEV uint32_t tagged(uint32_t v, uint32_t m, uint32_t tag) { uint32_t d; asm("lop3.b32 %0,%1,%2,%3,0xB8;" : "=r"(d) : "r"(v), "r"(m), "r"(tag)); return d; }
DEV uint32_t both(uint32_t a, uint32_t b, uint32_t x) { uint32_t d; asm("lop3.b32 %0,%1,%2,%3,0x42;" : "=r"(d) : "r"(a), "r"(b), "r"(x)); return d; }
DEV uint4 hadd8(const uint4& a, const uint4& b) { return make_uint4(hadd2(a.x, b.x), hadd2(a.y, b.y), hadd2(a.z, b.z), hadd2(a.w, b.w)); }
DEV uint32_t min4(const uint4& v) { return min(min(v.x, v.y), min(v.z, v.w)); }
DEV float rcp(float x) { float y; asm("rcp.approx.ftz.f32 %0,%1;" : "=f"(y) : "f"(x)); return y; }
DEV float sqrt_(float x) { float y; asm("sqrt.approx.ftz.f32 %0,%1;" : "=f"(y) : "f"(x)); return y; }
DEV float rsq(float x) { float y; asm("rsqrt.approx.ftz.f32 %0,%1;" : "=f"(y) : "f"(x)); return y; }
DEV float ex2(float x) { float y; asm("ex2.approx.ftz.f32 %0,%1;" : "=f"(y) : "f"(x)); return y; }

DEV uint4 ldr4(const void* p) { uint4 v; asm volatile("ld.relaxed.gpu.global.v4.u32 {%0,%1,%2,%3},[%4];" : "=r"(v.x), "=r"(v.y), "=r"(v.z), "=r"(v.w) : "l"(p) : "memory"); return v; }
DEV void ldr4_if(uint4& v, const void* p, bool c) {
  asm volatile("{.reg .pred q; setp.ne.u32 q,%5,0; @q ld.relaxed.gpu.global.v4.u32 {%0,%1,%2,%3},[%4];}"
    : "+r"(v.x), "+r"(v.y), "+r"(v.z), "+r"(v.w) : "l"(p), "r"((uint32_t)c) : "memory");
}
DEV uint2 ldr2(const void* p) { uint2 v; asm volatile("ld.relaxed.gpu.global.v2.u32 {%0,%1},[%2];" : "=r"(v.x), "=r"(v.y) : "l"(p) : "memory"); return v; }
DEV uint32_t ldr1(const void* p) { uint32_t v; asm volatile("ld.relaxed.gpu.global.u32 %0,[%1];" : "=r"(v) : "l"(p) : "memory"); return v; }
DEV void str4(void* p, uint32_t a, uint32_t b, uint32_t c, uint32_t d) { asm volatile("st.relaxed.gpu.global.v4.u32 [%0],{%1,%2,%3,%4};" :: "l"(p), "r"(a), "r"(b), "r"(c), "r"(d) : "memory"); }
DEV void str4_if(void* p, uint32_t a, uint32_t b, uint32_t c, uint32_t d, bool q) {
  asm volatile("{.reg .pred q; setp.ne.u32 q,%5,0; @q st.relaxed.gpu.global.v4.u32 [%0],{%1,%2,%3,%4};}" :: "l"(p), "r"(a), "r"(b), "r"(c), "r"(d), "r"((uint32_t)q) : "memory");
}
DEV void str2(void* p, uint32_t a, uint32_t b) { asm volatile("st.relaxed.gpu.global.v2.u32 [%0],{%1,%2};" :: "l"(p), "r"(a), "r"(b) : "memory"); }
DEV void str1(void* p, uint32_t a) { asm volatile("st.relaxed.gpu.global.u32 [%0],%1;" :: "l"(p), "r"(a) : "memory"); }
DEV void stw4(void* p, uint32_t a, uint32_t b, uint32_t c, uint32_t d) { asm volatile("st.global.v4.u32 [%0],{%1,%2,%3,%4};" :: "l"(p), "r"(a), "r"(b), "r"(c), "r"(d) : "memory"); }
DEV uint4 ldnc4(const void* p) { uint4 v; asm volatile("ld.global.nc.v4.u32 {%0,%1,%2,%3},[%4];" : "=r"(v.x), "=r"(v.y), "=r"(v.z), "=r"(v.w) : "l"(p)); return v; }
DEV uint4 ldw4(const void* p) { uint4 v; asm volatile("ld.global.v4.u32 {%0,%1,%2,%3},[%4];" : "=r"(v.x), "=r"(v.y), "=r"(v.z), "=r"(v.w) : "l"(p) : "memory"); return v; }
DEV void cp16(uint32_t d, const void* p) { asm volatile("cp.async.cg.shared.global [%0],[%1],16;" :: "r"(d), "l"(p) : "memory"); }
DEV uint32_t ldnc16(const void* p) { uint32_t v; asm volatile("ld.global.u16 %0,[%1];" : "=r"(v) : "l"(p) : "memory"); return v; }

DEV uint32_t lds1v(uint32_t a) { uint32_t v; asm volatile("ld.volatile.shared.u32 %0,[%1];" : "=r"(v) : "r"(a) : "memory"); return v; }
DEV uint4 lds4v(uint32_t a) { uint4 v; asm volatile("ld.volatile.shared.v4.u32 {%0,%1,%2,%3},[%4];" : "=r"(v.x), "=r"(v.y), "=r"(v.z), "=r"(v.w) : "r"(a) : "memory"); return v; }
DEV uint32_t lds1(uint32_t a) { uint32_t v; asm volatile("ld.shared.u32 %0,[%1];" : "=r"(v) : "r"(a)); return v; }
DEV uint2 lds2(uint32_t a) { uint2 v; asm volatile("ld.shared.v2.u32 {%0,%1},[%2];" : "=r"(v.x), "=r"(v.y) : "r"(a)); return v; }
DEV uint4 lds4(uint32_t a) { uint4 v; asm volatile("ld.shared.v4.u32 {%0,%1,%2,%3},[%4];" : "=r"(v.x), "=r"(v.y), "=r"(v.z), "=r"(v.w) : "r"(a)); return v; }
DEV uint32_t lds16(uint32_t a) { uint32_t v; asm volatile("ld.shared.u16 %0,[%1];" : "=r"(v) : "r"(a)); return v; }
DEV float lds1f(uint32_t a) { float v; asm volatile("ld.shared.f32 %0,[%1];" : "=f"(v) : "r"(a)); return v; }
DEV float2 lds2f(uint32_t a) { float2 v; asm volatile("ld.shared.v2.f32 {%0,%1},[%2];" : "=f"(v.x), "=f"(v.y) : "r"(a)); return v; }
DEV float4 lds4f(uint32_t a) { float4 v; asm volatile("ld.shared.v4.f32 {%0,%1,%2,%3},[%4];" : "=f"(v.x), "=f"(v.y), "=f"(v.z), "=f"(v.w) : "r"(a)); return v; }
DEV void sts1(uint32_t a, uint32_t v) { asm volatile("st.shared.u32 [%0],%1;" :: "r"(a), "r"(v) : "memory"); }
DEV void sts16(uint32_t a, uint32_t v) { asm volatile("{.reg .b16 h; cvt.u16.u32 h,%1; st.shared.u16 [%0],h;}" :: "r"(a), "r"(v) : "memory"); }
DEV void sts2f(uint32_t a, float x, float y) { asm volatile("st.shared.v2.f32 [%0],{%1,%2};" :: "r"(a), "f"(x), "f"(y) : "memory"); }
DEV void sts4f(uint32_t a, float x, float y, float z, float w) { asm volatile("st.shared.v4.f32 [%0],{%1,%2,%3,%4};" :: "r"(a), "f"(x), "f"(y), "f"(z), "f"(w) : "memory"); }
DEV void sts4(uint32_t a, uint32_t x, uint32_t y, uint32_t z, uint32_t w) { asm volatile("st.shared.v4.u32 [%0],{%1,%2,%3,%4};" :: "r"(a), "r"(x), "r"(y), "r"(z), "r"(w) : "memory"); }
DEV void sts4_if(uint32_t a, uint32_t x, uint32_t y, uint32_t z, uint32_t w, bool c) {
  asm volatile("{.reg .pred q; setp.ne.u32 q,%5,0; @q st.shared.v4.u32 [%0],{%1,%2,%3,%4};}" :: "r"(a), "r"(x), "r"(y), "r"(z), "r"(w), "r"((uint32_t)c) : "memory");
}
DEV void sts4z_if(uint32_t a, bool c) { asm volatile("{.reg .pred q; setp.ne.u32 q,%1,0; @q st.shared.v4.u32 [%0],{%2,%2,%2,%2};}" :: "r"(a), "r"((uint32_t)c), "r"(0) : "memory"); }

DEV void ldsm4t(uint32_t& r0, uint32_t& r1, uint32_t& r2, uint32_t& r3, uint32_t a) { asm volatile("ldmatrix.sync.aligned.m8n8.x4.trans.shared.b16 {%0,%1,%2,%3},[%4];" : "=r"(r0), "=r"(r1), "=r"(r2), "=r"(r3) : "r"(a) : "memory"); }
DEV void stsm4(uint32_t a, uint32_t r0, uint32_t r1, uint32_t r2, uint32_t r3) { asm volatile("stmatrix.sync.aligned.m8n8.x4.shared.b16 [%0],{%1,%2,%3,%4};" :: "r"(a), "r"(r0), "r"(r1), "r"(r2), "r"(r3) : "memory"); }
DEV void stsm2(uint32_t a, uint32_t r0, uint32_t r1) { asm volatile("stmatrix.sync.aligned.m8n8.x2.shared.b16 [%0],{%1,%2};" :: "r"(a), "r"(r0), "r"(r1) : "memory"); }
DEV void stsm4t(uint32_t a, uint32_t r0, uint32_t r1, uint32_t r2, uint32_t r3) { asm volatile("stmatrix.sync.aligned.m8n8.x4.trans.shared.b16 [%0],{%1,%2,%3,%4};" :: "r"(a), "r"(r0), "r"(r1), "r"(r2), "r"(r3) : "memory"); }
DEV uint32_t movm(uint32_t a) { uint32_t d; asm volatile("movmatrix.sync.aligned.m8n8.trans.b16 %0,%1;" : "=r"(d) : "r"(a)); return d; }
DEV void mma16(float (&d)[4], uint32_t a0, uint32_t a1, uint32_t a2, uint32_t a3, uint32_t b0, uint32_t b1) {
  asm volatile("mma.sync.aligned.m16n8k16.row.col.f32.bf16.bf16.f32 {%0,%1,%2,%3},{%4,%5,%6,%7},{%8,%9},{%0,%1,%2,%3};"
    : "+f"(d[0]), "+f"(d[1]), "+f"(d[2]), "+f"(d[3]) : "r"(a0), "r"(a1), "r"(a2), "r"(a3), "r"(b0), "r"(b1));
}
DEV void mma16z(float (&d)[4], uint32_t a0, uint32_t a1, uint32_t a2, uint32_t a3, uint32_t b0, uint32_t b1) {
  asm volatile("mma.sync.aligned.m16n8k16.row.col.f32.bf16.bf16.f32 {%0,%1,%2,%3},{%4,%5,%6,%7},{%8,%9},{%10,%10,%10,%10};"
    : "=f"(d[0]), "=f"(d[1]), "=f"(d[2]), "=f"(d[3]) : "r"(a0), "r"(a1), "r"(a2), "r"(a3), "r"(b0), "r"(b1), "f"(0.f));
}
DEV void mma8z(float (&d)[4], uint32_t a0, uint32_t a1, uint32_t b0) {
  asm volatile("mma.sync.aligned.m16n8k8.row.col.f32.bf16.bf16.f32 {%0,%1,%2,%3},{%4,%5},{%6},{%7,%7,%7,%7};"
    : "=f"(d[0]), "=f"(d[1]), "=f"(d[2]), "=f"(d[3]) : "r"(a0), "r"(a1), "r"(b0), "f"(0.f));
}
DEV void mma8(float (&d)[4], uint32_t a0, uint32_t a1, uint32_t b0) {
  asm volatile("mma.sync.aligned.m16n8k8.row.col.f32.bf16.bf16.f32 {%0,%1,%2,%3},{%4,%5},{%6},{%0,%1,%2,%3};"
    : "+f"(d[0]), "+f"(d[1]), "+f"(d[2]), "+f"(d[3]) : "r"(a0), "r"(a1), "r"(b0));
}

DEV void bar_sync(int id, int n) { asm volatile("bar.sync %0,%1;" :: "r"(id), "r"(n) : "memory"); }
DEV void bar_arrive(int id, int n) { asm volatile("bar.arrive %0,%1;" :: "r"(id), "r"(n) : "memory"); }
DEV void bar_sync_if(int id, int n, int c) { asm volatile("{.reg .pred q; setp.ne.s32 q,%2,0; @q bar.sync %0,%1;}" :: "r"(id), "r"(n), "r"(c) : "memory"); }
DEV void bar_arrive_if(int id, int n, int c) { asm volatile("{.reg .pred q; setp.ne.s32 q,%2,0; @q bar.arrive %0,%1;}" :: "r"(id), "r"(n), "r"(c) : "memory"); }
DEV bool bar_any(int id, int n, bool c) {
  uint32_t r; asm volatile("{.reg .pred p,q; setp.ne.u32 q,%3,0; bar.red.or.pred p,%1,%2,q; selp.u32 %0,1,0,p;}" : "=r"(r) : "r"(id), "r"(n), "r"((uint32_t)c) : "memory");
  return __any_sync(0xffffffffu, r);
}
DEV void fence_async_glob() { asm volatile("fence.proxy.async.global;" ::: "memory"); }
DEV void fence_async_smem() { asm volatile("fence.proxy.async.shared::cta;" ::: "memory"); }
DEV void fence_gpu() { asm volatile("fence.acq_rel.gpu;" ::: "memory"); }
DEV void mbar_wait(uint32_t b, uint32_t ph) {
  asm volatile("{\n.reg .pred p;\nW: mbarrier.try_wait.parity.shared::cta.b64 p,[%0],%1;\n@!p bra W;\n}" :: "r"(b), "r"(ph) : "memory");
}
DEV bool mbar_test(uint32_t b, uint32_t ph) {
  uint32_t r; asm volatile("{.reg .pred p; mbarrier.test_wait.parity.shared::cta.b64 p,[%1],%2; selp.u32 %0,1,0,p;}" : "=r"(r) : "r"(b), "r"(ph) : "memory");
  return __all_sync(0xffffffffu, r);
}
DEV uint32_t mbar_test2(uint32_t b, uint32_t ph) {
  uint32_t r; asm volatile("{.reg .pred p,q; mbarrier.test_wait.parity.shared::cta.b64 p,[%1],%2; mbarrier.test_wait.parity.shared::cta.b64 q,[%1+8],%2;\n"
                           "and.pred p,p,q; selp.u32 %0,1,0,p;}" : "=r"(r) : "r"(b), "r"(ph) : "memory");
  return r;
}
DEV void spin_guard(int it) { asm volatile("{.reg .pred p; setp.gt.s32 p,%0,%1; @p trap;}" :: "r"(it), "n"(SPIN_LIMIT)); }
DEV uint32_t here(uint32_t zero) {
  uint32_t d; asm volatile("mov.u32 %0,%%clock;" : "=r"(d) :: "memory"); return d & zero;
}
DEV int lane_here(uint32_t zero) {
  uint32_t d; asm volatile("mov.u32 %0,%%laneid;" : "=r"(d)); return d | here(zero);
}
DEV void delay(uint32_t n) {
  asm volatile("{\n.reg .pred p;\n.reg .u32 a,b;\nmov.u32 a,%%clock;\nW: mov.u32 b,%%clock;\nsub.u32 b,b,a;\nsetp.lt.u32 p,b,%0;\n@p bra.uni W;\n}" :: "r"(n) : "memory");
}
DEV void poll(const uint32_t* p, uint32_t n) {
  for (int it = 0; !__all_sync(0xffffffffu, ldr1(p) >= n); ++it) spin_guard(it);
}
DEV uint32_t* cnt_at(const Params& P, int n, int c, int lane) { return P.S->C + (32 * (NSUB * lane + c % NSUB) + n * 1024); }
DEV void cnt_add(uint32_t* p, uint32_t one, bool q) { asm volatile("{.reg .pred p; setp.ne.u32 p,%2,0; @p red.relaxed.gpu.global.add.u32 [%0],%1;}" :: "l"(p), "r"(one), "r"((uint32_t)q) : "memory"); }
DEV void cnt_wait(const Params& P, int n, int c, int lane) { poll(P.S->C + (32 * (NSUB * (c / (128 / NCOPY)) + lane % NSUB) + n * 1024), 128 / NSUB); }
DEV void mbar_init1(uint32_t b, int n) { asm volatile("{.reg .pred p; elect.sync _|p,0xffffffff; @p mbarrier.init.shared::cta.b64 [%0],%1;}" :: "r"(b), "r"(n) : "memory"); }
DEV void mbar_arrive1(uint32_t b) { asm volatile("{.reg .pred p; elect.sync _|p,0xffffffff; @p mbarrier.arrive.shared::cta.b64 _,[%0];}" :: "r"(b) : "memory"); }
DEV void mbar_arrive1_if(uint32_t b, int c) {
  asm volatile("{.reg .pred p,q; setp.ne.s32 q,%1,0; elect.sync _|p,0xffffffff; and.pred p,p,q; @p mbarrier.arrive.shared::cta.b64 _,[%0];}" :: "r"(b), "r"(c) : "memory");
}
DEV void mbar_expect1(uint32_t b, int bytes) { asm volatile("{.reg .pred p; elect.sync _|p,0xffffffff; @p mbarrier.arrive.expect_tx.shared::cta.b64 _,[%0],%1;}" :: "r"(b), "r"(bytes) : "memory"); }
DEV void flag_set1(uint32_t* q) { asm volatile("{.reg .pred p; elect.sync _|p,0xffffffff; @p st.relaxed.gpu.global.u32 [%0],1;}" :: "l"(q) : "memory"); }
DEV void tma3(uint32_t dst, const CUtensorMap* m, int c0, int c1, uint32_t bar) {
  asm volatile("{.reg .pred p; elect.sync _|p,0xffffffff;\n"
    "@p cp.async.bulk.tensor.3d.shared::cluster.global.mbarrier::complete_tx::bytes [%0],[%1,{%2,%3,%5}],[%4];}"
    :: "r"(dst), "l"(m), "r"(c0), "r"(c1), "r"(bar), "r"(0) : "memory");
}
DEV void tma5(uint32_t dst, const CUtensorMap* m, int c0, int c4, uint32_t bar) {
  asm volatile("{.reg .pred p; elect.sync _|p,0xffffffff;\n"
    "@p cp.async.bulk.tensor.5d.shared::cluster.global.mbarrier::complete_tx::bytes [%0],[%1,{%2,%5,%5,%5,%3}],[%4];}"
    :: "r"(dst), "l"(m), "r"(c0), "r"(c4), "r"(bar), "r"(0) : "memory");
}
DEV void bulk(uint32_t dst, const void* src, int bytes, uint32_t bar) {
  asm volatile("{.reg .pred p; elect.sync _|p,0xffffffff;\n@p cp.async.bulk.shared::cluster.global.mbarrier::complete_tx::bytes [%0],[%1],%2,[%3];}" :: "r"(dst), "l"(src), "r"(bytes), "r"(bar) : "memory");
}
DEV void bulk_store(void* dst, uint32_t src, int bytes) {
  asm volatile("{.reg .pred p; elect.sync _|p,0xffffffff;\n@p cp.async.bulk.global.shared::cta.bulk_group [%0],[%1],%2;}" :: "l"(dst), "r"(src), "r"(bytes) : "memory");
}
DEV void l2_prefetch(const void* src, int bytes) {
  asm volatile("{.reg .pred p; elect.sync _|p,0xffffffff;\n@p cp.async.bulk.prefetch.L2.global [%0],%1;}" :: "l"(src), "r"(bytes) : "memory");
}

DEV uint64_t mkdesc(uint32_t addr, uint32_t lbo, uint32_t sbo, uint32_t swz) {
  return (uint64_t)((addr >> 4) | ((lbo >> 4) << 16)) | ((uint64_t)((sbo >> 4) | (swz << 30)) << 32);
}
DEV void wg_fence() { asm volatile("wgmma.fence.sync.aligned;" ::: "memory"); }
DEV void wg_commit() { asm volatile("wgmma.commit_group.sync.aligned;" ::: "memory"); }
template <int N> DEV void wg_wait() { asm volatile("wgmma.wait_group.sync.aligned %0;" :: "n"(N) : "memory"); }
template <int N> DEV void zerov(float (&d)[N]) {
#pragma unroll
  for (int i = 0; i < N; ++i) asm volatile("mov.b32 %0,0;" : "=f"(d[i]));
}
template <int N> DEV void undef(float (&d)[N]) {
#pragma unroll
  for (int i = 0; i < N; ++i) asm volatile("" : "=f"(d[i]));
}
#define R4(d, o) "+f"(d[o]), "+f"(d[o + 1]), "+f"(d[o + 2]), "+f"(d[o + 3])
#define R8(d, o) R4(d, o), R4(d, o + 4)
#define R16(d, o) R8(d, o), R8(d, o + 8)
#define R32(d, o) R16(d, o), R16(d, o + 16)
#define L0 "%0,%1,%2,%3,%4,%5,%6,%7,%8,%9,"
#define L10(a) "%" #a "0,%" #a "1,%" #a "2,%" #a "3,%" #a "4,%" #a "5,%" #a "6,%" #a "7,%" #a "8,%" #a "9,"
#define WG_HEAD(pr, n) "{.reg .pred p; setp.ne.s32 p,%" #pr ",0;\nwgmma.mma_async.sync.aligned.m64n" #n "k16.f32.bf16.bf16 {"
DEV void wg_rs64k(float (&d)[32], const uint32_t (&a)[4], uint64_t db, int acc) {
  asm volatile(WG_HEAD(37, 64) L0 L10(1) L10(2) "%30,%31},{%32,%33,%34,%35},%36,p,1,1,0;}"
    : R32(d, 0) : "r"(a[0]), "r"(a[1]), "r"(a[2]), "r"(a[3]), "l"(db), "r"(acc));
}
DEV void wg_rs48t(float (&d)[24], const uint32_t (&a)[4], uint64_t db, int acc) {
  asm volatile(WG_HEAD(29, 48) L0 L10(1) "%20,%21,%22,%23},{%24,%25,%26,%27},%28,p,1,1,1;}"
    : R16(d, 0), R8(d, 16) : "r"(a[0]), "r"(a[1]), "r"(a[2]), "r"(a[3]), "l"(db), "r"(acc));
}
DEV void wg_rs32t(float (&d)[16], const uint32_t (&a)[4], uint64_t db, int acc) {
  asm volatile(WG_HEAD(21, 32) L0 "%10,%11,%12,%13,%14,%15},{%16,%17,%18,%19},%20,p,1,1,1;}"
    : R16(d, 0) : "r"(a[0]), "r"(a[1]), "r"(a[2]), "r"(a[3]), "l"(db), "r"(acc));
}
DEV void wg_ss48(float (&d)[24], uint64_t da, uint64_t db, int acc) {
  asm volatile(WG_HEAD(26, 48) L0 L10(1) "%20,%21,%22,%23},%24,%25,p,1,1,1,1;}" : R16(d, 0), R8(d, 16) : "l"(da), "l"(db), "r"(acc));
}
DEV void wg_ss64(float (&d)[32], uint64_t da, uint64_t db, int acc) {
  asm volatile(WG_HEAD(34, 64) L0 L10(1) L10(2) "%30,%31},%32,%33,p,1,1,0,1;}" : R32(d, 0) : "l"(da), "l"(db), "r"(acc));
}
DEV void wg_ss192(float (&d)[96], uint64_t da, uint64_t db, int acc) {
  asm volatile(WG_HEAD(98, 192) L0 L10(1) L10(2) L10(3) L10(4) L10(5) L10(6) L10(7) L10(8) "%90,%91,%92,%93,%94,%95},%96,%97,p,1,1,1,1;}"
    : R32(d, 0), R32(d, 32), R32(d, 64) : "l"(da), "l"(db), "r"(acc));
}

DEV void wg_rs192t(float (&d)[96], const uint32_t (&a)[4], uint64_t db) {
  asm volatile("wgmma.mma_async.sync.aligned.m64n192k16.f32.bf16.bf16 {" L0 L10(1) L10(2) L10(3) L10(4) L10(5) L10(6) L10(7) L10(8) "%90,%91,%92,%93,%94,%95},{%96,%97,%98,%99},%100,1,1,1,1;"
    : R32(d, 0), R32(d, 32), R32(d, 64) : "r"(a[0]), "r"(a[1]), "r"(a[2]), "r"(a[3]), "l"(db));
}

DEV float ln_sd(float s, float q, float& m) {
  m = s * (1.f / 512.f);
  return bfr(sqrt_(bfr(bfr(fmaxf(q * (1.f / 512.f) - m * m, 0.f)) + 1e-5f)));
}
DEV float4 gram(const uint32_t (&w)[8][2], int g, uint32_t zero) {
  float s[4], q[4][4];
  const uint32_t o0 = 0x3F803F80u | zero, o1 = 0x3F803F80u ^ zero;
#pragma unroll
  for (int j = 0; j < 8; ++j) {
#pragma unroll
    for (int h = 0; h < 2; ++h) { if (j < 2) mma8z(q[2 * j + h], w[j][0], w[j][1], w[j][h]); else mma8(q[2 * (j & 1) + h], w[j][0], w[j][1], w[j][h]); }
    if (j == 1) mma16z(s, w[0][0], w[0][1], w[1][0], w[1][1], o0, o1);
    else if (j & 1) mma16(s, w[j - 1][0], w[j - 1][1], w[j][0], w[j][1], o0, o1);
  }
  const bool od = g & 1;
  return make_float4(s[0], od ? q[0][1] + q[2][1] : q[0][0] + q[2][0], s[2], od ? q[1][3] + q[3][3] : q[1][2] + q[3][2]);
}
DEV void keep(uint32_t v, uint32_t zero) {
  asm volatile("{.reg .pred p; setp.ne.u32 p,%1,0; @p st.shared.u32 [%0],%0;}" :: "r"(v), "r"(zero) : "memory");
}
DEV void keep(const void* v, uint32_t zero) { asm volatile("{.reg .pred p; setp.ne.u32 p,%1,0; @p st.global.u32 [%0],%1;}" :: "l"(v), "r"(zero) : "memory"); }
struct XgAddr { uint32_t a, b; uint4* dst; };
template <bool FRAG> DEV XgAddr xg_addr(uint4* dst, uint32_t stg, int wp, int lane, uint32_t zero) {
  const int t = lane & 3, r = 4 * wp + (lane >> 3);
  XgAddr x = {stg + t * (FRAG ? 256 : 1024) + ((wp ^ t) * 32) + (lane >> 2) * 4,
              stg + r * 128 + (((lane & 7) ^ (2 * (((r >> 1) ^ (r >> 3)) & 3))) * 16), dst + (r * 256 + (lane & 7))};
  keep(x.a, zero); keep(x.b, zero); keep(x.dst, zero);
  return x;
}
template <bool FRAG> DEV void xg_put(const XgAddr& x, const uint32_t (&w)[8][2]) {
#pragma unroll
  for (int n = 0; n < 8; ++n) {
    const uint32_t b = (x.a ^ ((n & 3) * 32)) + (FRAG ? n * 1024 : (n >> 2) * 4096 + (n & 3) * 256);
    sts1(b, prmt(w[n][0], w[n][1], 0x5410)); sts1(b + 128, prmt(w[n][0], w[n][1], 0x7632));
  }
}
DEV void xg_store(const XgAddr& x) {
#pragma unroll
  for (int k = 0; k < 4; ++k) {
    const uint4 v = lds4((x.b ^ ((k & 1) * 64)) + k * 2048);
    str4(x.dst + k * 4096, nz(v.x), v.y, v.z, v.w);
  }
}
template <int N, int M> DEV void fold(float (&v)[M], int lane, int bit) {
  const bool b = lane & bit;
#pragma unroll
  for (int k = 0; k < N; ++k) { const float sn = b ? v[k] : v[k + N], kp = b ? v[k + N] : v[k]; v[k] = kp + __shfl_xor_sync(0xffffffffu, sn, bit); }
}
DEV void refetch(uint32_t dst, const uint4* src, int half, int e, int w) {
#pragma unroll 1
  for (int r = 0; r < 2; ++r) {
    if (w == 0) { mbar_expect1(B_R + 8 * e, half); bulk(dst + r * half, src + r * (half >> 4), half, B_R + 8 * e); }
    mbar_wait(B_R + 8 * e, r);
    bar_sync(NB_WG + e, 128);
  }
}
DEV uint32_t kvslot(int cg, int pos) { return (pos & 2 ? SM_XA : SM_S1) + (cg < 4 ? 5 : 2) * 8192 + (pos & 1) * 4096; }
DEV uint32_t xstage(int q, int e) { return ((q + 1) & 2) ? SM_R + ((q & 2) + e) * 16384 : e ? SM_XB : SM_XA; }
DEV void cmul(float& orr, float& oi, float ar, float ai, float br, float bi) {
  float r = ar * br - ai * bi, i = ar * bi + ai * br; orr = r; oi = i;
}
DEV void cexp_(float al, float bt, float s, float& er, float& ei) {
  float mag = ex2(al * s), ph = bt * s;
  ph -= rintf(ph);
  float ang = ph * 6.283185307179586f;
  er = mag * __cosf(ang); ei = mag * __sinf(ang);
}

#define KS 2048
DEV void put8(uint32_t a, const float (&r)[8], const float (&i)[8]) {
  sts4(a, pack2(r[0], r[1]), pack2(r[2], r[3]), pack2(r[4], r[5]), pack2(r[6], r[7]));
  sts4(a + 1024, pack2(i[0], i[1]), pack2(i[2], i[3]), pack2(i[4], i[5]), pack2(i[6], i[7]));
}
DEV void tables(const uint32_t (&pv)[8], int k4, int w, int lane) {
  PW(4 * k4 + w)
  [[maybe_unused]] const int layer = 0;
  const float dt = bfr(__expf(bflo(pv[6])));
  const float al = dt * bflo(pv[0]) * 1.4426950408889634f, bt = dt * bflo(pv[1]) * 0.15915494309189535f;
  float qr[8], qi[8], yr[8], yi[8];
  cmul(qr[0], qi[0], bflo(pv[4]), bflo(pv[5]), dt * bflo(pv[2]), dt * bflo(pv[3]));
  PROFD(2, a_par, __float_as_uint(qr[0] + al + bt));
  float e1r, e1i, eMr, eMi, eLr, eLi;
  cexp_(al, bt, 1.f, e1r, e1i); cexp_(al, -bt, 8.f, yr[1], yi[1]); cexp_(al, -bt, 64.f, eMr, eMi); cexp_(al, bt, 256.f, eLr, eLi);
  const uint32_t ad = SB + k4 * 32768 + (w & 1) * 512 + lane * 16, am = ad + (w >> 1) * KS, an = ad + (8 + 3 * (w >> 1)) * KS;
  yr[0] = 1.f; yi[0] = 0.f;
#pragma unroll
  for (int k = 1; k < 8; ++k) {
    cmul(qr[k], qi[k], qr[k - 1], qi[k - 1], e1r, e1i);
    if (k > 1) cmul(yr[k], yi[k], yr[k - 1], yi[k - 1], yr[1], yi[1]);
  }
  put8(an, qr, qi);
#pragma unroll
  for (int j = 0; j < 4; ++j) {
    put8(am + j * 2 * KS, yr, yi);
#pragma unroll
    for (int k = 0; k < 8; ++k) {
      if (j == 0 && k == 0) { yr[0] = eMr; yi[0] = eMi; } else if (j < 3) cmul(yr[k], yi[k], yr[k], yi[k], eMr, eMi);
    }
    if (j == 0) {
#pragma unroll
      for (int k = 0; k < 8; ++k) { const int o = k < 4 ? 2 * k : k < 6 ? 2 * k - 8 : k - 2; cmul(qr[k], qi[k], qr[o], qi[o], eLr, eLi); }
      put8(an + KS, qr, qi);
    } else if (j == 1) {
#pragma unroll
      for (int k = 0; k < 5; ++k) cmul(qr[k], qi[k], qr[k ? k - 1 : 6], qi[k ? k - 1 : 6], eLr, eLi);
      put8(an + 2 * KS, qr, qi);
    }
  }
  PROF(3, a_tab);
}

DEV void sts16_if(uint32_t a, uint32_t v, bool c) { asm volatile("{.reg .pred q; .reg .b16 h; setp.ne.u32 q,%2,0; cvt.u16.u32 h,%1; @q st.shared.u16 [%0],h;}" :: "r"(a), "r"(v), "r"((uint32_t)c) : "memory"); }
DEV void sts1_if(uint32_t a, uint32_t v, bool c) { asm volatile("{.reg .pred q; setp.ne.u32 q,%2,0; @q st.shared.u32 [%0],%1;}" :: "r"(a), "r"(v), "r"((uint32_t)c) : "memory"); }
DEV void taps(uint32_t dskip, int k4, int w, int lane) {
  PW(4 * k4 + w)
  [[maybe_unused]] const int layer = 0;
  fence_async_smem();
  bar_sync((k4 & 1) ? NB_WG + k4 : NB_Q, (k4 & 1) ? 128 : 448);
  float d[24];
  undef(d);
  const uint64_t da = mkdesc(SB + k4 * 32768, 1024, KS, 0);
  wg_fence();
#pragma unroll
  for (int j = 0; j < 8; ++j) wg_ss48(d, da + j * 8, da + KS / 2 + j * 8, j);
  wg_commit();
  const int b = 8 * w + (lane >> 2), t = lane & 3, id = 32 * w + lane;
  constexpr int DO = T_O - T_E;
  const uint32_t te = SM_TAP + k4 * TAP_SZ + T_E, a0 = te - 16 * b - 4 * t;
  const uint32_t a1 = a0 - 512 - 4 * t, a2 = te - 2 * (511 + b) - 64 * t, a3 = te + (T_C - T_E) - 2 * (127 + b) - 128 * t;
  wg_wait<0>();
  PROF(4, a_mma);
  {
    const uint32_t v = pack2(d[1] + d[15], d[0] + d[14] + (id ? 0.f : bflo(dskip)));
    sts1(a0 + DO - 2, v); sts16(a0 - 2, v); sts16(a0, v >> 16);
  }
  {
    const uint32_t v = pack2(d[5] + d[19], d[4] + d[18]), u = prmt(v, v, 0x3232);
    const bool lo = t < 2, k512 = id == 2;
    sts1_if(k512 ? te - 2 * 512 : a1, u, (lo && id) || k512);
    sts1_if(k512 ? te - 2 * 514 : a1 - 4, k512 ? u : v, lo || k512);
    sts1_if(k512 ? te + DO - 2 * 513 : a1 + DO - 2, u, lo || k512);
    sts16(lo ? a1 + DO - 4 : a2 + DO - 194, v);
    sts16(lo ? (id ? a1 + DO + 2 : a1) : k512 ? te + DO - 2 * 511 : a2 + DO, u);
    sts16_if(a2 - 194, v, !lo);
    sts16_if(k512 ? te + DO - 2 * 514 : a2, u, !lo);
  }
  {
    const uint32_t v = pack2(d[8] + d[22], d[9] + d[23]);
    sts16_if(id ? a3 : te - 2 * 639, v, t < 2 || id == 2);
    sts16_if(a3 - 64, v >> 16, t < 2);
    sts16_if(te + DO - 2 * 639, v, id == 0);
  }
  bar_sync(NB_WG + k4, 128);
  mbar_arrive1_if(B_K, w == 0);
}

DEV uint32_t cpy(uint32_t v, uint32_t id) {
  uint32_t d; asm volatile("prmt.b32 %0,%1,%1,%2;" : "=r"(d) : "r"(v), "r"(id)); return d;
}
DEV uint32_t uoff(int s) { return (s ^ ((s >> 3) & 3)) * 16; }
template <bool FULL> DEV void boxes(const uint32_t (&u)[10], uint32_t a, uint32_t a9, uint32_t a7, uint32_t (&pv)[4]) {
  uint32_t v[8], p[8], x[4], y[4];
#pragma unroll
  for (int j = 0; j < 8; ++j) { v[j] = prmt(u[j], u[j + 1], 0x5432); p[j] = hadd2(u[j], v[j]); }
#pragma unroll
  for (int j = 0; j < 4; ++j) { x[j] = hadd2(hadd2(p[j + 1], p[j + 2]), u[j + 3]); y[j] = hadd2(v[j + 3], p[j + 4]); }
  sts4(a + R_A5, x[0], x[1], x[2], x[3]);
  sts4(a + R_A3, y[0], y[1], y[2], y[3]);
  if (FULL) {
#pragma unroll
    for (int j = 0; j < 4; ++j) { x[j] = hadd2(x[j], hadd2(v[j], v[j + 3])); y[j] = hadd2(x[j], hadd2(u[j], u[j + 4])); pv[j] = p[j + 4]; }
    sts4(a7, x[0], x[1], x[2], x[3]);
    sts4(a9, y[0], y[1], y[2], y[3]);
  }
}
DEV uint32_t shfl_up(uint32_t v, int d) { uint32_t r; asm volatile("shfl.sync.up.b32 %0,%1,%2,0,0xffffffff;" : "=r"(r) : "r"(v), "r"(d) : "memory"); return r; }
DEV void halo(uint32_t (&u)[10], uint32_t a, uint32_t b, int lane) {
  asm volatile("{.reg .pred p,q; setp.eq.s32 p,%8,0; setp.lt.s32 q,%8,2;\n@p ld.shared.v4.u32 {%2,%3,%4,%5},[%6];\n@q ld.shared.v2.u32 {%0,%1},[%7];}"
    : "+r"(u[0]), "+r"(u[1]), "+r"(u[2]), "+r"(u[3]), "+r"(u[4]), "+r"(u[5]) : "r"(a), "r"(b), "r"(lane));
}
#define W1 4
#define ROT 2
#define G1 -1
#define G2 0
#define G3 1
#define TPS 0x7135
#define GMASK ((G1 >= 0 ? 2 : 0) | (G2 >= 0 ? 4 : 0) | (G3 >= 0 ? 8 : 0))
#define GATE1(g, n, p) if (g >= 0 && (g & 3) == p) mbar_arrive1_if(B_G + 8 * n, k4 == (g >> 2));
#define GATE(p) GATE1(G1, 0, p) GATE1(G2, 1, p) GATE1(G3, 2, p)
#define TMASK(p) (((TPS & 15) == p) | ((((TPS >> 4) & 15) == p) << 1) | ((((TPS >> 8) & 15) == p) << 2) | ((((TPS >> 12) & 15) == p) << 3))
#define TURN(p) if (TMASK(p) == 15) bar_arrive(NB_T + 1 + k4, 256); else if (TMASK(p)) { if ((TMASK(p) >> k4) & 1) bar_arrive(NB_T + 1 + k4, 256); }
DEV void w_load(const CUtensorMap* mW, int cg, int h) {
  mbar_expect1(B_W + 8 * h, 24576);
  tma3(SM_S0 + (h & 3) * 24576, mW, 64 * cg, 64 * h, B_W + 8 * h);
}

DEV void conv(const Params& P, const CUtensorMap* mW, int c, int k4, int w, int layer) {
  const uint32_t zero = P.zero;
  PW(4 * k4 + w)
  int lane = lane_here(zero);
  const int g = lane >> 2, t = lane & 3, v = w ^ (ROT * (k4 & 1)), tid = 32 * v + lane;
  const uint32_t reg = SM_R + k4 * 16384, tp = SM_TAP + k4 * TAP_SZ;
  const uint32_t g0 = tp + ((g & 1) ? T_O : T_E) + 2 * (2 * t - g);
  uint32_t F[18][4], U[20], qc[4][4];
#define LO(q, a) q[0] = lds1(a); q[2] = lds1(a + 16);
#define HI(q, a) q[1] = lds1(a - 128); q[3] = lds1(a - 112);
  {
    const uint32_t ga = g0 - 32 * (w & 1) - 576 * (w >> 1), g2 = tp + T_C - 258 - 32 * w + 4 * (t - g);
    F[0][2] = lds1(ga + 48);
#pragma unroll
    for (int j = 0; j < 8; ++j) { F[j][0] = lds1(ga + 32 - 32 * j); F[j][1] = lds1(ga + 16 - 32 * j); }
#pragma unroll
    for (int j = 0; j < 20; ++j) U[j] = lds1(ga - 224 - 16 * j);
#pragma unroll
    for (int j = 0; j < 4; ++j) { LO(qc[j], g2 + 32 * j) HI(qc[j], g2 + 32 * j) }
  }
  if (layer) { mbar_wait(B_ED, 0); mbar_wait(B_ED + 8, 0); }
  sts4z_if(reg + lane * 16 + (w ? w * 3584 + 1024 : 0), w < 3);
  PROF(5, a_pre);
  if (k4 == 3 && w == 3) {
    mbar_wait(B_E, layer);
    mbar_wait(B_K, 0);
#pragma unroll
    for (int h = 0; h < 4; ++h) w_load(mW, c & 7, h);
  }
  const uint32_t bo = reg + R_B + tid * 16 + (v >> 1) * 1056, be = tid == 127 ? reg + R_B + 1024 : bo + (tid == 63 ? 2112 : 1056);
  const uint32_t a9 = (lane & 1) ? be : bo, a7 = (lane & 1) ? bo : be, ua = reg + R_U + uoff(tid);
  const uint32_t h1 = reg + R_U + v * 512 - 64, h2 = h1 + 24 - 16 * lane;
  keep(a9 & a7 & ua & h2, zero);
  mbar_wait(k4 && ((GMASK >> k4) & 1) ? B_G - 8 + 8 * k4 : B_E, layer);
  PROF(6, a_x);
  uint4 x[2];
  uint32_t pv[4];
  {
    uint4 s[4];
    uint32_t u[2][10];
#pragma unroll
    for (int z = 0; z < 2; ++z) { x[z] = lds4(reg + R_B + tid * 16 + z * 2048); s[2 * z] = lds4(SM_RES + tid * 16 + z * 2048); s[2 * z + 1] = lds4(SM_RES + tid * 16 + z * 2048 + 4096); }
    for (int it = 0;; ++it) {
      const uint32_t m = min(min(min(x[0].x, min(s[0].x, s[0].z)), min(s[1].x, s[1].z)), min(min(x[1].x, min(s[2].x, s[2].z)), min(s[3].x, s[3].z)));
      if (__builtin_expect(__all_sync(0xffffffffu, m != 0u), 1)) break;
      EVENT(16 + layer * 4 + k4);
      const int o = tid | here(zero);
#pragma unroll
      for (int z = 0; z < 2; ++z) x[z] = ldr4(&P.S->XG[layer][(128 * k4 + c) * 256 + o] + z * 128);
#pragma unroll
      for (int z = 0; z < 4; ++z) {
        s[z] = ldr4(&P.S->SR[layer][c >> 4][o] + ((z >> 1) * 128 + (z & 1) * 256));
        sts4(SM_RES + tid * 16 + (z >> 1) * 2048 + (z & 1) * 4096, s[z].x, s[z].y, s[z].z, s[z].w);
      }
      spin_guard(it);
    }
#pragma unroll
    for (int z = 0; z < 2; ++z) {
      u[z][6] = hmul2(hsub2(x[z].x, s[2 * z].y), s[2 * z].x); u[z][7] = hmul2(hsub2(x[z].y, s[2 * z].w), s[2 * z].z);
      u[z][8] = hmul2(hsub2(x[z].z, s[2 * z + 1].y), s[2 * z + 1].x); u[z][9] = hmul2(hsub2(x[z].w, s[2 * z + 1].w), s[2 * z + 1].z);
      sts4(ua + z * 2048, u[z][6], u[z][7], u[z][8], u[z][9]);
    }
    u[1][0] = 0; u[1][1] = s[3].x; u[1][2] = s[2].x; u[1][3] = s[2].y; u[1][4] = s[2].z; u[1][5] = s[2].w;
    if (v < 2) {
#pragma unroll
      for (int j = 1; j < 6; ++j) u[1][j] = shfl_up(u[1][j < 2 ? 8 + j : 4 + j], j < 2 ? 2 : 1);
    }
#pragma unroll
    for (int j = 0; j < 6; ++j) u[0][j] = shfl_up(u[0][j < 2 ? 8 + j : 4 + j], j < 2 ? 2 : 1);
    bar_sync(NB_WG + k4, 128);
    GATE(0)
    PROF(7, a_u);
    halo(u[0], h1, h2, lane);
    halo(u[1], h1 + 2048, h2 + 2048, lane + 16 * (v & 2));
    sts4z_if(reg + R_B + 1040, tid == 0);
    boxes<true>(u[0], reg + tid * 16, a9, a7, pv);
    if (v < 2) boxes<false>(u[1], reg + tid * 16 + 2048, 0, 0, pv);
  }
  GATE(1)
  fence_async_smem();
  if (k4 == 3 && w < 3) {
    const uint32_t src = SM_RES + 8192 + w * 2048, f = (w >> 1) - 1;
#pragma unroll
    for (int z = 0; z < 4; ++z) sts4(src + lane * 16 + z * 512, f, f, f, f);
    fence_async_smem();
    __syncwarp();
    if (w < 2) {
#pragma unroll
      for (int z = 0; z < 4; ++z) bulk_store(&P.S->O[((c >> 3) * 16 + w * 8 + (c & 7)) * 512] + z * 128, src, 2048);
    } else {
#pragma unroll
      for (int z = 0; z < 2; ++z) {
        bulk_store(&P.S->H[(c + 8) * 256] + z * 128, src, 2048);
        bulk_store(P.S->F + ((c >> 3) * 64 + 4 * (c & 7)) + z * 32, src, 16);
      }
      bulk_store(&P.S->PS[c * 64], src, 1024);
      bulk_store(&P.S->ST[c * 4], src, 64);
      if (c < 5) bulk_store(P.S->C + (c + 5 - 5 * layer) * 1024, src, 128 * NCOPY * NSUB);
    }
    asm volatile("cp.async.bulk.commit_group;" ::: "memory");
  }
  const uint32_t id = opq(0x3210u);
#pragma unroll
  for (int j = 0; j < 8; ++j) { F[j][3] = cpy(F[j][0], id); if (j) F[j][2] = cpy(F[j - 1][1], id); }
  PROF(8, a_box);
  bar_sync(NB_T + k4, k4 ? 256 : 128);
  PROF(9, a_turn);
  float acc[32], f1[24], f3[16];
  uint32_t qa[4][4], qb[4][4], fp[4];
  const uint64_t db = mkdesc(reg + R_U, 16, 512, 2) + 2;
#define STEP(mm, n) wg_fence(); mm; wg_commit(); wg_wait<n>();
#define D(j, n) STEP(wg_rs64k(acc, F[j], db - 2 * j, j), n)
#define C(j, n) STEP(wg_rs32t(f3, qc[j], mkdesc(reg + R_B, 128, 1040, 0) + 16 * j, j), n)
#define NIL(q, y) { const uint32_t z = y & zero; q[2][1] = cpy(z, 0); q[2][3] = cpy(z, 1); q[3][1] = cpy(z, 2); q[3][3] = cpy(z, 3); }
#define X(j) F[j][0] = cpy(U[2 * j - 16], ix); F[j][1] = cpy(U[2 * j - 15], ix); F[j][3] = cpy(F[j][0], ix); F[j][2] = cpy(F[j - 1][1], ix);
  const uint32_t g1 = g0 - 2 * 576 - 16 * w;
  const uint64_t d1 = mkdesc(reg + R_A5, 128, 512, 0);
  constexpr int O3 = (R_A3 - R_A5) / 16;
  uint32_t ix = id;
  undef(acc);
  D(0, 4) TURN(0) D(1, 4) D(2, 4) D(3, 4) D(4, 4) D(5, 2)
  undef(f3);
  C(0, 3) C(1, 3) TURN(1) C(2, 3) X(8) C(3, W1) X(9) LO(qa[0], g1)
  D(6, W1) HI(qa[0], g1) X(10) D(7, W1) LO(qa[1], g1 + 32) X(11) D(8, W1) HI(qa[1], g1 + 32) D(9, 4) LO(qa[2], g1 - 64)
  fp[0] = pack2(f3[0], f3[1]); fp[1] = pack2(f3[4], f3[5]); fp[2] = pack2(f3[8] + f3[2], f3[9] + f3[3]); fp[3] = pack2(f3[12] + f3[6], f3[13] + f3[7]);
  ix |= fp[0] & fp[1] & fp[2] & fp[3] & zero;
  X(12) D(10, 4) TURN(2) LO(qa[3], g1 - 32) X(13) X(14) D(11, 4) LO(qb[0], g1 - 192) X(15) D(12, 4) HI(qb[0], g1 - 192) X(16)
  D(13, 4) LO(qb[1], g1 - 160) X(17) D(14, 4) TURN(3) HI(qb[1], g1 - 160) NIL(qa, qa[1][0])
  D(15, 4) LO(qb[2], g1 - 256) D(16, 3) LO(qb[3], g1 - 224) NIL(qb, qa[1][1]) D(17, 2) TURN(4)
  PROF(10, a_den);
  undef(f1);
  wg_fence();
#pragma unroll
  for (int j = 0; j < 4; ++j) wg_rs48t(f1, qa[j], d1 + 16 * (j & 1) - 32 * (j >> 1), j);
  wg_commit();
  wg_wait<1>();
  TURN(5)
  wg_fence();
#pragma unroll
  for (int j = 0; j < 4; ++j) wg_rs48t(f1, qb[j], d1 + O3 + 16 * (j & 1) - 32 * (j >> 1), 1);
  wg_commit();
  TURN(6)
  lane = lane_here(zero);
  bar_sync(NB_WG + k4, 128);
  {
    const int p = (lane + 9 * (w >> 1)) & 31;
    const uint32_t ya = reg + ((w >> 1) ? R_B : R_U) + p * 64 + (((2 * (w & 1)) ^ ((p >> 1) & 3)) * 16), up = p < lane ? 2048 : 0;
#pragma unroll
    for (int z = 0; z < 4; ++z) {
      const float* a = acc + 16 * (z >> 1) + 2 * (z & 1);
      stsm4t((ya + (up ^ ((z >> 1) * 2048))) ^ ((z & 1) * 16), pack2(a[0], a[1]), pack2(a[4], a[5]), pack2(a[8], a[9]), pack2(a[12], a[13]));
    }
  }
  asm volatile("cp.async.bulk.wait_group 0;" ::: "memory");
  const uint32_t fa = reg + R_A5 + (lane >> 3) * 512 + w * 128 + (lane & 7) * 16;
  const uint32_t fc = reg + R_A3 + uoff(64 * (lane >> 4) + 16 * w + 2 * (lane & 7) + 1 - ((lane >> 3) & 1));
  uint32_t k1024 = lds16(tp + T_E - 2 * 639 + (fa & fc & zero));
  wg_wait<0>();
  GATE(2)
  PROF(11, a_far);
  bar_sync(NB_WG + k4, 128);
  stsm4(fc, fp[0], fp[1], fp[2], fp[3]);
  stsm4(fa, pack2(f1[0], f1[1]), pack2(f1[4], f1[5]), pack2(f1[8] + f1[2], f1[9] + f1[3]), pack2(f1[12] + f1[6], f1[13] + f1[7]));
  stsm2(fa + 2048, pack2(f1[16] + f1[10], f1[17] + f1[11]), pack2(f1[20] + f1[14], f1[21] + f1[15]));
  {
    const int o = 32 * v + lane;
    const uint32_t a = reg + uoff(o), b = reg + R_A5 + o * 16;
    uint4 y[2] = {hadd8(lds4(a + R_U), lds4(o >= 36 ? a + R_B : reg)), hadd8(lds4(a + R_U + 2048), lds4(a + R_B + 2048))};
    bar_sync(NB_WG + k4, 128);
    TURN(7)
    PROF(12, a_sts);
    const uint4 f = lds4(v >= 2 ? b - 1024 : reg), f2 = lds4(b + 1024);
    uint4 h = lds4(a + R_A3);
    const int e0 = (o >> 3) * 8192 + (128 * k4 + c) * 16 + (((o & 4) + ((o >> 1) & 1)) ^ (c & 7)) * 2 + (o & 1);
    const uint32_t me = (e0 & 3) == ((c >> 1) & 3), m0 = me & ~c, m1 = me & c, tag = 1 - layer;
    uint32_t* cp = cnt_at(P, 1 + 5 * layer + k4, c, lane);
    keep(cp, zero);
    k1024 = prmt(k1024, k1024, 0x1010);
    h = make_uint4(hfma2(pv[0], k1024, h.x), hfma2(pv[1], k1024, h.y), hfma2(pv[2], k1024, h.z), hfma2(pv[3], k1024, h.w));
    y[0] = hadd8(y[0], f); y[1] = hadd8(y[1], hadd8(f2, h));
    cnt_add(cp, 1 | (y[0].x & y[1].x & zero), (o ^ 96) < NCOPY);
#pragma unroll
    for (int z = 0; z < 2; ++z) {
      const uint4 r = hadd8(x[z], y[z]);
      str2((uint2*)P.S->XF + e0 + z * 131072, tagged(prmt(r.x, r.y, 0x5410), m0, tag), tagged(prmt(r.z, r.w, 0x5410), m1, tag));
      str2((uint2*)P.S->XF + (e0 ^ 4) + z * 131072, tagged(prmt(r.x, r.y, 0x7632), m0, tag), tagged(prmt(r.z, r.w, 0x7632), m1, tag));
    }
  }
  TURN(9)
  GATE(3)
  PROF(13, a_out);
}

#define WGATE 1
#define FH 1
#define QPIN 1
#define XORD 1
DEV void x_load(const Params& P, int c, int q, int layer) {
#pragma unroll
  for (int z = 0; z < 2; ++z) {
    const int e = z ^ (XORD && q == 3 && !(c & 4));
    mbar_expect1(B_X + 16 * q + 8 * e, 16384);
    bulk(xstage(q, e), P.S->XF + ((2 * (c >> 3) + 1 - e) * 4096 + q * 1024), 16384, B_X + 16 * q + 8 * e);
  }
}

DEV void means(uint32_t (&m)[4], int row, int lane, int layer, uint32_t zero) {
  mbar_wait(B_CS, 0);
  mbar_wait(B_ST, layer);
  const uint32_t a = SM_MISC + row * 4 + (lane & 28), k = (lane & 3) ? 0u : ~0u;
  m[0] = lds1(a) & k; m[1] = lds1(a + 32) & k; m[2] = m[0] & zero; m[3] = m[1] & zero;
}

DEV void attn_phase(const Params& P, int c, int e, int w, int lane, int layer) {
  PW(4 * e + w)
  const int cg = c & 7, J = 2 * (c >> 3) + 1 - e;
  float acc[96];
  zerov(acc);
  uint32_t m[4] = {0, 0, 0, 0};
#pragma unroll 1
  for (int q = 0;; ++q) {
    const uint64_t da = mkdesc(xstage(q, e), 16, 1024, 1), db = mkdesc(SM_S0 + (q & 1) * 49152, 8192, 1024, 1);
    const uint32_t wr = mbar_test2(B_W + 16 * q, layer), xa = xstage(q, e) + w * 4096 + lane * 132;
    mbar_wait(B_X + 16 * q + 8 * e, layer);
    for (int it = 0;; ++it) {
      const uint32_t ok = both(lds1(xa), lds1(xa ^ 32), layer) & both(lds1(xa ^ 64), lds1(xa ^ 96), layer);
      if (__all_sync(0xffffffffu, ok & 1)) break;
      EVENT(8 * layer + 2 * q + e);
#pragma unroll 1
      for (int j = 0; j < 8; ++j) cp16(xstage(q, e) + w * 4096 + j * 512 + lane * 16, P.S->XF + (J * 4096 + q * 1024 + w * 256 + j * 32 + lane));
      asm volatile("cp.async.wait_all;" ::: "memory");
      fence_async_smem();
      __syncwarp();
      spin_guard(it);
    }
    bool all = __all_sync(0xffffffffu, wr);
    if (q == 0 && e && w == 0) {
      bar_sync(NB_H, 256);
      cnt_wait(P, 2 + 5 * layer, c, lane);
      x_load(P, c, 1, layer);
      PROF(27, m_xi);
    }
    if (q == 3 && e) means(m, 16 * w, lane, layer, P.zero);
    if (!all) { mbar_wait(B_W + 16 * q, layer); all = mbar_test(B_W + 16 * q + 8, layer); }
    bar_sync(e ? NB_Q : q ? NB_T : NB_T + 4, 256);
    PROF(14 + q, m_q);
    wg_fence();
#pragma unroll
    for (int k = 0; k < 8; ++k) {
      if (k == 4) { wg_commit(); if (!all) mbar_wait(B_W + 16 * q + 8, layer); wg_fence(); }
      wg_ss192(acc, da + k * 128, db + (k >> 2) * 1536 + (k & 3) * 128, 1);
    }
    wg_commit();
    if (q == 3) break;
    bar_arrive(e ? NB_T : NB_Q, 256);
    if (FH) { wg_wait<1>(); mbar_arrive1_if(B_FH + 8 * q, e && q < 2); }
    wg_wait<0>();
    mbar_arrive1(B_F + 8 * q);
  }
  const int pos = 2 - 2 * e + (w >> 1);
  uint4* h = P.S->H + ((c + 8) * 256 + (w & 1) * 128 + lane);
  const uint32_t kw = kvslot(cg, pos + 1) + (w & 1) * 2048 + lane * 16;
  {
    if (!e) means(m, 64 + 16 * w, lane, layer, P.zero);
    PROF(28, m_sub);
    wg_fence();
    wg_rs192t(acc, m, mkdesc(SM_CS, 0, 32, 0));
    wg_commit();
    bar_arrive_if(NB_Q, 256, !e);
    keep(h, kw & P.zero);
    mbar_wait(B_F + 16, layer);
    wg_wait<0>();
    mbar_arrive1(B_F + 24);
  }
  PROF(18, m_qkv);
  uint32_t Q[4][4], K[4][3][2], V[4][3][2];
  uint32_t pin = P.zero;
#pragma unroll
  for (int z = 0; z < 4; ++z) {
    V[z][1][0] = pack2(acc[64 + 8 * z], acc[65 + 8 * z]); V[z][1][1] = pack2(acc[68 + 8 * z], acc[69 + 8 * z]);
    K[z][1][0] = pack2(acc[32 + 8 * z], acc[33 + 8 * z]); K[z][1][1] = pack2(acc[36 + 8 * z], acc[37 + 8 * z]);
    pin &= V[z][1][0] & V[z][1][1];
    K[z][2][0] = nz(pack2(acc[34 + 8 * z], acc[35 + 8 * z])); K[z][2][1] = pack2(acc[38 + 8 * z], acc[39 + 8 * z]);
    V[z][2][0] = pack2(acc[66 + 8 * z], acc[67 + 8 * z]); V[z][2][1] = pack2(acc[70 + 8 * z], acc[71 + 8 * z]);
    str4_if(h + z * 32, K[z][2][0], K[z][2][1], V[z][2][0], V[z][2][1], pos == 3);
  }
#pragma unroll
  for (int z = 0; z < 8; ++z) V[z >> 1][2][z & 1] = movm(z < 7 ? V[z >> 1][2][z & 1] : V[3][2][1] | pin);
  if (pos == 0) mbar_wait(B_F + 24, layer);
#pragma unroll
  for (int z = 0; z < 4; ++z) sts4_if(kw + z * 512, K[z][2][0], K[z][2][1], V[z][2][0], V[z][2][1], pos < 3);
  bar_arrive(NB_H + pos + 1, 128);
  PROF(19, m_kv);
  lane |= here(P.zero);
  int g = lane >> 2, t = lane & 3;
  const uint32_t ra = SM_STAT + 256 + (32 - 32 * e + 8 * w) * 16, ob = e ? SM_S1 : SM_XA;
  const float r0 = lds1f(ra + (g >> 1) * 16 + (g & 1) * 4), r1 = lds1f(ra + 64 + (g >> 1) * 16 + (g & 1) * 4);
  const uint4 k1 = lds4(ra + 16 * t), k2 = lds4(ra + 64 + 16 * t);
#pragma unroll
  for (int z = 0; z < 8; ++z) {
    V[z >> 1][1][z & 1] = movm(V[z >> 1][1][z & 1]);
    Q[z >> 1][2 * (z & 1)] = pack2(acc[4 * z], acc[4 * z + 1]);
    Q[z >> 1][2 * (z & 1) + 1] = pack2(acc[4 * z + 2], acc[4 * z + 3]);
    pin &= Q[z >> 1][2 * (z & 1)] & Q[z >> 1][2 * (z & 1) + 1];
  }
  {
    const bool p0 = 2 * t > g, p1 = 2 * t + 1 > g, first = c < 8 && pos == 0;
    const uint32_t M = (p0 ? 0xFFFFu : 0u) | (p1 ? 0xFFFF0000u : 0u);
    const float sc0 = r0 * (0.25f * 1.4426950408889634f), sc1 = r1 * (0.25f * 1.4426950408889634f);
    const float sk2 = __uint_as_float(p0 ? k1.x : k2.x) * sc1, sk3 = __uint_as_float(p1 ? k1.y : k2.y) * sc1;
    const int oo = cg * 512 + (2 * (w & 2) + (w & 1)) * 64 + (lane ^ (g >> 1));
    uint4* O = P.S->O + (J * 4096 + oo);
    keep(oo, pin & M & __float_as_uint(sk2) & __float_as_uint(sk3) & __float_as_uint(sc0));
    mbar_wait(B_F + 24, layer);
    float L[4][4];
#pragma unroll
    for (int z = 0; z < 4; ++z) {
      float S[4];
      mma16z(L[z], Q[z][0], Q[z][1], Q[z][2], Q[z][3], K[z][1][0], K[z][1][1]);
      mma16z(S, Q[z][0], Q[z][1], Q[z][2], Q[z][3], K[z][2][0], K[z][2][1]);
      L[z][2] = (p0 ? L[z][2] : S[2]) * sk2; L[z][3] = (p1 ? L[z][3] : S[3]) * sk3;
      if (QPIN) pin &= __float_as_uint(L[z][2]) & __float_as_uint(L[z][3]);
    }
    bar_sync(NB_H + pos + pin, pos ? 128 : 160);
    const uint4 k0 = lds4(ra - 192 + 16 * t);
#pragma unroll
    for (int z = 0; z < 4; ++z) {
      const uint4 hv = lds4(kvslot(cg, pos) + (w & 1) * 2048 + lane * 16 + z * 512);
      K[z][0][0] = hv.x; K[z][0][1] = hv.y; V[z][0][0] = hv.z; V[z][0][1] = hv.w;
    }
    PROF(20, m_halo);
    const float sk0 = __uint_as_float(p0 ? k0.x : k1.x) * sc0, sk1 = __uint_as_float(p1 ? k0.y : k1.y) * sc0;
    const uint32_t rm[4] = {k0.z & M, k1.z & ~M, k1.z & M, k2.z & ~M}, s0 = k0.w | P.zero, s1 = k1.w | P.zero;
#pragma unroll
    for (int h2 = 0; h2 < 2; ++h2) {
      uint32_t A[2], B[2], mx[2];
#pragma unroll
      for (int z = 0; z < 2; ++z) {
        const int h = 2 * h2 + z;
        float S[4];
        mma16z(S, Q[h][0], Q[h][1], Q[h][2], Q[h][3], K[h][0][0], K[h][0][1]);
        if (first) { S[0] = __uint_as_float(0xFF800000u); S[1] = S[0]; }
        A[z] = pack2((p0 ? S[0] : L[h][0]) * sk0, L[h][2]);
        B[z] = pack2((p1 ? S[1] : L[h][1]) * sk1, L[h][3]);
      }
#pragma unroll
      for (int z = 0; z < 2; ++z) mx[z] = hmax2(A[z], B[z]);
#pragma unroll
      for (int z = 0; z < 2; ++z) mx[z] = hmax2(mx[z], __shfl_xor_sync(0xffffffffu, mx[z], 1));
#pragma unroll
      for (int z = 0; z < 2; ++z) mx[z] = hmax2(mx[z], __shfl_xor_sync(0xffffffffu, mx[z], 2));
      float Oa[2][3][4];
#pragma unroll
      for (int z = 0; z < 2; ++z) {
        const int h = 2 * h2 + z;
        const uint32_t a = hsub2(A[z], mx[z]), b = hsub2(B[z], mx[z]);
        const uint32_t w0 = pack2(ex2(bflo(a)), ex2(bflo(b))), w1 = pack2(ex2(bfhi(a)), ex2(bfhi(b)));
        const uint32_t u0 = hmul2(w0, rm[0]), u1 = hmul2(w0, rm[1]), u2 = hmul2(w1, rm[2]), u3 = hmul2(w1, rm[3]);
        const uint32_t z0 = w0 & P.zero, z1 = w1 & P.zero;
        mma16z(Oa[z][2], u0, z0, u1, u2, s0, s1);
#pragma unroll
        for (int d = 0; d < 2; ++d) mma16z(Oa[z][d], u0, z0, u1, u2, V[h][0][d], V[h][1][d]);
        mma8(Oa[z][2], z1, u3, k2.w);
#pragma unroll
        for (int d = 0; d < 2; ++d) mma8(Oa[z][d], z1, u3, V[h][2][d]);
      }
#pragma unroll
      for (int r = 0; r < 4; r += 2) {
        const float i0 = rcp(Oa[0][2][r]), i1 = rcp(Oa[1][2][r]);
        const uint32_t o0 = pack2(Oa[0][0][r] * i0, Oa[0][0][r + 1] * i0), o1 = pack2(Oa[0][1][r] * i0, Oa[0][1][r + 1] * i0);
        const uint32_t o2 = pack2(Oa[1][0][r] * i1, Oa[1][0][r + 1] * i1), o3 = pack2(Oa[1][1][r] * i1, Oa[1][1][r + 1] * i1);
        str4(O + h2 * 32 + r * 64, o0, o1, o2, o3);
        sts4(ob + oo * 16 + h2 * 512 + r * 1024, o0, o1, o2, o3);
      }
    }
  }
  bar_arrive(NB_T + 1 + e, 160);
  fence_async_smem();
  PROF(21, m_att);
  lane = lane_here(P.zero); g = lane >> 2; t = lane & 3;
  uint32_t res[8][2];
  mbar_wait(B_RES, layer);
  {
    const uint32_t a = SM_RES + e * 8192 + (lane >> 4) * 1024 + (lane & 7) * 128 + (((2 * (w & 2) + ((lane >> 2) & 2) + (w & 1)) ^ (lane & 7)) * 16);
#pragma unroll
    for (int j = 0; j < 8; j += 2) ldsm4t(res[j][0], res[j][1], res[j + 1][0], res[j + 1][1], a + j * 1024);
  }
  PROF(26, m_res);
  if (WGATE) bar_sync(NB_T, 256); else bar_sync(NB_WG + e, 128);
  XgAddr xa = xg_addr<true>(P.S->XG[1] + (64 * cg * 256 + 8 * J), ob, w, lane, P.zero);
  uint4* ps = &P.S->PS[((4 * J + w) * 8 + cg) * 8 + g];
  keep(ps, P.zero);
  if (layer) {
    xa.a = ob + w * 2048 + (lane & 15) * 128 + (((lane >> 4) ^ (lane & 7)) * 16);
    xa.b = ob + w * 2048 + (lane >> 3) * 128 + (((lane & 7) ^ (lane >> 3)) * 16);
    xa.dst = (uint4*)P.out + ((64 * J + 16 * w + 2 * (lane >> 3)) * 64 + 8 * cg + (lane & 7));
  }
  uint32_t y[8][2];
#pragma unroll 1
  for (int it = 0;; ++it) {
    float ac[32];
#pragma unroll
    for (int j = 0; j < 16; ++j) {
      asm volatile("shl.b32 %0,%1,16;" : "=f"(ac[2 * j]) : "r"(res[j >> 1][j & 1]));
      asm volatile("and.b32 %0,%1,0xFFFF0000;" : "=f"(ac[2 * j + 1]) : "r"(res[j >> 1][j & 1]));
    }
#pragma unroll 1
    for (int n = 0; n < 8; ++n) {
      const int s = n == 0 ? cg : n - (n <= cg);
      mbar_wait(n ? B_O + 64 * e + 8 * s : B_WO, layer);
      if (n == 1) PROF(22, m_o1);
      if (n == 7) PROF(23, m_o7);
      const uint64_t da = mkdesc(ob + s * 8192, 16, 1024, 2), db = mkdesc(SM_R + s * 8192, 16, 1024, 1);
      wg_fence();
#pragma unroll
      for (int k = 0; k < 4; ++k) wg_ss64(ac, da + (k >> 1) * 32 + (k & 1) * 2, db + k * 128, 1);
      wg_commit();
    }
    wg_wait<0>();
    const bool bad = ac[0] != ac[0] || ac[2] != ac[2];
#pragma unroll
    for (int j = 0; j < 8; ++j) {
      y[j][0] = pack2(ac[4 * j], ac[4 * j + 1]); y[j][1] = pack2(ac[4 * j + 2], ac[4 * j + 3]);
    }
    if (!bar_any(NB_WG + e, 128, bad) || it == 16) break;
    EVENT(24 + 2 * layer + e);
    refetch(ob, P.S->O + J * 4096, 32768, e, w);
  }
  PROF(24, m_wo);
  if (layer == 0) {
    const float4 s = gram(y, g, P.zero);
    xg_put<true>(xa, y);
    str4_if(ps, nz(__float_as_uint(s.x)), __float_as_uint(s.y), __float_as_uint(s.z), __float_as_uint(s.w), t == (g >> 1));
    mbar_arrive1(B_ED + 8 * e);
    bar_sync(NB_WG + e, 128);
    xg_store(xa);
    bar_arrive(NB_T + 3, 288);
  } else {
#pragma unroll
    for (int j = 0; j < 8; j += 2) stsm4(xa.a ^ (j * 16), y[j][0], y[j][1], y[j + 1][0], y[j + 1][1]);
    __syncwarp();
#pragma unroll
    for (int k = 0; k < 4; ++k) {
      const uint4 v = lds4((xa.b ^ ((k & 1) * 64)) + k * 512);
      stw4(xa.dst + ((k & 1) * 8 + (k >> 1)) * 64, v.x, v.y, v.z, v.w);
    }
  }
  PROF(25, m_epi);
}

#define HDELAY 300
#define ODELAY 200
#define PDELAY 0
#define FDELAY 300
#define CSP 0
#define CSU 4
#define PHOLD 0
#define XDEL 300
#define WOQ 2
#define H5 1
#define SRDELAY 350
#define ZPACE 20

DEV void o_load(const Params& P, int c, int e, int lane, int layer) {
  PW(8 + e)
  const int J = 2 * (c >> 3) + 1 - e;
#pragma unroll 1
  for (int s = 0; s < 8; ++s) mbar_expect1(B_O + 64 * e + 8 * s, s == (c & 7) ? 0 : 8192);
  const uint4* src = P.S->O + J * 4096;
  const uint32_t* fp = P.S->F + (J * 32 + (lane & 28));
  keep(fp, P.zero);
  bar_sync(NB_T + 1 + e, 160);
  flag_set1(P.S->F + (J * 32 + 4 * (c & 7)));
  if (ODELAY) delay(ODELAY);
  PROF(26, a_go);
  poll(fp, 1);
  PROF(25, h_seen);
  bar_sync_if(NB_Q, 64, e);
#pragma unroll 1
  for (int n = 0; n < 7; ++n) {
    const int s = n + (n >= (c & 7));
    bulk((e ? SM_S1 : SM_XA) + s * 8192, src + s * 512, 8192, B_O + 64 * e + 8 * s);
  }
  bar_arrive_if(NB_Q, 64, !e);
  PROF(28, a_o);
}

DEV void stats(const Params& P, int c, int w, int lane, int layer) {
  PW(12 + w)
  lane = opq(lane);
  const int r = (lane & 6) + ((lane >> 3) & 1), k = (2 * (c & 3) + (lane & 1)) ^ r, e = 1 - ((c >> 2) & 1);
  const uint32_t o = (32 * w + 8 * (lane >> 4) + r) * 128 + k * 16;
  const uint32_t mk = ((k & 1) == (r >> 2)) << (r & 3), tag = 1 - layer;
  float v[16];
#pragma unroll
  for (int z = 0; z < 16; ++z) v[z] = 0.f;
#pragma unroll 1
  for (int q = 0; q < 4; ++q) {
    mbar_wait(B_X + 16 * q + 8 * e, layer);
    PROF(19 + q, s_l);
    uint4 x, y;
    for (int it = 0;; ++it) {
      x = lds4v(xstage(q, e) + o); y = lds4v(xstage(q, e) + o + 2048);
      const uint32_t bad = (((x.x ^ tag) | (y.x ^ tag)) & mk) | (((x.y ^ tag) | (y.y ^ tag)) & (mk >> 1)) |
                           (((x.z ^ tag) | (y.z ^ tag)) & (mk >> 2)) | (((x.w ^ tag) | (y.w ^ tag)) & (mk >> 3));
      if (!__any_sync(0xffffffffu, bad & 1)) break;
      spin_guard(it);
    }
    mbar_arrive1(B_F + 8 * q);
    const uint32_t ws[8] = {x.x, x.y, x.z, x.w, y.x, y.y, y.z, y.w};
#pragma unroll
    for (int z = 0; z < 8; ++z) {
      const float lo = bflo(ws[z]), hi = bfhi(ws[z]);
      float* u = v + 4 * (z & 3);
      u[0] += lo; u[1] += lo * lo; u[2] += hi; u[3] += hi * hi;
    }
  }
  PROFD(14, s_part, __float_as_uint(v[0]));
  fold<8>(v, lane, 16); fold<4>(v, lane, 8); fold<2>(v, lane, 4); fold<1>(v, lane, 2);
  PROFD(16, s_fold, __float_as_uint(v[0]));
  if (w) {
    sts1(SM_MISC - 128 + w * 128 + lane * 4, __float_as_uint(v[0]));
    bar_arrive(NB_P, 128);
  } else {
    bar_sync(NB_P, 128);
    v[0] += lds1f(SM_MISC + lane * 4) + lds1f(SM_MISC + 128 + lane * 4) + lds1f(SM_MISC + 256 + lane * 4);
    float m;
    const float sd = ln_sd(v[0], __shfl_xor_sync(0xffffffffu, v[0], 2), m);
    if (!(lane & 2)) str1((uint32_t*)P.S->ST + (16 * c + 8 * (lane & 1) + (lane >> 2)), pack2(m, sd));
    sts4(SM_STAT - 32 + min(lane, 17) * 16, 0x3F800000u, 0x3F800000u, 0x3F803F80u, 0x3F803F80u);
    fence_async_smem();
    PROF(17, s_pub);
    uint4 s;
    for (int it = 0;; ++it) {
      s = ldr4(P.S->ST + ((c >> 3) * 32 + lane));
      if (__all_sync(0xffffffffu, min4(s) != 0u)) break;
      spin_guard(it);
    }
    PROF(18, s_seen);
    const float r0 = rcp(bfhi(s.x)), r1 = rcp(bfhi(s.y)), r2 = rcp(bfhi(s.z)), r3 = rcp(bfhi(s.w));
    const uint32_t sg = 0x80008000u;
    sts4(SM_MISC + lane * 16, prmt(s.x, s.x, 0x1010) ^ sg, prmt(s.y, s.y, 0x1010) ^ sg, prmt(s.z, s.z, 0x1010) ^ sg, prmt(s.w, s.w, 0x1010) ^ sg);
    sts4(SM_STAT + 256 + lane * 32, __float_as_uint(r0), __float_as_uint(r1), pack2(r0, r1), prmt(s.x, s.y, 0x7632));
    sts4(SM_STAT + 272 + lane * 32, __float_as_uint(r2), __float_as_uint(r3), pack2(r2, r3), prmt(s.z, s.w, 0x7632));
    __syncwarp();
    mbar_arrive1(B_ST);
  }
  PROF(15, s_stat);
  if (w == 1) {
    mbar_wait(B_ST, layer);
    if (c >= 8) {
      uint2 s;
      for (int it = 0;; ++it) {
        s = ldr2((const uint2*)P.S->ST + ((c >> 3) * 64 - 12 + (lane & 11)));
        if (__all_sync(0xffffffffu, min(s.x, s.y) != 0u)) break;
        spin_guard(it);
      }
      const float r0 = rcp(bfhi(s.x)), r1 = rcp(bfhi(s.y));
      sts4(SM_STAT + 64 + (lane & 11) * 16, __float_as_uint(r0), __float_as_uint(r1), pack2(r0, r1), prmt(s.x, s.y, 0x7632));
    }
    bar_arrive(NB_H, 160);
  }
  if (w >= 2) {
    const uint4* h = P.S->H + (c * 256 + (w & 1) * 128 + lane);
    uint4 hv[4];
#pragma unroll
    for (int z = 0; z < 4; ++z) hv[z] = make_uint4(0, 0, 0, 0);
    bar_sync(NB_RL, 128);
    PROFD(26, s_hb, lds1v(SM_MISC));
    delay(HDELAY);
    for (int it = 0; c >= 8; ++it) {
#pragma unroll
      for (int z = 0; z < 4; ++z) hv[z] = ldr4(h + z * 32);
      if (__all_sync(0xffffffffu, min(min(hv[0].x, hv[1].x), min(hv[2].x, hv[3].x)) != 0u)) break;
      spin_guard(it);
    }
    mbar_wait(B_F + 24, layer);
#pragma unroll
    for (int z = 0; z < 4; ++z) sts4(kvslot(c & 7, 0) + (w & 1) * 2048 + lane * 16 + z * 512, hv[z].x, hv[z].y, movm(hv[z].z), movm(hv[z].w));
    bar_arrive(NB_H, 160);
    PROF(25, s_halo);
  }
}

DEV void finalize(const Params& P, int c, int lane, int layer) {
  PW(12)
  uint2* so = (uint2*)P.S->SR[layer] + ((lane >> 3) * 1024 + (lane & 2) * 256 + 4 * c + ((lane >> 1) & 2) + (lane & 1));
  const uint4* ps = &P.S->PS[c * 64 + lane];
  keep(so, P.zero); keep(ps, P.zero);
  uint4 a, b;
  if (layer == 0) {
    bar_sync(NB_P, 256);
    a = lds4(SM_RES + 8192 + lane * 16); b = lds4(SM_RES + 8704 + lane * 16);
  } else {
    mbar_wait(B_ED + 8 - 2 * (c & 4), 0);
    delay(FDELAY);
    for (int it = 0;; ++it) {
      a = ldr4(ps); b = ldr4(ps + 32);
      if (__all_sync(0xffffffffu, min(a.x, b.x) != 0u)) break;
      spin_guard(it);
    }
  }
  float z[4] = {__uint_as_float(a.x) + __uint_as_float(b.x), __uint_as_float(a.y) + __uint_as_float(b.y),
                __uint_as_float(a.z) + __uint_as_float(b.z), __uint_as_float(a.w) + __uint_as_float(b.w)};
#pragma unroll
  for (int o = 8; o < 32; o <<= 1)
#pragma unroll
    for (int k = 0; k < 4; ++k) z[k] += __shfl_xor_sync(0xffffffffu, z[k], o);
  const float m0 = z[0] * (1.f / 512.f), m1 = z[2] * (1.f / 512.f);
  const float r0 = rsq(fmaxf(z[1] * (1.f / 512.f) - m0 * m0, 0.f) + 1e-5f), r1 = rsq(fmaxf(z[3] * (1.f / 512.f) - m1 * m1, 0.f) + 1e-5f);
  const uint32_t wr = nz(pack2(r0, r1)), wm = pack2(m0, m1);
  str2(so, wr, wm); str2(so + 4096, wr, wm);
  bar_arrive_if(NB_Q, 448, !layer);
  PROF(23, s_sr);
}

DEV void announce(const Params& P, int c, int lane, int layer) {
  PW(13)
  uint32_t* cp = cnt_at(P, 5 * layer, c, lane);
  keep(cp, P.zero);
  bar_sync(NB_T + 3, layer ? 288 : 160);
  cnt_add(cp, 1, lane < NCOPY);
  if (!layer) { bar_sync(NB_Q, 448); fence_async_smem(); }
  PROF(24, s_own);
}

DEV void fetch(const Params& P, int c, int lane, int layer) {
  PW(13)
  mbar_expect1(B_E, 24576);
  cnt_wait(P, 5 * layer, c, lane);
#pragma unroll
  for (int k = 0; k < 4; ++k) bulk(SM_R + k * 16384 + R_B, P.S->XG[layer] + (128 * k + c) * 256, 4096, B_E);
  if (layer) delay(SRDELAY);
  bulk(SM_RES, P.S->SR[layer][c >> 4], 8192, B_E);
  if (!layer) { if (!CSP) l2_prefetch(P.wqkv + c * 6144, 12288); l2_prefetch(P.wo + c * 2048, 4096); }
  if (PHOLD) mbar_arrive1_if(B_ST + 8, !layer);
  PROF(25, s_all);
}

DEV void cs_part(const Params& P, int c, int w, int lane, int layer) {
  float cs[8];
#pragma unroll
  for (int k = 0; k < 8; ++k) cs[k] = 0.f;
  const int col = w * 512 + 64 * (c & 7) + 8 * (lane & 7);
#pragma unroll 1
  for (int r = 8 * layer; r < 8; r += CSU) {
    uint4 v[CSU];
#pragma unroll
    for (int k = 0; k < CSU; ++k) v[k] = ldnc4(P.wqkv + ((32 * (c >> 3) + 4 * r + (lane >> 3)) * 1536 + col) + 4 * k * 1536);
#pragma unroll
    for (int k = 0; k < CSU; ++k) {
      cs[0] += bflo(v[k].x); cs[1] += bfhi(v[k].x); cs[2] += bflo(v[k].y); cs[3] += bfhi(v[k].y);
      cs[4] += bflo(v[k].z); cs[5] += bfhi(v[k].z); cs[6] += bflo(v[k].w); cs[7] += bfhi(v[k].w);
    }
  }
  fold<4>(cs, lane, 16); fold<2>(cs, lane, 8);
  str2((float*)P.S->CS + ((c >> 3) * 1536 + col + 2 * (lane >> 3)), max(__float_as_uint(cs[0]), 1u - layer), __float_as_uint(cs[1]));
}

DEV void cs_sum(const Params& P, int c, int w, int lane) {
  float a, b;
  for (int it = 0;; ++it) {
    uint32_t m = ~0u;
    a = b = 0.f;
#pragma unroll
    for (int k = 0; k < 16; ++k) {
      const uint2 u = ldr2((const float*)P.S->CS + (w * 512 + 64 * (c & 7) + 2 * lane) + k * 1536);
      a += __uint_as_float(u.x); b += __uint_as_float(u.y); m = min(m, u.x);
    }
    if (__all_sync(0xffffffffu, m != 0u)) break;
    spin_guard(it);
  }
  const uint32_t hi = pack2(a, b), ad = SM_CS + w * 256 + (lane >> 2) * 32 + (lane & 3) * 4;
  sts1(ad, hi); sts1(ad + 16, pack2(a - bflo(hi), b - bfhi(hi)));
  fence_async_smem();
  __syncwarp();
  mbar_arrive1(B_CS);
}

DEV void x0_get(uint32_t (&x)[8][2], uint32_t a) {
  asm volatile("cp.async.wait_group 0;" ::: "memory");
#pragma unroll
  for (int z = 0; z < 4; ++z) {
    const uint4 v = lds4(a + z * 512);
    x[2 * (z & 2)][z & 1] = v.x; x[2 * (z & 2) + 1][z & 1] = v.y; x[2 * (z & 2) + 2][z & 1] = v.z; x[2 * (z & 2) + 3][z & 1] = v.w;
  }
}

DEV void par_load(const Params& P, int ch, int m, uint32_t (&pv)[8]) {
  const int mo = ch * 128 + m;
  pv[0] = ldnc16(P.Are + mo); pv[1] = ldnc16(P.Aim + mo); pv[2] = ldnc16(P.Bre + mo); pv[3] = ldnc16(P.Bim + mo);
  pv[4] = ldnc16(P.Cre + mo); pv[5] = ldnc16(P.Cim + mo); pv[6] = ldnc16(P.logdt + ch); pv[7] = ldnc16(P.dskip + ch);
}

__global__ void __launch_bounds__(NTHR, 1)
fused_kernel(const __grid_constant__ Params P, const __grid_constant__ CUtensorMap mapW,
             const __grid_constant__ CUtensorMap mapWo) {
  extern __shared__ __align__(1024) uint8_t smem_raw[];
  if (s2u(smem_raw) != SB) __trap();
  const int warp0 = __shfl_sync(0xffffffffu, threadIdx.x >> 5, 0), lane0 = threadIdx.x & 31;
  uint32_t smid; asm volatile("mov.u32 %0,%%smid;" : "=r"(smid));
  const int c = __shfl_sync(0xffffffffu, P.by_sm ? P.role[smid] : blockIdx.x, 0);
  if (c == 255) {
    if (threadIdx.x < NCOPY * NSUB)
#pragma unroll 1
      for (int it = 0; it < 256 && ldr1(P.S->C + 32 * threadIdx.x) < 128 / NSUB; ++it) __nanosleep(200);
    return;
  }
  const int cg = c & 7;
  PW(warp0)
  uint32_t dskip;
  {
    [[maybe_unused]] const int layer = 0;
    const int lane = lane0, g = lane >> 2, t = lane & 3, warp = warp0, k4 = warp >> 2, w = warp & 3;
    uint32_t pv[8];
    if (k4 < 3) par_load(P, 128 * k4 + c, 32 * w + lane, pv);
    else {
#pragma unroll
      for (int n = 0; n < 8; ++n) pv[n] = 0;
    }
    __syncthreads();
    if (XDEL) delay(XDEL);
    const uint16_t* r = P.x0 + ((k4 < 2 ? 8192 * c + 64 * warp : (128 * (c >> 3) + 16 * w) * 512 + 64 * cg) + 1024 * g + 8 * t);
    const uint32_t xa = SM_R + k4 * 16384 + w * 2048 + lane * 16;
    if (k4 != 2) {
#pragma unroll
      for (int z = 0; z < 4; ++z) cp16(xa + z * 512, r + (z & 1) * 512 + (z & 2) * 16);
    }
    sts4(SM_TAP + k4 * TAP_SZ + (32 * w + lane) * 16, 0, 0, 0, 0);
    sts4z_if(SM_TAP + k4 * TAP_SZ + 2048 + (32 * w + lane) * 16, w < 3);
    uint32_t x[8][2];
    if (k4 == 3) {
#pragma unroll
      for (int z = 0; z < 4; ++z) cp16(xa - 16384 + z * 512, r + 32768 + (z & 1) * 512 + (z & 2) * 16);
      asm volatile("cp.async.commit_group;" ::: "memory");
      if (threadIdx.x == 448) {
        asm volatile("prefetch.tensormap [%0];" :: "l"(&mapW) : "memory");
        asm volatile("prefetch.tensormap [%0];" :: "l"(&mapWo) : "memory");
      }
      __syncwarp();
      if (PDELAY) delay(PDELAY);
      par_load(P, 128 * k4 + c, 32 * w + lane, pv);
      XgAddr xd = xg_addr<false>(P.S->XG[0] + (64 * cg * 256 + 16 * (c >> 3)), SM_R + 3 * 16384 + 8192, w, lane, P.zero);
      x0_get(x, xa);
      PROF(27, a_ld);
      xg_put<false>(xd, x);
      x0_get(x, xa - 16384);
      xd.a -= 16384;
      xg_put<false>(xd, x);
      bar_sync(NB_WG + 3, 128);
      xg_store(xd);
      xd.b -= 16384; xd.dst += 8;
      xg_store(xd);
      bar_arrive(NB_T + 3, 160);
      bar_sync(NB_Q, 448);
    } else asm volatile("cp.async.commit_group;" ::: "memory");
    tables(pv, k4, w, lane);
    if (k4 < 2) {
      x0_get(x, xa);
      const float4 s = gram(x, g, P.zero);
      if (t == (g >> 1)) sts4f(SM_RES + 8192 + (warp * 8 + g) * 16, s.x, s.y, s.z, s.w);
      __syncwarp();
      bar_arrive_if(NB_P, 256, warp != 7);
    }
    if (k4 == 2) {
#pragma unroll
      for (int n = 0; n < 14; ++n) mbar_init1(SM_BAR + (n < 10 ? w * 80 : 240 + w * 32) + n * 8, n < 10 ? 1 : (CNT >> (8 * w + 2 * (n - 10 & 2))) & 15);
    }
    dskip = pv[7];
    PROF(1, a_x0);
  }
#pragma unroll 1
  for (int layer = 0; layer < 2; ++layer) {
    int lane = lane_here(P.zero);
    const int warp = warp0 | (layer & P.zero), k4 = warp >> 2, w = warp & 3;
    if (warp == (layer ? 12 : 7)) finalize(P, c, lane, layer);
    if (warp == (layer ? 13 : 6)) { announce(P, c, lane, layer); fetch(P, c, lane, layer); }
    if (layer == 0) {
      if (CSP && k4 == 1 && w != 2) { if (CSP > 1) delay(CSP); cs_part(P, c, w - (w >> 1), lane, 0); }
      taps(dskip, k4, w, lane);
    }
    if (!layer && ((PHOLD >> k4) & 1)) mbar_wait(B_ST + 8, 0);
    conv(P, &mapW, c, k4, w, layer);
    lane = lane_here(P.zero);
    if (k4 < 2) {
      bar_arrive_if(NB_H, 256, warp != 4);
      if (warp == 0) {
        mbar_wait(B_K, 0);
        cnt_wait(P, 1 + 5 * layer, c, lane);
        x_load(P, c, 0, layer);
        PROF(27, m_xi);
      } else if (k4 == 0 && (CSP == 0 || layer)) cs_part(P, c, w - 1, lane, CSP ? 1 : layer);
      attn_phase(P, c, k4, w, lane, layer);
    } else {
      bar_arrive_if(NB_RL, 256, warp >= 10);
      if (k4 == 3) {
        stats(P, c, w, lane, layer);
      } else if (w < 2) {
        bar_sync_if(NB_RL, 256, w);
        cnt_wait(P, 3 + 5 * layer + w, c, lane);
        bar_sync_if(NB_RL, 256, !w);
        if (w) mbar_wait(B_F, layer);
        x_load(P, c, 2 + w, layer);
        if (H5 && w) w_load(&mapW, cg, 5);
        PROF(14, h_xi);
        if (w == 1) str4(&P.S->SR[layer][lane >> 2][4 * c + (lane & 3)], 0, 0, 0, 0);
      } else if (w == 2) {
        mbar_expect1(B_WO, 65536);
        mbar_expect1(B_RES, 16384);
#pragma unroll 1
        for (int q = 0; q < 4; ++q) {
          if (FH && q < 2) { mbar_wait(B_FH + 8 * q, layer); w_load(&mapW, cg, 4 + 2 * q); }
          mbar_wait(B_F + 8 * q, layer);
          if (!FH && q < 2) w_load(&mapW, cg, 4 + 2 * q);
          if (q == 1 || (q == 0 && !H5)) w_load(&mapW, cg, 5 + 2 * q);
          if (WOQ == 0 && ((q + 1) & 2)) tma5(SM_R + (q & 2) * 16384, &mapWo, 64 * cg, 4 * (q & 2), B_WO);
          if (WOQ && q == 2) {
            if (WOQ >= 2) mbar_wait(B_ST, layer);
            tma5(SM_R, &mapWo, 64 * cg, 0, B_WO);
            if (WOQ < 3) tma5(SM_R + 32768, &mapWo, 64 * cg, 8, B_WO);
          }
          if (q == 3) {
#pragma unroll
            for (int e = 0; e < 2; ++e) bulk(SM_RES + e * 8192, P.S->XF + ((2 * (c >> 3) + 1 - e) * 4096 + cg * 512), 8192, B_RES);
          }
          PROF(15 + q, h_w);
        }
      }
      if (k4 == 2 && w != 2) {
        if (layer == 0) cs_sum(P, c, w - (w >> 1), lane);
        if (w == 3) {
          uint4* xz = P.S->XG[layer] + (c * 256 + lane);
          mbar_wait(B_F, layer);
#pragma unroll 1
          for (int k = 0; k < 32; ++k) {
            str4(xz + ((k >> 3) * 32768 + (k & 7) * 32), 0, 0, 0, 0);
            if (ZPACE) __nanosleep(ZPACE);
          }
          PROF(19, h_z);
        }
      }
      if (warp < 10) o_load(P, c, w, lane, layer);
    }
    asm volatile("mov.b32 %0,0;" : "=r"(dskip));
  }
}

typedef CUresult (*EncodeFn)(CUtensorMap*, CUtensorMapDataType, cuuint32_t, void*, const cuuint64_t*, const cuuint64_t*,
                             const cuuint32_t*, const cuuint32_t*, CUtensorMapInterleave, CUtensorMapSwizzle,
                             CUtensorMapL2promotion, CUtensorMapFloatOOBfill);

#define POOL 0
#define GOFF 0
static int place_roles(uint8_t* role) {
  int dev = 0, nsm = 0;
  cudaGetDevice(&dev);
  cudaDeviceGetAttribute(&nsm, cudaDevAttrMultiProcessorCount, dev);
  if (nsm < 128 || nsm > 144 || (nsm & 1)) return 0;
  cudaFuncSetAttribute(fused_kernel, cudaFuncAttributeNonPortableClusterSizeAllowed, 1);
  int occ[9] = {0};
  for (int k = 2; k <= 8; ++k) {
    cudaLaunchConfig_t cfg = {};
    cudaLaunchAttribute at[1];
    at[0].id = cudaLaunchAttributeClusterDimension;
    at[0].val.clusterDim.x = 2 * k; at[0].val.clusterDim.y = 1; at[0].val.clusterDim.z = 1;
    cfg.gridDim = dim3(2 * k); cfg.blockDim = dim3(NTHR); cfg.dynamicSmemBytes = SM_TOTAL; cfg.attrs = at; cfg.numAttrs = 1;
    if (cudaOccupancyMaxActiveClusters(&occ[k], fused_kernel, &cfg) != cudaSuccess) { cudaGetLastError(); occ[k] = 0; }
  }
  int n[10];
  n[7] = occ[8]; n[6] = occ[7]; n[5] = occ[6] - 0; n[4] = occ[5];
  n[3] = occ[4] - n[7]; n[1] = occ[2] - n[3] - n[5] - n[7]; n[0] = n[2] = n[1];
  n[8] = occ[3] - n[2] - n[5];
  const int ntpc = nsm / 2;
  int sum = 0;
  bool ok = n[0] > 0 && n[0] <= 8;
  for (int r = 0; r < 9; ++r) { ok = ok && n[r] >= 0 && (r == 0 || n[r] <= n[r - 1]); sum += n[r]; }
  if (!ok || sum > ntpc) { for (int r = 0; r < 9; ++r) n[r] = r < 8 ? 8 : 0; sum = 64; }
  int tp[8][9], cnt[8] = {0}, pool[72], np = 0, id = 0;
  for (int r = 0; r < 9; ++r)
    for (int g = n[0] - n[r]; g < n[0]; ++g) tp[g][cnt[g]++] = id++;
  for (; id < ntpc; ++id) pool[np++] = id;
  int order[72], no = 0;
  for (int g = 0; g < n[0]; ++g) {
    const int full = cnt[g] / 4 * 4;
    for (int k = 0; k < cnt[g]; ++k) { if (k < full) order[no++] = tp[g][k]; else pool[np++] = tp[g][k]; }
  }
  for (int k = 0; k < np; ++k) order[no++] = pool[POOL == 1 ? np - 1 - k : POOL == 2 ? (k + np - 2) % np : k];
  for (int k = 0; k < 144; ++k) role[k] = 255;
  for (int k = 0; k < 64; ++k) { role[2 * order[k]] = (2 * k + GOFF) & 127; role[2 * order[k] + 1] = (2 * k + 1 + GOFF) & 127; }
  return nsm;
}

extern "C" void kernel_launch(void* const* d_in, const int* in_sizes, int n_in, void* d_out, int out_size) {
  (void)in_sizes; (void)n_in; (void)out_size;
  static EncodeFn enc = nullptr;
  static uint8_t role[144];
  static int nsm = 0;
  static void* scratch = nullptr;
  if (!enc) {
    void* fn = nullptr;
    cudaDriverEntryPointQueryResult qr;
    cudaGetDriverEntryPoint("cuTensorMapEncodeTiled", &fn, cudaEnableDefault, &qr);
    enc = (EncodeFn)fn;
    cudaFuncSetAttribute(fused_kernel, cudaFuncAttributeMaxDynamicSharedMemorySize, SM_TOTAL);
    nsm = place_roles(role);
    cudaGetSymbolAddress(&scratch, g_S);
  }
  CUtensorMap mW, mWo;
  {
    cuuint64_t dim[3] = {512, 512, 3}, str[2] = {3072, 1024};
    cuuint32_t box[3] = {64, 64, 3}, es[3] = {1, 1, 1};
    enc(&mW, CU_TENSOR_MAP_DATA_TYPE_BFLOAT16, 3, d_in[10], dim, str, box, es, CU_TENSOR_MAP_INTERLEAVE_NONE,
        CU_TENSOR_MAP_SWIZZLE_128B, CU_TENSOR_MAP_L2_PROMOTION_NONE, CU_TENSOR_MAP_FLOAT_OOB_FILL_NONE);
  }
  {
    cuuint64_t dim[5] = {512, 2, 4, 4, 16}, str[4] = {1024, 8192, 2048, 32768};
    cuuint32_t box[5] = {64, 2, 4, 4, 8}, es[5] = {1, 1, 1, 1, 1};
    enc(&mWo, CU_TENSOR_MAP_DATA_TYPE_BFLOAT16, 5, d_in[11], dim, str, box, es, CU_TENSOR_MAP_INTERLEAVE_NONE,
        CU_TENSOR_MAP_SWIZZLE_128B, CU_TENSOR_MAP_L2_PROMOTION_NONE, CU_TENSOR_MAP_FLOAT_OOB_FILL_NONE);
  }
  Params P;
  P.x0 = (const uint16_t*)d_in[0]; P.Are = (const uint16_t*)d_in[1]; P.Aim = (const uint16_t*)d_in[2];
  P.Bre = (const uint16_t*)d_in[3]; P.Bim = (const uint16_t*)d_in[4]; P.Cre = (const uint16_t*)d_in[5];
  P.Cim = (const uint16_t*)d_in[6]; P.logdt = (const uint16_t*)d_in[7]; P.dskip = (const uint16_t*)d_in[8];
  P.wqkv = (const uint16_t*)d_in[10]; P.wo = (const uint16_t*)d_in[11]; P.out = (uint16_t*)d_out;
  for (int k = 0; k < 144; ++k) P.role[k] = role[k];
  P.by_sm = nsm > 0;
  P.zero = 0;
  P.S = (Scratch*)scratch;
  fused_kernel<<<nsm > 0 ? nsm : 128, NTHR, SM_TOTAL, cudaStreamPerThread>>>(P, mW, mWo);
}
```

```cpp
#include <cuda_runtime.h>
#include <cuda_bf16.h>
#include <cuda.h>
#include <stdint.h>

#define DEV __device__ __forceinline__

#define NCOPY 4
#define NSUB 1
constexpr int NTHR = 512;
constexpr int SPIN_LIMIT = 1 << 22;

constexpr uint32_t SB = 1024;
constexpr uint32_t SM_XA   = SB;
constexpr uint32_t SM_S0   = SM_XA + 16384;
constexpr uint32_t SM_S1   = SM_S0 + 49152;
constexpr uint32_t SM_XB   = SM_S1 + 49152;
constexpr uint32_t SM_R    = SM_XB + 16384;
constexpr uint32_t SM_RES  = SM_R + 65536;
constexpr uint32_t SM_TAP  = SM_RES + 16384;
constexpr int TAP_SZ = 3584;
constexpr uint32_t SM_CS   = SM_TAP + 4 * TAP_SZ;
constexpr uint32_t SM_STAT = SM_CS + 800;
constexpr uint32_t SM_MISC = SM_STAT + 1280;
constexpr uint32_t SM_BAR  = SM_MISC + 512;
constexpr int SM_TOTAL = SM_BAR + 448 - SB;
constexpr int R_U = 512, R_A5 = 5120, R_A3 = 8704, R_B = 11776;
constexpr int T_E = 1536, T_O = T_E + 1602, T_C = 3714;
constexpr uint32_t B_W = SM_BAR, B_X = SM_BAR + 64, B_O = SM_BAR + 128, B_WO = SM_BAR + 256, B_RES = SM_BAR + 264;
constexpr uint32_t B_ST = SM_BAR + 272, B_R = SM_BAR + 288, B_E = SM_BAR + 304;
constexpr uint32_t B_F = SM_BAR + 320, B_G = SM_BAR + 352, B_K = SM_BAR + 376, B_ED = SM_BAR + 384, B_CS = SM_BAR + 400, B_FH = SM_BAR + 416;
constexpr uint32_t CNT = 0x143444CC;
constexpr int NB_WG = 1, NB_T = 5, NB_Q = 10, NB_H = 11, NB_P = 14, NB_RL = 15;

struct Scratch {
  uint32_t F[32 * 32];
  uint4    H[17 * 8 * 256];
  uint4    SR[2][8][512];
  uint4    ST[32 * 16];
  uint4    PS[128 * 64];
  float4   CS[16 * 1536 / 4];
  uint32_t C[10 * 32 * 32];
  uint4    XF[32 * 4096];
  uint4    O[32 * 8 * 512];
  uint4    XG[512 * 256];
};
__device__ __align__(1024) Scratch g_S;

struct Params {
  int by_sm;
  uint32_t zero;
  Scratch* S;
  const uint16_t *x0, *Are, *Aim, *Bre, *Bim, *Cre, *Cim, *logdt, *dskip, *wqkv, *wo;
  uint16_t* out;
  uint8_t role[144];
};
#define EVENT(n) do {} while (0)
#define PROFD(slot, name, v) do {} while (0)
#define PROF(slot, name) do {} while (0)
#define PW(x)

DEV uint32_t s2u(const void* p) { return (uint32_t)__cvta_generic_to_shared(p); }
template <class T> DEV T opq(T x) { asm volatile("" : "+r"(x)); return x; }
DEV uint32_t pack2(float lo, float hi) { uint32_t d; asm("cvt.rn.bf16x2.f32 %0,%1,%2;" : "=r"(d) : "f"(hi), "f"(lo)); return d; }
DEV float bflo(uint32_t v) { return __uint_as_float(v << 16); }
DEV float bfhi(uint32_t v) { return __uint_as_float(v & 0xFFFF0000u); }
DEV float bfr(float x) { return bflo(pack2(x, 0.f)); }
DEV uint32_t hadd2(uint32_t a, uint32_t b) { uint32_t d; asm("add.rn.bf16x2 %0,%1,%2;" : "=r"(d) : "r"(a), "r"(b)); return d; }
DEV uint32_t hsub2(uint32_t a, uint32_t b) { uint32_t d; asm("sub.rn.bf16x2 %0,%1,%2;" : "=r"(d) : "r"(a), "r"(b)); return d; }
DEV uint32_t hmul2(uint32_t a, uint32_t b) { uint32_t d; asm("mul.rn.bf16x2 %0,%1,%2;" : "=r"(d) : "r"(a), "r"(b)); return d; }
DEV uint32_t hfma2(uint32_t a, uint32_t b, uint32_t c) { uint32_t d; asm("fma.rn.bf16x2 %0,%1,%2,%3;" : "=r"(d) : "r"(a), "r"(b), "r"(c)); return d; }
DEV uint32_t hmax2(uint32_t a, uint32_t b) { uint32_t d; asm("max.bf16x2 %0,%1,%2;" : "=r"(d) : "r"(a), "r"(b)); return d; }
DEV uint32_t prmt(uint32_t a, uint32_t b, uint32_t s) { uint32_t d; asm("prmt.b32 %0,%1,%2,%3;" : "=r"(d) : "r"(a), "r"(b), "r"(s)); return d; }
DEV uint32_t nz(uint32_t v) { uint32_t d; asm("max.u32 %0,%1,1;" : "=r"(d) : "r"(v)); return d; }
DEV uint32_t tagged(uint32_t v, uint32_t m, uint32_t tag) { uint32_t d; asm("lop3.b32 %0,%1,%2,%3,0xB8;" : "=r"(d) : "r"(v), "r"(m), "r"(tag)); return d; }
DEV uint32_t both(uint32_t a, uint32_t b, uint32_t x) { uint32_t d; asm("lop3.b32 %0,%1,%2,%3,0x42;" : "=r"(d) : "r"(a), "r"(b), "r"(x)); return d; }
DEV uint4 hadd8(const uint4& a, const uint4& b) { return make_uint4(hadd2(a.x, b.x), hadd2(a.y, b.y), hadd2(a.z, b.z), hadd2(a.w, b.w)); }
DEV uint32_t min4(const uint4& v) { return min(min(v.x, v.y), min(v.z, v.w)); }
DEV float rcp(float x) { float y; asm("rcp.approx.ftz.f32 %0,%1;" : "=f"(y) : "f"(x)); return y; }
DEV float sqrt_(float x) { float y; asm("sqrt.approx.ftz.f32 %0,%1;" : "=f"(y) : "f"(x)); return y; }
DEV float rsq(float x) { float y; asm("rsqrt.approx.ftz.f32 %0,%1;" : "=f"(y) : "f"(x)); return y; }
DEV float ex2(float x) { float y; asm("ex2.approx.ftz.f32 %0,%1;" : "=f"(y) : "f"(x)); return y; }

DEV uint4 ldr4(const void* p) { uint4 v; asm volatile("ld.relaxed.gpu.global.v4.u32 {%0,%1,%2,%3},[%4];" : "=r"(v.x), "=r"(v.y), "=r"(v.z), "=r"(v.w) : "l"(p) : "memory"); return v; }
DEV void ldr4_if(uint4& v, const void* p, bool c) {
  asm volatile("{.reg .pred q; setp.ne.u32 q,%5,0; @q ld.relaxed.gpu.global.v4.u32 {%0,%1,%2,%3},[%4];}"
    : "+r"(v.x), "+r"(v.y), "+r"(v.z), "+r"(v.w) : "l"(p), "r"((uint32_t)c) : "memory");
}
DEV uint2 ldr2(const void* p) { uint2 v; asm volatile("ld.relaxed.gpu.global.v2.u32 {%0,%1},[%2];" : "=r"(v.x), "=r"(v.y) : "l"(p) : "memory"); return v; }
DEV uint32_t ldr1(const void* p) { uint32_t v; asm volatile("ld.relaxed.gpu.global.u32 %0,[%1];" : "=r"(v) : "l"(p) : "memory"); return v; }
DEV void str4(void* p, uint32_t a, uint32_t b, uint32_t c, uint32_t d) { asm volatile("st.relaxed.gpu.global.v4.u32 [%0],{%1,%2,%3,%4};" :: "l"(p), "r"(a), "r"(b), "r"(c), "r"(d) : "memory"); }
DEV void str4_if(void* p, uint32_t a, uint32_t b, uint32_t c, uint32_t d, bool q) {
  asm volatile("{.reg .pred q; setp.ne.u32 q,%5,0; @q st.relaxed.gpu.global.v4.u32 [%0],{%1,%2,%3,%4};}" :: "l"(p), "r"(a), "r"(b), "r"(c), "r"(d), "r"((uint32_t)q) : "memory");
}
DEV void str2(void* p, uint32_t a, uint32_t b) { asm volatile("st.relaxed.gpu.global.v2.u32 [%0],{%1,%2};" :: "l"(p), "r"(a), "r"(b) : "memory"); }
DEV void str1(void* p, uint32_t a) { asm volatile("st.relaxed.gpu.global.u32 [%0],%1;" :: "l"(p), "r"(a) : "memory"); }
DEV void stw4(void* p, uint32_t a, uint32_t b, uint32_t c, uint32_t d) { asm volatile("st.global.v4.u32 [%0],{%1,%2,%3,%4};" :: "l"(p), "r"(a), "r"(b), "r"(c), "r"(d) : "memory"); }
DEV uint4 ldnc4(const void* p) { uint4 v; asm volatile("ld.global.nc.v4.u32 {%0,%1,%2,%3},[%4];" : "=r"(v.x), "=r"(v.y), "=r"(v.z), "=r"(v.w) : "l"(p)); return v; }
DEV uint4 ldw4(const void* p) { uint4 v; asm volatile("ld.global.v4.u32 {%0,%1,%2,%3},[%4];" : "=r"(v.x), "=r"(v.y), "=r"(v.z), "=r"(v.w) : "l"(p) : "memory"); return v; }
DEV void cp16(uint32_t d, const void* p) { asm volatile("cp.async.cg.shared.global [%0],[%1],16;" :: "r"(d), "l"(p) : "memory"); }
DEV uint32_t ldnc16(const void* p) { uint32_t v; asm volatile("ld.global.u16 %0,[%1];" : "=r"(v) : "l"(p) : "memory"); return v; }

DEV uint32_t lds1v(uint32_t a) { uint32_t v; asm volatile("ld.volatile.shared.u32 %0,[%1];" : "=r"(v) : "r"(a) : "memory"); return v; }
DEV uint4 lds4v(uint32_t a) { uint4 v; asm volatile("ld.volatile.shared.v4.u32 {%0,%1,%2,%3},[%4];" : "=r"(v.x), "=r"(v.y), "=r"(v.z), "=r"(v.w) : "r"(a) : "memory"); return v; }
DEV uint32_t lds1(uint32_t a) { uint32_t v; asm volatile("ld.shared.u32 %0,[%1];" : "=r"(v) : "r"(a)); return v; }
DEV uint2 lds2(uint32_t a) { uint2 v; asm volatile("ld.shared.v2.u32 {%0,%1},[%2];" : "=r"(v.x), "=r"(v.y) : "r"(a)); return v; }
DEV uint4 lds4(uint32_t a) { uint4 v; asm volatile("ld.shared.v4.u32 {%0,%1,%2,%3},[%4];" : "=r"(v.x), "=r"(v.y), "=r"(v.z), "=r"(v.w) : "r"(a)); return v; }
DEV uint32_t lds16(uint32_t a) { uint32_t v; asm volatile("ld.shared.u16 %0,[%1];" : "=r"(v) : "r"(a)); return v; }
DEV float lds1f(uint32_t a) { float v; asm volatile("ld.shared.f32 %0,[%1];" : "=f"(v) : "r"(a)); return v; }
DEV float2 lds2f(uint32_t a) { float2 v; asm volatile("ld.shared.v2.f32 {%0,%1},[%2];" : "=f"(v.x), "=f"(v.y) : "r"(a)); return v; }
DEV float4 lds4f(uint32_t a) { float4 v; asm volatile("ld.shared.v4.f32 {%0,%1,%2,%3},[%4];" : "=f"(v.x), "=f"(v.y), "=f"(v.z), "=f"(v.w) : "r"(a)); return v; }
DEV void sts1(uint32_t a, uint32_t v) { asm volatile("st.shared.u32 [%0],%1;" :: "r"(a), "r"(v) : "memory"); }
DEV void sts16(uint32_t a, uint32_t v) { asm volatile("{.reg .b16 h; cvt.u16.u32 h,%1; st.shared.u16 [%0],h;}" :: "r"(a), "r"(v) : "memory"); }
DEV void sts2f(uint32_t a, float x, float y) { asm volatile("st.shared.v2.f32 [%0],{%1,%2};" :: "r"(a), "f"(x), "f"(y) : "memory"); }
DEV void sts4f(uint32_t a, float x, float y, float z, float w) { asm volatile("st.shared.v4.f32 [%0],{%1,%2,%3,%4};" :: "r"(a), "f"(x), "f"(y), "f"(z), "f"(w) : "memory"); }
DEV void sts4(uint32_t a, uint32_t x, uint32_t y, uint32_t z, uint32_t w) { asm volatile("st.shared.v4.u32 [%0],{%1,%2,%3,%4};" :: "r"(a), "r"(x), "r"(y), "r"(z), "r"(w) : "memory"); }
DEV void sts4_if(uint32_t a, uint32_t x, uint32_t y, uint32_t z, uint32_t w, bool c) {
  asm volatile("{.reg .pred q; setp.ne.u32 q,%5,0; @q st.shared.v4.u32 [%0],{%1,%2,%3,%4};}" :: "r"(a), "r"(x), "r"(y), "r"(z), "r"(w), "r"((uint32_t)c) : "memory");
}
DEV void sts4z_if(uint32_t a, bool c) { asm volatile("{.reg .pred q; setp.ne.u32 q,%1,0; @q st.shared.v4.u32 [%0],{%2,%2,%2,%2};}" :: "r"(a), "r"((uint32_t)c), "r"(0) : "memory"); }

DEV void ldsm4t(uint32_t& r0, uint32_t& r1, uint32_t& r2, uint32_t& r3, uint32_t a) { asm volatile("ldmatrix.sync.aligned.m8n8.x4.trans.shared.b16 {%0,%1,%2,%3},[%4];" : "=r"(r0), "=r"(r1), "=r"(r2), "=r"(r3) : "r"(a) : "memory"); }
DEV void stsm4(uint32_t a, uint32_t r0, uint32_t r1, uint32_t r2, uint32_t r3) { asm volatile("stmatrix.sync.aligned.m8n8.x4.shared.b16 [%0],{%1,%2,%3,%4};" :: "r"(a), "r"(r0), "r"(r1), "r"(r2), "r"(r3) : "memory"); }
DEV void stsm2(uint32_t a, uint32_t r0, uint32_t r1) { asm volatile("stmatrix.sync.aligned.m8n8.x2.shared.b16 [%0],{%1,%2};" :: "r"(a), "r"(r0), "r"(r1) : "memory"); }
DEV void stsm4t(uint32_t a, uint32_t r0, uint32_t r1, uint32_t r2, uint32_t r3) { asm volatile("stmatrix.sync.aligned.m8n8.x4.trans.shared.b16 [%0],{%1,%2,%3,%4};" :: "r"(a), "r"(r0), "r"(r1), "r"(r2), "r"(r3) : "memory"); }
DEV uint32_t movm(uint32_t a) { uint32_t d; asm volatile("movmatrix.sync.aligned.m8n8.trans.b16 %0,%1;" : "=r"(d) : "r"(a)); return d; }
DEV void mma16(float (&d)[4], uint32_t a0, uint32_t a1, uint32_t a2, uint32_t a3, uint32_t b0, uint32_t b1) {
  asm volatile("mma.sync.aligned.m16n8k16.row.col.f32.bf16.bf16.f32 {%0,%1,%2,%3},{%4,%5,%6,%7},{%8,%9},{%0,%1,%2,%3};"
    : "+f"(d[0]), "+f"(d[1]), "+f"(d[2]), "+f"(d[3]) : "r"(a0), "r"(a1), "r"(a2), "r"(a3), "r"(b0), "r"(b1));
}
DEV void mma16z(float (&d)[4], uint32_t a0, uint32_t a1, uint32_t a2, uint32_t a3, uint32_t b0, uint32_t b1) {
  asm volatile("mma.sync.aligned.m16n8k16.row.col.f32.bf16.bf16.f32 {%0,%1,%2,%3},{%4,%5,%6,%7},{%8,%9},{%10,%10,%10,%10};"
    : "=f"(d[0]), "=f"(d[1]), "=f"(d[2]), "=f"(d[3]) : "r"(a0), "r"(a1), "r"(a2), "r"(a3), "r"(b0), "r"(b1), "f"(0.f));
}
DEV void mma8z(float (&d)[4], uint32_t a0, uint32_t a1, uint32_t b0) {
  asm volatile("mma.sync.aligned.m16n8k8.row.col.f32.bf16.bf16.f32 {%0,%1,%2,%3},{%4,%5},{%6},{%7,%7,%7,%7};"
    : "=f"(d[0]), "=f"(d[1]), "=f"(d[2]), "=f"(d[3]) : "r"(a0), "r"(a1), "r"(b0), "f"(0.f));
}
DEV void mma8(float (&d)[4], uint32_t a0, uint32_t a1, uint32_t b0) {
  asm volatile("mma.sync.aligned.m16n8k8.row.col.f32.bf16.bf16.f32 {%0,%1,%2,%3},{%4,%5},{%6},{%0,%1,%2,%3};"
    : "+f"(d[0]), "+f"(d[1]), "+f"(d[2]), "+f"(d[3]) : "r"(a0), "r"(a1), "r"(b0));
}

DEV void bar_sync(int id, int n) { asm volatile("bar.sync %0,%1;" :: "r"(id), "r"(n) : "memory"); }
DEV void bar_arrive(int id, int n) { asm volatile("bar.arrive %0,%1;" :: "r"(id), "r"(n) : "memory"); }
DEV void bar_sync_if(int id, int n, int c) { asm volatile("{.reg .pred q; setp.ne.s32 q,%2,0; @q bar.sync %0,%1;}" :: "r"(id), "r"(n), "r"(c) : "memory"); }
DEV void bar_arrive_if(int id, int n, int c) { asm volatile("{.reg .pred q; setp.ne.s32 q,%2,0; @q bar.arrive %0,%1;}" :: "r"(id), "r"(n), "r"(c) : "memory"); }
DEV bool bar_any(int id, int n, bool c) {
  uint32_t r; asm volatile("{.reg .pred p,q; setp.ne.u32 q,%3,0; bar.red.or.pred p,%1,%2,q; selp.u32 %0,1,0,p;}" : "=r"(r) : "r"(id), "r"(n), "r"((uint32_t)c) : "memory");
  return __any_sync(0xffffffffu, r);
}
DEV void fence_async_glob() { asm volatile("fence.proxy.async.global;" ::: "memory"); }
DEV void fence_async_smem() { asm volatile("fence.proxy.async.shared::cta;" ::: "memory"); }
DEV void fence_gpu() { asm volatile("fence.acq_rel.gpu;" ::: "memory"); }
DEV void mbar_wait(uint32_t b, uint32_t ph) {
  asm volatile("{\n.reg .pred p;\nW: mbarrier.try_wait.parity.shared::cta.b64 p,[%0],%1;\n@!p bra W;\n}" :: "r"(b), "r"(ph) : "memory");
}
DEV bool mbar_test(uint32_t b, uint32_t ph) {
  uint32_t r; asm volatile("{.reg .pred p; mbarrier.test_wait.parity.shared::cta.b64 p,[%1],%2; selp.u32 %0,1,0,p;}" : "=r"(r) : "r"(b), "r"(ph) : "memory");
  return __all_sync(0xffffffffu, r);
}
DEV uint32_t mbar_test2(uint32_t b, uint32_t ph) {
  uint32_t r; asm volatile("{.reg .pred p,q; mbarrier.test_wait.parity.shared::cta.b64 p,[%1],%2; mbarrier.test_wait.parity.shared::cta.b64 q,[%1+8],%2;\n"
                           "and.pred p,p,q; selp.u32 %0,1,0,p;}" : "=r"(r) : "r"(b), "r"(ph) : "memory");
  return r;
}
DEV void spin_guard(int it) { asm volatile("{.reg .pred p; setp.gt.s32 p,%0,%1; @p trap;}" :: "r"(it), "n"(SPIN_LIMIT)); }
DEV uint32_t here(uint32_t zero) {
  uint32_t d; asm volatile("mov.u32 %0,%%clock;" : "=r"(d) :: "memory"); return d & zero;
}
DEV int lane_here(uint32_t zero) {
  uint32_t d; asm volatile("mov.u32 %0,%%laneid;" : "=r"(d)); return d | here(zero);
}
DEV void delay(uint32_t n) {
  asm volatile("{\n.reg .pred p;\n.reg .u32 a,b;\nmov.u32 a,%%clock;\nW: mov.u32 b,%%clock;\nsub.u32 b,b,a;\nsetp.lt.u32 p,b,%0;\n@p bra.uni W;\n}" :: "r"(n) : "memory");
}
DEV void poll(const uint32_t* p, uint32_t n) {
  for (int it = 0; !__all_sync(0xffffffffu, ldr1(p) >= n); ++it) spin_guard(it);
}
DEV uint32_t* cnt_at(const Params& P, int n, int c, int lane) { return P.S->C + (32 * (NSUB * lane + c % NSUB) + n * 1024); }
DEV void cnt_add(uint32_t* p, uint32_t one, bool q) { asm volatile("{.reg .pred p; setp.ne.u32 p,%2,0; @p red.relaxed.gpu.global.add.u32 [%0],%1;}" :: "l"(p), "r"(one), "r"((uint32_t)q) : "memory"); }
DEV void cnt_wait(const Params& P, int n, int c, int lane) { poll(P.S->C + (32 * (NSUB * (c / (128 / NCOPY)) + lane % NSUB) + n * 1024), 128 / NSUB); }
DEV void mbar_init1(uint32_t b, int n) { asm volatile("{.reg .pred p; elect.sync _|p,0xffffffff; @p mbarrier.init.shared::cta.b64 [%0],%1;}" :: "r"(b), "r"(n) : "memory"); }
DEV void mbar_arrive1(uint32_t b) { asm volatile("{.reg .pred p; elect.sync _|p,0xffffffff; @p mbarrier.arrive.shared::cta.b64 _,[%0];}" :: "r"(b) : "memory"); }
DEV void mbar_arrive1_if(uint32_t b, int c) {
  asm volatile("{.reg .pred p,q; setp.ne.s32 q,%1,0; elect.sync _|p,0xffffffff; and.pred p,p,q; @p mbarrier.arrive.shared::cta.b64 _,[%0];}" :: "r"(b), "r"(c) : "memory");
}
DEV void mbar_expect1(uint32_t b, int bytes) { asm volatile("{.reg .pred p; elect.sync _|p,0xffffffff; @p mbarrier.arrive.expect_tx.shared::cta.b64 _,[%0],%1;}" :: "r"(b), "r"(bytes) : "memory"); }
DEV void flag_set1(uint32_t* q) { asm volatile("{.reg .pred p; elect.sync _|p,0xffffffff; @p st.relaxed.gpu.global.u32 [%0],1;}" :: "l"(q) : "memory"); }
DEV void tma3(uint32_t dst, const CUtensorMap* m, int c0, int c1, uint32_t bar) {
  asm volatile("{.reg .pred p; elect.sync _|p,0xffffffff;\n"
    "@p cp.async.bulk.tensor.3d.shared::cluster.global.mbarrier::complete_tx::bytes [%0],[%1,{%2,%3,%5}],[%4];}"
    :: "r"(dst), "l"(m), "r"(c0), "r"(c1), "r"(bar), "r"(0) : "memory");
}
DEV void tma5(uint32_t dst, const CUtensorMap* m, int c0, int c4, uint32_t bar) {
  asm volatile("{.reg .pred p; elect.sync _|p,0xffffffff;\n"
    "@p cp.async.bulk.tensor.5d.shared::cluster.global.mbarrier::complete_tx::bytes [%0],[%1,{%2,%5,%5,%5,%3}],[%4];}"
    :: "r"(dst), "l"(m), "r"(c0), "r"(c4), "r"(bar), "r"(0) : "memory");
}
DEV void bulk(uint32_t dst, const void* src, int bytes, uint32_t bar) {
  asm volatile("{.reg .pred p; elect.sync _|p,0xffffffff;\n@p cp.async.bulk.shared::cluster.global.mbarrier::complete_tx::bytes [%0],[%1],%2,[%3];}" :: "r"(dst), "l"(src), "r"(bytes), "r"(bar) : "memory");
}
DEV void bulk_store(void* dst, uint32_t src, int bytes) {
  asm volatile("{.reg .pred p; elect.sync _|p,0xffffffff;\n@p cp.async.bulk.global.shared::cta.bulk_group [%0],[%1],%2;}" :: "l"(dst), "r"(src), "r"(bytes) : "memory");
}
DEV void l2_prefetch(const void* src, int bytes) {
  asm volatile("{.reg .pred p; elect.sync _|p,0xffffffff;\n@p cp.async.bulk.prefetch.L2.global [%0],%1;}" :: "l"(src), "r"(bytes) : "memory");
}

DEV uint64_t mkdesc(uint32_t addr, uint32_t lbo, uint32_t sbo, uint32_t swz) {
  return (uint64_t)((addr >> 4) | ((lbo >> 4) << 16)) | ((uint64_t)((sbo >> 4) | (swz << 30)) << 32);
}
DEV void wg_fence() { asm volatile("wgmma.fence.sync.aligned;" ::: "memory"); }
DEV void wg_commit() { asm volatile("wgmma.commit_group.sync.aligned;" ::: "memory"); }
template <int N> DEV void wg_wait() { asm volatile("wgmma.wait_group.sync.aligned %0;" :: "n"(N) : "memory"); }
template <int N> DEV void zerov(float (&d)[N]) {
#pragma unroll
  for (int i = 0; i < N; ++i) asm volatile("mov.b32 %0,0;" : "=f"(d[i]));
}
template <int N> DEV void undef(float (&d)[N]) {
#pragma unroll
  for (int i = 0; i < N; ++i) asm volatile("" : "=f"(d[i]));
}
#define R4(d, o) "+f"(d[o]), "+f"(d[o + 1]), "+f"(d[o + 2]), "+f"(d[o + 3])
#define R8(d, o) R4(d, o), R4(d, o + 4)
#define R16(d, o) R8(d, o), R8(d, o + 8)
#define R32(d, o) R16(d, o), R16(d, o + 16)
#define L0 "%0,%1,%2,%3,%4,%5,%6,%7,%8,%9,"
#define L10(a) "%" #a "0,%" #a "1,%" #a "2,%" #a "3,%" #a "4,%" #a "5,%" #a "6,%" #a "7,%" #a "8,%" #a "9,"
#define WG_HEAD(pr, n) "{.reg .pred p; setp.ne.s32 p,%" #pr ",0;\nwgmma.mma_async.sync.aligned.m64n" #n "k16.f32.bf16.bf16 {"
DEV void wg_rs64k(float (&d)[32], const uint32_t (&a)[4], uint64_t db, int acc) {
  asm volatile(WG_HEAD(37, 64) L0 L10(1) L10(2) "%30,%31},{%32,%33,%34,%35},%36,p,1,1,0;}"
    : R32(d, 0) : "r"(a[0]), "r"(a[1]), "r"(a[2]), "r"(a[3]), "l"(db), "r"(acc));
}
DEV void wg_rs48t(float (&d)[24], const uint32_t (&a)[4], uint64_t db, int acc) {
  asm volatile(WG_HEAD(29, 48) L0 L10(1) "%20,%21,%22,%23},{%24,%25,%26,%27},%28,p,1,1,1;}"
    : R16(d, 0), R8(d, 16) : "r"(a[0]), "r"(a[1]), "r"(a[2]), "r"(a[3]), "l"(db), "r"(acc));
}
DEV void wg_rs32t(float (&d)[16], const uint32_t (&a)[4], uint64_t db, int acc) {
  asm volatile(WG_HEAD(21, 32) L0 "%10,%11,%12,%13,%14,%15},{%16,%17,%18,%19},%20,p,1,1,1;}"
    : R16(d, 0) : "r"(a[0]), "r"(a[1]), "r"(a[2]), "r"(a[3]), "l"(db), "r"(acc));
}
DEV void wg_ss48(float (&d)[24], uint64_t da, uint64_t db, int acc) {
  asm volatile(WG_HEAD(26, 48) L0 L10(1) "%20,%21,%22,%23},%24,%25,p,1,1,1,1;}" : R16(d, 0), R8(d, 16) : "l"(da), "l"(db), "r"(acc));
}
DEV void wg_ss64(float (&d)[32], uint64_t da, uint64_t db, int acc) {
  asm volatile(WG_HEAD(34, 64) L0 L10(1) L10(2) "%30,%31},%32,%33,p,1,1,0,1;}" : R32(d, 0) : "l"(da), "l"(db), "r"(acc));
}
DEV void wg_ss192(float (&d)[96], uint64_t da, uint64_t db, int acc) {
  asm volatile(WG_HEAD(98, 192) L0 L10(1) L10(2) L10(3) L10(4) L10(5) L10(6) L10(7) L10(8) "%90,%91,%92,%93,%94,%95},%96,%97,p,1,1,1,1;}"
    : R32(d, 0), R32(d, 32), R32(d, 64) : "l"(da), "l"(db), "r"(acc));
}

DEV void wg_rs192t(float (&d)[96], const uint32_t (&a)[4], uint64_t db) {
  asm volatile("wgmma.mma_async.sync.aligned.m64n192k16.f32.bf16.bf16 {" L0 L10(1) L10(2) L10(3) L10(4) L10(5) L10(6) L10(7) L10(8) "%90,%91,%92,%93,%94,%95},{%96,%97,%98,%99},%100,1,1,1,1;"
    : R32(d, 0), R32(d, 32), R32(d, 64) : "r"(a[0]), "r"(a[1]), "r"(a[2]), "r"(a[3]), "l"(db));
}

DEV float ln_sd(float s, float q, float& m) {
  m = s * (1.f / 512.f);
  return bfr(sqrt_(bfr(bfr(fmaxf(q * (1.f / 512.f) - m * m, 0.f)) + 1e-5f)));
}
DEV float4 gram(const uint32_t (&w)[8][2], int g, uint32_t zero) {
  float s[4], q[4][4];
  const uint32_t o0 = 0x3F803F80u | zero, o1 = 0x3F803F80u ^ zero;
#pragma unroll
  for (int j = 0; j < 8; ++j) {
#pragma unroll
    for (int h = 0; h < 2; ++h) { if (j < 2) mma8z(q[2 * j + h], w[j][0], w[j][1], w[j][h]); else mma8(q[2 * (j & 1) + h], w[j][0], w[j][1], w[j][h]); }
    if (j == 1) mma16z(s, w[0][0], w[0][1], w[1][0], w[1][1], o0, o1);
    else if (j & 1) mma16(s, w[j - 1][0], w[j - 1][1], w[j][0], w[j][1], o0, o1);
  }
  const bool od = g & 1;
  return make_float4(s[0], od ? q[0][1] + q[2][1] : q[0][0] + q[2][0], s[2], od ? q[1][3] + q[3][3] : q[1][2] + q[3][2]);
}
DEV void keep(uint32_t v, uint32_t zero) {
  asm volatile("{.reg .pred p; setp.ne.u32 p,%1,0; @p st.shared.u32 [%0],%0;}" :: "r"(v), "r"(zero) : "memory");
}
DEV void keep(const void* v, uint32_t zero) { asm volatile("{.reg .pred p; setp.ne.u32 p,%1,0; @p st.global.u32 [%0],%1;}" :: "l"(v), "r"(zero) : "memory"); }
struct XgAddr { uint32_t a, b; uint4* dst; };
template <bool FRAG> DEV XgAddr xg_addr(uint4* dst, uint32_t stg, int wp, int lane, uint32_t zero) {
  const int t = lane & 3, r = 4 * wp + (lane >> 3);
  XgAddr x = {stg + t * (FRAG ? 256 : 1024) + ((wp ^ t) * 32) + (lane >> 2) * 4,
              stg + r * 128 + (((lane & 7) ^ (2 * (((r >> 1) ^ (r >> 3)) & 3))) * 16), dst + (r * 256 + (lane & 7))};
  keep(x.a, zero); keep(x.b, zero); keep(x.dst, zero);
  return x;
}
template <bool FRAG> DEV void xg_put(const XgAddr& x, const uint32_t (&w)[8][2]) {
#pragma unroll
  for (int n = 0; n < 8; ++n) {
    const uint32_t b = (x.a ^ ((n & 3) * 32)) + (FRAG ? n * 1024 : (n >> 2) * 4096 + (n & 3) * 256);
    sts1(b, prmt(w[n][0], w[n][1], 0x5410)); sts1(b + 128, prmt(w[n][0], w[n][1], 0x7632));
  }
}
DEV void xg_store(const XgAddr& x, uint32_t tag) {
  const uint32_t m = (~x.b >> 4) & 1;
#pragma unroll
  for (int k = 0; k < 4; ++k) {
    const uint4 v = lds4((x.b ^ ((k & 1) * 64)) + k * 2048);
    str4(x.dst + k * 4096, tagged(v.x, m, tag), v.y, v.z, v.w);
  }
}
template <int N, int M> DEV void fold(float (&v)[M], int lane, int bit) {
  const bool b = lane & bit;
#pragma unroll
  for (int k = 0; k < N; ++k) { const float sn = b ? v[k] : v[k + N], kp = b ? v[k + N] : v[k]; v[k] = kp + __shfl_xor_sync(0xffffffffu, sn, bit); }
}
DEV void refetch(uint32_t dst, const uint4* src, int half, int e, int w) {
#pragma unroll 1
  for (int r = 0; r < 2; ++r) {
    if (w == 0) { mbar_expect1(B_R + 8 * e, half); bulk(dst + r * half, src + r * (half >> 4), half, B_R + 8 * e); }
    mbar_wait(B_R + 8 * e, r);
    bar_sync(NB_WG + e, 128);
  }
}
DEV uint32_t kvslot(int cg, int pos) { return (pos & 2 ? SM_XA : SM_S1) + (cg < 4 ? 5 : 2) * 8192 + (pos & 1) * 4096; }
DEV uint32_t xstage(int q, int e) { return ((q + 1) & 2) ? SM_R + ((q & 2) + e) * 16384 : e ? SM_XB : SM_XA; }
DEV void cmul(float& orr, float& oi, float ar, float ai, float br, float bi) {
  float r = ar * br - ai * bi, i = ar * bi + ai * br; orr = r; oi = i;
}
DEV void cexp_(float al, float bt, float s, float& er, float& ei) {
  float mag = ex2(al * s), ph = bt * s;
  ph -= rintf(ph);
  float ang = ph * 6.283185307179586f;
  er = mag * __cosf(ang); ei = mag * __sinf(ang);
}

#define KS 2048
DEV void put8(uint32_t a, const float (&r)[8], const float (&i)[8]) {
  sts4(a, pack2(r[0], r[1]), pack2(r[2], r[3]), pack2(r[4], r[5]), pack2(r[6], r[7]));
  sts4(a + 1024, pack2(i[0], i[1]), pack2(i[2], i[3]), pack2(i[4], i[5]), pack2(i[6], i[7]));
}
DEV void tables(const uint32_t (&pv)[8], int k4, int w, int lane) {
  PW(4 * k4 + w)
  [[maybe_unused]] const int layer = 0;
  const float dt = bfr(__expf(bflo(pv[6])));
  const float al = dt * bflo(pv[0]) * 1.4426950408889634f, bt = dt * bflo(pv[1]) * 0.15915494309189535f;
  float qr[8], qi[8], yr[8], yi[8];
  cmul(qr[0], qi[0], bflo(pv[4]), bflo(pv[5]), dt * bflo(pv[2]), dt * bflo(pv[3]));
  PROFD(2, a_par, __float_as_uint(qr[0] + al + bt));
  float e1r, e1i, eMr, eMi, eLr, eLi;
  cexp_(al, bt, 1.f, e1r, e1i); cexp_(al, -bt, 8.f, yr[1], yi[1]); cexp_(al, -bt, 64.f, eMr, eMi); cexp_(al, bt, 256.f, eLr, eLi);
  const uint32_t ad = SB + k4 * 32768 + (w & 1) * 512 + lane * 16, am = ad + (w >> 1) * KS, an = ad + (8 + 3 * (w >> 1)) * KS;
  yr[0] = 1.f; yi[0] = 0.f;
#pragma unroll
  for (int k = 1; k < 8; ++k) {
    cmul(qr[k], qi[k], qr[k - 1], qi[k - 1], e1r, e1i);
    if (k > 1) cmul(yr[k], yi[k], yr[k - 1], yi[k - 1], yr[1], yi[1]);
  }
  put8(an, qr, qi);
#pragma unroll
  for (int j = 0; j < 4; ++j) {
    put8(am + j * 2 * KS, yr, yi);
#pragma unroll
    for (int k = 0; k < 8; ++k) {
      if (j == 0 && k == 0) { yr[0] = eMr; yi[0] = eMi; } else if (j < 3) cmul(yr[k], yi[k], yr[k], yi[k], eMr, eMi);
    }
    if (j == 0) {
#pragma unroll
      for (int k = 0; k < 8; ++k) { const int o = k < 4 ? 2 * k : k < 6 ? 2 * k - 8 : k - 2; cmul(qr[k], qi[k], qr[o], qi[o], eLr, eLi); }
      put8(an + KS, qr, qi);
    } else if (j == 1) {
#pragma unroll
      for (int k = 0; k < 5; ++k) cmul(qr[k], qi[k], qr[k ? k - 1 : 6], qi[k ? k - 1 : 6], eLr, eLi);
      put8(an + 2 * KS, qr, qi);
    }
  }
  PROF(3, a_tab);
}

DEV void sts16_if(uint32_t a, uint32_t v, bool c) { asm volatile("{.reg .pred q; .reg .b16 h; setp.ne.u32 q,%2,0; cvt.u16.u32 h,%1; @q st.shared.u16 [%0],h;}" :: "r"(a), "r"(v), "r"((uint32_t)c) : "memory"); }
DEV void sts1_if(uint32_t a, uint32_t v, bool c) { asm volatile("{.reg .pred q; setp.ne.u32 q,%2,0; @q st.shared.u32 [%0],%1;}" :: "r"(a), "r"(v), "r"((uint32_t)c) : "memory"); }
DEV void taps(uint32_t dskip, int k4, int w, int lane) {
  PW(4 * k4 + w)
  [[maybe_unused]] const int layer = 0;
  fence_async_smem();
  bar_sync((k4 & 1) ? NB_WG + k4 : NB_Q, (k4 & 1) ? 128 : 448);
  float d[24];
  undef(d);
  const uint64_t da = mkdesc(SB + k4 * 32768, 1024, KS, 0);
  wg_fence();
#pragma unroll
  for (int j = 0; j < 8; ++j) wg_ss48(d, da + j * 8, da + KS / 2 + j * 8, j);
  wg_commit();
  const int b = 8 * w + (lane >> 2), t = lane & 3, id = 32 * w + lane;
  constexpr int DO = T_O - T_E;
  const uint32_t te = SM_TAP + k4 * TAP_SZ + T_E, a0 = te - 16 * b - 4 * t;
  const uint32_t a1 = a0 - 512 - 4 * t, a2 = te - 2 * (511 + b) - 64 * t, a3 = te + (T_C - T_E) - 2 * (127 + b) - 128 * t;
  wg_wait<0>();
  PROF(4, a_mma);
  {
    const uint32_t v = pack2(d[1] + d[15], d[0] + d[14] + (id ? 0.f : bflo(dskip)));
    sts1(a0 + DO - 2, v); sts16(a0 - 2, v); sts16(a0, v >> 16);
  }
  {
    const uint32_t v = pack2(d[5] + d[19], d[4] + d[18]), u = prmt(v, v, 0x3232);
    const bool lo = t < 2, k512 = id == 2;
    sts1_if(k512 ? te - 2 * 512 : a1, u, (lo && id) || k512);
    sts1_if(k512 ? te - 2 * 514 : a1 - 4, k512 ? u : v, lo || k512);
    sts1_if(k512 ? te + DO - 2 * 513 : a1 + DO - 2, u, lo || k512);
    sts16(lo ? a1 + DO - 4 : a2 + DO - 194, v);
    sts16(lo ? (id ? a1 + DO + 2 : a1) : k512 ? te + DO - 2 * 511 : a2 + DO, u);
    sts16_if(a2 - 194, v, !lo);
    sts16_if(k512 ? te + DO - 2 * 514 : a2, u, !lo);
  }
  {
    const uint32_t v = pack2(d[8] + d[22], d[9] + d[23]);
    sts16_if(id ? a3 : te - 2 * 639, v, t < 2 || id == 2);
    sts16_if(a3 - 64, v >> 16, t < 2);
    sts16_if(te + DO - 2 * 639, v, id == 0);
  }
  bar_sync(NB_WG + k4, 128);
  mbar_arrive1_if(B_K, w == 0);
}

DEV uint32_t cpy(uint32_t v, uint32_t id) {
  uint32_t d; asm volatile("prmt.b32 %0,%1,%1,%2;" : "=r"(d) : "r"(v), "r"(id)); return d;
}
DEV uint32_t uoff(int s) { return (s ^ ((s >> 3) & 3)) * 16; }
template <bool FULL> DEV void boxes(const uint32_t (&u)[10], uint32_t a, uint32_t a9, uint32_t a7, uint32_t (&pv)[4]) {
  uint32_t v[8], p[8], x[4], y[4];
#pragma unroll
  for (int j = 0; j < 8; ++j) { v[j] = prmt(u[j], u[j + 1], 0x5432); p[j] = hadd2(u[j], v[j]); }
#pragma unroll
  for (int j = 0; j < 4; ++j) { x[j] = hadd2(hadd2(p[j + 1], p[j + 2]), u[j + 3]); y[j] = hadd2(v[j + 3], p[j + 4]); }
  sts4(a + R_A5, x[0], x[1], x[2], x[3]);
  sts4(a + R_A3, y[0], y[1], y[2], y[3]);
  if (FULL) {
#pragma unroll
    for (int j = 0; j < 4; ++j) { x[j] = hadd2(x[j], hadd2(v[j], v[j + 3])); y[j] = hadd2(x[j], hadd2(u[j], u[j + 4])); pv[j] = p[j + 4]; }
    sts4(a7, x[0], x[1], x[2], x[3]);
    sts4(a9, y[0], y[1], y[2], y[3]);
  }
}
DEV uint32_t shfl_up(uint32_t v, int d) { uint32_t r; asm volatile("shfl.sync.up.b32 %0,%1,%2,0,0xffffffff;" : "=r"(r) : "r"(v), "r"(d) : "memory"); return r; }
DEV void halo(uint32_t (&u)[10], uint32_t a, uint32_t b, int lane) {
  asm volatile("{.reg .pred p,q; setp.eq.s32 p,%8,0; setp.lt.s32 q,%8,2;\n@p ld.shared.v4.u32 {%2,%3,%4,%5},[%6];\n@q ld.shared.v2.u32 {%0,%1},[%7];}"
    : "+r"(u[0]), "+r"(u[1]), "+r"(u[2]), "+r"(u[3]), "+r"(u[4]), "+r"(u[5]) : "r"(a), "r"(b), "r"(lane));
}
#define W1 4
#define ROT 2
#define G1 -1
#define G2 0
#define G3 1
#define TPS 0x7135
#define GMASK ((G1 >= 0 ? 2 : 0) | (G2 >= 0 ? 4 : 0) | (G3 >= 0 ? 8 : 0))
#define GATE1(g, n, p) if (g >= 0 && (g & 3) == p) mbar_arrive1_if(B_G + 8 * n, k4 == (g >> 2));
#define GATE(p) GATE1(G1, 0, p) GATE1(G2, 1, p) GATE1(G3, 2, p)
#define TMASK(p) (((TPS & 15) == p) | ((((TPS >> 4) & 15) == p) << 1) | ((((TPS >> 8) & 15) == p) << 2) | ((((TPS >> 12) & 15) == p) << 3))
#define TURN(p) if (TMASK(p) == 15) bar_arrive(NB_T + 1 + k4, 256); else if (TMASK(p)) { if ((TMASK(p) >> k4) & 1) bar_arrive(NB_T + 1 + k4, 256); }
DEV void w_load(const CUtensorMap* mW, int cg, int h) {
  mbar_expect1(B_W + 8 * h, 24576);
  tma3(SM_S0 + (h & 3) * 24576, mW, 64 * cg, 64 * h, B_W + 8 * h);
}

DEV void conv(const Params& P, const CUtensorMap* mW, int c, int k4, int w, int layer) {
  const uint32_t zero = P.zero;
  PW(4 * k4 + w)
  int lane = lane_here(zero);
  const int g = lane >> 2, t = lane & 3, v = w ^ (ROT * (k4 & 1)), tid = 32 * v + lane;
  const uint32_t reg = SM_R + k4 * 16384, tp = SM_TAP + k4 * TAP_SZ;
  const uint32_t g0 = tp + ((g & 1) ? T_O : T_E) + 2 * (2 * t - g);
  uint32_t F[18][4], U[20], qc[4][4];
#define LO(q, a) q[0] = lds1(a); q[2] = lds1(a + 16);
#define HI(q, a) q[1] = lds1(a - 128); q[3] = lds1(a - 112);
  {
    const uint32_t ga = g0 - 32 * (w & 1) - 576 * (w >> 1), g2 = tp + T_C - 258 - 32 * w + 4 * (t - g);
    F[0][2] = lds1(ga + 48);
#pragma unroll
    for (int j = 0; j < 8; ++j) { F[j][0] = lds1(ga + 32 - 32 * j); F[j][1] = lds1(ga + 16 - 32 * j); }
#pragma unroll
    for (int j = 0; j < 20; ++j) U[j] = lds1(ga - 224 - 16 * j);
#pragma unroll
    for (int j = 0; j < 4; ++j) { LO(qc[j], g2 + 32 * j) HI(qc[j], g2 + 32 * j) }
  }
  if (layer) { mbar_wait(B_ED, 0); mbar_wait(B_ED + 8, 0); }
  sts4z_if(reg + lane * 16 + (w ? w * 3584 + 1024 : 0), w < 3);
  PROF(5, a_pre);
  if (k4 == 3 && w == 3) {
    mbar_wait(B_E, layer);
    mbar_wait(B_K, 0);
#pragma unroll
    for (int h = 0; h < 4; ++h) w_load(mW, c & 7, h);
  }
  const uint32_t bo = reg + R_B + tid * 16 + (v >> 1) * 1056, be = tid == 127 ? reg + R_B + 1024 : bo + (tid == 63 ? 2112 : 1056);
  const uint32_t a9 = (lane & 1) ? be : bo, a7 = (lane & 1) ? bo : be, ua = reg + R_U + uoff(tid);
  const uint32_t h1 = reg + R_U + v * 512 - 64, h2 = h1 + 24 - 16 * lane;
  keep(a9 & a7 & ua & h2, zero);
  mbar_wait(k4 && ((GMASK >> k4) & 1) ? B_G - 8 + 8 * k4 : B_E, layer);
  PROF(6, a_x);
  uint4 x[2];
  uint32_t pv[4];
  {
    uint4 s[4];
    uint32_t u[2][10];
#pragma unroll
    for (int z = 0; z < 2; ++z) { x[z] = lds4(reg + R_B + tid * 16 + z * 2048); s[2 * z] = lds4(SM_RES + tid * 16 + z * 2048); s[2 * z + 1] = lds4(SM_RES + tid * 16 + z * 2048 + 4096); }
    for (int it = 0;; ++it) {
      const uint32_t m = min(min(min((both(x[0].x, x[1].x, layer) | lane) & 1, min(s[0].x, s[0].z)), min(s[1].x, s[1].z)), min(min(s[2].x, s[2].z), min(s[3].x, s[3].z)));
      if (__builtin_expect(__all_sync(0xffffffffu, m != 0u), 1)) break;
      EVENT(16 + layer * 4 + k4);
      const int o = tid | here(zero);
#pragma unroll
      for (int z = 0; z < 2; ++z) x[z] = ldr4(&P.S->XG[(128 * k4 + c) * 256 + o] + z * 128);
#pragma unroll
      for (int z = 0; z < 4; ++z) {
        s[z] = ldr4(&P.S->SR[layer][c >> 4][o] + ((z >> 1) * 128 + (z & 1) * 256));
        sts4(SM_RES + tid * 16 + (z >> 1) * 2048 + (z & 1) * 4096, s[z].x, s[z].y, s[z].z, s[z].w);
      }
      spin_guard(it);
    }
#pragma unroll
    for (int z = 0; z < 2; ++z) {
      u[z][6] = hmul2(hsub2(x[z].x, s[2 * z].y), s[2 * z].x); u[z][7] = hmul2(hsub2(x[z].y, s[2 * z].w), s[2 * z].z);
      u[z][8] = hmul2(hsub2(x[z].z, s[2 * z + 1].y), s[2 * z + 1].x); u[z][9] = hmul2(hsub2(x[z].w, s[2 * z + 1].w), s[2 * z + 1].z);
      sts4(ua + z * 2048, u[z][6], u[z][7], u[z][8], u[z][9]);
    }
    u[1][0] = 0; u[1][1] = s[3].x; u[1][2] = s[2].x; u[1][3] = s[2].y; u[1][4] = s[2].z; u[1][5] = s[2].w;
    if (v < 2) {
#pragma unroll
      for (int j = 1; j < 6; ++j) u[1][j] = shfl_up(u[1][j < 2 ? 8 + j : 4 + j], j < 2 ? 2 : 1);
    }
#pragma unroll
    for (int j = 0; j < 6; ++j) u[0][j] = shfl_up(u[0][j < 2 ? 8 + j : 4 + j], j < 2 ? 2 : 1);
    bar_sync(NB_WG + k4, 128);
    GATE(0)
    PROF(7, a_u);
    halo(u[0], h1, h2, lane);
    halo(u[1], h1 + 2048, h2 + 2048, lane + 16 * (v & 2));
    sts4z_if(reg + R_B + 1040, tid == 0);
    boxes<true>(u[0], reg + tid * 16, a9, a7, pv);
    if (v < 2) boxes<false>(u[1], reg + tid * 16 + 2048, 0, 0, pv);
  }
  GATE(1)
  fence_async_smem();
  if (k4 == 3 && w == 0) {
    const uint32_t src = SM_RES + 8192;
#pragma unroll
    for (int z = 0; z < 4; ++z) sts4(src + lane * 16 + z * 512, 0, 0, 0, 0);
    fence_async_smem();
    __syncwarp();
#pragma unroll
    for (int z = 0; z < 2; ++z) {
      bulk_store(&P.S->H[(c + 8) * 256] + z * 128, src, 2048);
      bulk_store(P.S->F + ((c >> 3) * 64 + 4 * (c & 7)) + z * 32, src, 16);
    }
    bulk_store(&P.S->PS[c * 64], src, 1024);
    bulk_store(&P.S->ST[c * 4], src, 64);
    if (c < 5) bulk_store(P.S->C + (c + 5 - 5 * layer) * 1024, src, 128 * NCOPY * NSUB);
    asm volatile("cp.async.bulk.commit_group;" ::: "memory");
  }
  const uint32_t id = opq(0x3210u);
#pragma unroll
  for (int j = 0; j < 8; ++j) { F[j][3] = cpy(F[j][0], id); if (j) F[j][2] = cpy(F[j - 1][1], id); }
  PROF(8, a_box);
  bar_sync(NB_T + k4, k4 ? 256 : 128);
  PROF(9, a_turn);
  float acc[32], f1[24], f3[16];
  uint32_t qa[4][4], qb[4][4], fp[4];
  const uint64_t db = mkdesc(reg + R_U, 16, 512, 2) + 2;
#define STEP(mm, n) wg_fence(); mm; wg_commit(); wg_wait<n>();
#define D(j, n) STEP(wg_rs64k(acc, F[j], db - 2 * j, j), n)
#define C(j, n) STEP(wg_rs32t(f3, qc[j], mkdesc(reg + R_B, 128, 1040, 0) + 16 * j, j), n)
#define NIL(q, y) { const uint32_t z = y & zero; q[2][1] = cpy(z, 0); q[2][3] = cpy(z, 1); q[3][1] = cpy(z, 2); q[3][3] = cpy(z, 3); }
#define X(j) F[j][0] = cpy(U[2 * j - 16], ix); F[j][1] = cpy(U[2 * j - 15], ix); F[j][3] = cpy(F[j][0], ix); F[j][2] = cpy(F[j - 1][1], ix);
  const uint32_t g1 = g0 - 2 * 576 - 16 * w;
  const uint64_t d1 = mkdesc(reg + R_A5, 128, 512, 0);
  constexpr int O3 = (R_A3 - R_A5) / 16;
  uint32_t ix = id;
  undef(acc);
  D(0, 4) TURN(0) D(1, 4) D(2, 4) D(3, 4) D(4, 4) D(5, 2)
  undef(f3);
  C(0, 3) C(1, 3) TURN(1) C(2, 3) X(8) C(3, W1) X(9) LO(qa[0], g1)
  D(6, W1) HI(qa[0], g1) X(10) D(7, W1) LO(qa[1], g1 + 32) X(11) D(8, W1) HI(qa[1], g1 + 32) D(9, 4) LO(qa[2], g1 - 64)
  fp[0] = pack2(f3[0], f3[1]); fp[1] = pack2(f3[4], f3[5]); fp[2] = pack2(f3[8] + f3[2], f3[9] + f3[3]); fp[3] = pack2(f3[12] + f3[6], f3[13] + f3[7]);
  ix |= fp[0] & fp[1] & fp[2] & fp[3] & zero;
  X(12) D(10, 4) TURN(2) LO(qa[3], g1 - 32) X(13) X(14) D(11, 4) LO(qb[0], g1 - 192) X(15) D(12, 4) HI(qb[0], g1 - 192) X(16)
  D(13, 4) LO(qb[1], g1 - 160) X(17) D(14, 4) TURN(3) HI(qb[1], g1 - 160) NIL(qa, qa[1][0])
  D(15, 4) LO(qb[2], g1 - 256) D(16, 3) LO(qb[3], g1 - 224) NIL(qb, qa[1][1]) D(17, 2) TURN(4)
  PROF(10, a_den);
  undef(f1);
  wg_fence();
#pragma unroll
  for (int j = 0; j < 4; ++j) wg_rs48t(f1, qa[j], d1 + 16 * (j & 1) - 32 * (j >> 1), j);
  wg_commit();
  wg_wait<1>();
  TURN(5)
  wg_fence();
#pragma unroll
  for (int j = 0; j < 4; ++j) wg_rs48t(f1, qb[j], d1 + O3 + 16 * (j & 1) - 32 * (j >> 1), 1);
  wg_commit();
  TURN(6)
  lane = lane_here(zero);
  bar_sync(NB_WG + k4, 128);
  {
    const int p = (lane + 9 * (w >> 1)) & 31;
    const uint32_t ya = reg + ((w >> 1) ? R_B : R_U) + p * 64 + (((2 * (w & 1)) ^ ((p >> 1) & 3)) * 16), up = p < lane ? 2048 : 0;
#pragma unroll
    for (int z = 0; z < 4; ++z) {
      const float* a = acc + 16 * (z >> 1) + 2 * (z & 1);
      stsm4t((ya + (up ^ ((z >> 1) * 2048))) ^ ((z & 1) * 16), pack2(a[0], a[1]), pack2(a[4], a[5]), pack2(a[8], a[9]), pack2(a[12], a[13]));
    }
  }
  asm volatile("cp.async.bulk.wait_group 0;" ::: "memory");
  const uint32_t fa = reg + R_A5 + (lane >> 3) * 512 + w * 128 + (lane & 7) * 16;
  const uint32_t fc = reg + R_A3 + uoff(64 * (lane >> 4) + 16 * w + 2 * (lane & 7) + 1 - ((lane >> 3) & 1));
  uint32_t k1024 = lds16(tp + T_E - 2 * 639 + (fa & fc & zero));
  wg_wait<0>();
  GATE(2)
  PROF(11, a_far);
  bar_sync(NB_WG + k4, 128);
  stsm4(fc, fp[0], fp[1], fp[2], fp[3]);
  stsm4(fa, pack2(f1[0], f1[1]), pack2(f1[4], f1[5]), pack2(f1[8] + f1[2], f1[9] + f1[3]), pack2(f1[12] + f1[6], f1[13] + f1[7]));
  stsm2(fa + 2048, pack2(f1[16] + f1[10], f1[17] + f1[11]), pack2(f1[20] + f1[14], f1[21] + f1[15]));
  {
    const int o = 32 * v + lane;
    const uint32_t a = reg + uoff(o), b = reg + R_A5 + o * 16;
    uint4 y[2] = {hadd8(lds4(a + R_U), lds4(o >= 36 ? a + R_B : reg)), hadd8(lds4(a + R_U + 2048), lds4(a + R_B + 2048))};
    bar_sync(NB_WG + k4, 128);
    TURN(7)
    PROF(12, a_sts);
    const uint4 f = lds4(v >= 2 ? b - 1024 : reg), f2 = lds4(b + 1024);
    uint4 h = lds4(a + R_A3);
    const int e0 = (o >> 3) * 8192 + (128 * k4 + c) * 16 + (((o & 4) + ((o >> 1) & 1)) ^ (c & 7)) * 2 + (o & 1);
    const uint32_t me = (e0 & 3) == ((c >> 1) & 3), m0 = me & ~c, m1 = me & c, tag = 1 - layer;
    uint32_t* cp = cnt_at(P, 1 + 5 * layer + k4, c, lane);
    keep(cp, zero);
    k1024 = prmt(k1024, k1024, 0x1010);
    h = make_uint4(hfma2(pv[0], k1024, h.x), hfma2(pv[1], k1024, h.y), hfma2(pv[2], k1024, h.z), hfma2(pv[3], k1024, h.w));
    y[0] = hadd8(y[0], f); y[1] = hadd8(y[1], hadd8(f2, h));
    cnt_add(cp, 1 | (y[0].x & y[1].x & zero), (o ^ 96) < NCOPY);
#pragma unroll
    for (int z = 0; z < 2; ++z) {
      const uint4 r = hadd8(x[z], y[z]);
      str2((uint2*)P.S->XF + e0 + z * 131072, tagged(prmt(r.x, r.y, 0x5410), m0, tag), tagged(prmt(r.z, r.w, 0x5410), m1, tag));
      str2((uint2*)P.S->XF + (e0 ^ 4) + z * 131072, tagged(prmt(r.x, r.y, 0x7632), m0, tag), tagged(prmt(r.z, r.w, 0x7632), m1, tag));
    }
  }
  TURN(9)
  GATE(3)
  PROF(13, a_out);
}

#define WGATE 1
#define FH 1
#define QPIN 1
#define XORD 1
DEV void x_load(const Params& P, int c, int q, int layer) {
#pragma unroll
  for (int z = 0; z < 2; ++z) {
    const int e = z ^ (XORD && q == 3 && !(c & 4));
    mbar_expect1(B_X + 16 * q + 8 * e, 16384);
    bulk(xstage(q, e), P.S->XF + ((2 * (c >> 3) + 1 - e) * 4096 + q * 1024), 16384, B_X + 16 * q + 8 * e);
  }
}

DEV void means(uint32_t (&m)[4], int row, int lane, int layer, uint32_t zero) {
  mbar_wait(B_CS, 0);
  mbar_wait(B_ST, layer);
  const uint32_t a = SM_MISC + row * 4 + (lane & 28), k = (lane & 3) ? 0u : ~0u;
  m[0] = lds1(a) & k; m[1] = lds1(a + 32) & k; m[2] = m[0] & zero; m[3] = m[1] & zero;
}

DEV void attn_phase(const Params& P, int c, int e, int w, int lane, int layer) {
  PW(4 * e + w)
  const int cg = c & 7, J = 2 * (c >> 3) + 1 - e;
  float acc[96];
  zerov(acc);
  uint32_t m[4] = {0, 0, 0, 0};
#pragma unroll 1
  for (int q = 0;; ++q) {
    const uint64_t da = mkdesc(xstage(q, e), 16, 1024, 1), db = mkdesc(SM_S0 + (q & 1) * 49152, 8192, 1024, 1);
    const uint32_t wr = mbar_test2(B_W + 16 * q, layer), xa = xstage(q, e) + w * 4096 + lane * 132;
    mbar_wait(B_X + 16 * q + 8 * e, layer);
    for (int it = 0;; ++it) {
      const uint32_t ok = both(lds1(xa), lds1(xa ^ 32), layer) & both(lds1(xa ^ 64), lds1(xa ^ 96), layer);
      if (__all_sync(0xffffffffu, ok & 1)) break;
      EVENT(8 * layer + 2 * q + e);
#pragma unroll 1
      for (int j = 0; j < 8; ++j) cp16(xstage(q, e) + w * 4096 + j * 512 + lane * 16, P.S->XF + (J * 4096 + q * 1024 + w * 256 + j * 32 + lane));
      asm volatile("cp.async.wait_all;" ::: "memory");
      fence_async_smem();
      __syncwarp();
      spin_guard(it);
    }
    bool all = __all_sync(0xffffffffu, wr);
    if (q == 0 && e && w == 0) {
      bar_sync(NB_H, 256);
      cnt_wait(P, 2 + 5 * layer, c, lane);
      x_load(P, c, 1, layer);
      PROF(27, m_xi);
    }
    if (q == 3 && e) means(m, 16 * w, lane, layer, P.zero);
    if (!all) { mbar_wait(B_W + 16 * q, layer); all = mbar_test(B_W + 16 * q + 8, layer); }
    bar_sync(e ? NB_Q : q ? NB_T : NB_T + 4, 256);
    PROF(14 + q, m_q);
    wg_fence();
#pragma unroll
    for (int k = 0; k < 8; ++k) {
      if (k == 4) { wg_commit(); if (!all) mbar_wait(B_W + 16 * q + 8, layer); wg_fence(); }
      wg_ss192(acc, da + k * 128, db + (k >> 2) * 1536 + (k & 3) * 128, 1);
    }
    wg_commit();
    if (q == 3) break;
    bar_arrive(e ? NB_T : NB_Q, 256);
    if (FH) { wg_wait<1>(); mbar_arrive1_if(B_FH + 8 * q, e && q < 2); }
    wg_wait<0>();
    mbar_arrive1(B_F + 8 * q);
  }
  const int pos = 2 - 2 * e + (w >> 1);
  uint4* h = P.S->H + ((c + 8) * 256 + (w & 1) * 128 + lane);
  const uint32_t kw = kvslot(cg, pos + 1) + (w & 1) * 2048 + lane * 16;
  {
    if (!e) means(m, 64 + 16 * w, lane, layer, P.zero);
    PROF(28, m_sub);
    wg_fence();
    wg_rs192t(acc, m, mkdesc(SM_CS, 0, 32, 0));
    wg_commit();
    bar_arrive_if(NB_Q, 256, !e);
    keep(h, kw & P.zero);
    mbar_wait(B_F + 16, layer);
    wg_wait<0>();
    mbar_arrive1(B_F + 24);
  }
  PROF(18, m_qkv);
  uint32_t Q[4][4], K[4][3][2], V[4][3][2];
  uint32_t pin = P.zero;
#pragma unroll
  for (int z = 0; z < 4; ++z) {
    V[z][1][0] = pack2(acc[64 + 8 * z], acc[65 + 8 * z]); V[z][1][1] = pack2(acc[68 + 8 * z], acc[69 + 8 * z]);
    K[z][1][0] = pack2(acc[32 + 8 * z], acc[33 + 8 * z]); K[z][1][1] = pack2(acc[36 + 8 * z], acc[37 + 8 * z]);
    pin &= V[z][1][0] & V[z][1][1];
    K[z][2][0] = nz(pack2(acc[34 + 8 * z], acc[35 + 8 * z])); K[z][2][1] = pack2(acc[38 + 8 * z], acc[39 + 8 * z]);
    V[z][2][0] = pack2(acc[66 + 8 * z], acc[67 + 8 * z]); V[z][2][1] = pack2(acc[70 + 8 * z], acc[71 + 8 * z]);
    str4_if(h + z * 32, K[z][2][0], K[z][2][1], V[z][2][0], V[z][2][1], pos == 3);
  }
#pragma unroll
  for (int z = 0; z < 8; ++z) V[z >> 1][2][z & 1] = movm(z < 7 ? V[z >> 1][2][z & 1] : V[3][2][1] | pin);
  if (pos == 0) mbar_wait(B_F + 24, layer);
#pragma unroll
  for (int z = 0; z < 4; ++z) sts4_if(kw + z * 512, K[z][2][0], K[z][2][1], V[z][2][0], V[z][2][1], pos < 3);
  bar_arrive(NB_H + pos + 1, 128);
  PROF(19, m_kv);
  lane |= here(P.zero);
  int g = lane >> 2, t = lane & 3;
  const uint32_t ra = SM_STAT + 256 + (32 - 32 * e + 8 * w) * 16, ob = e ? SM_S1 : SM_XA;
  const float r0 = lds1f(ra + (g >> 1) * 16 + (g & 1) * 4), r1 = lds1f(ra + 64 + (g >> 1) * 16 + (g & 1) * 4);
  const uint4 k1 = lds4(ra + 16 * t), k2 = lds4(ra + 64 + 16 * t);
#pragma unroll
  for (int z = 0; z < 8; ++z) {
    V[z >> 1][1][z & 1] = movm(V[z >> 1][1][z & 1]);
    Q[z >> 1][2 * (z & 1)] = pack2(acc[4 * z], acc[4 * z + 1]);
    Q[z >> 1][2 * (z & 1) + 1] = pack2(acc[4 * z + 2], acc[4 * z + 3]);
    pin &= Q[z >> 1][2 * (z & 1)] & Q[z >> 1][2 * (z & 1) + 1];
  }
  {
    const bool p0 = 2 * t > g, p1 = 2 * t + 1 > g, first = c < 8 && pos == 0;
    const uint32_t M = (p0 ? 0xFFFFu : 0u) | (p1 ? 0xFFFF0000u : 0u);
    const float sc0 = r0 * (0.25f * 1.4426950408889634f), sc1 = r1 * (0.25f * 1.4426950408889634f);
    const float sk2 = __uint_as_float(p0 ? k1.x : k2.x) * sc1, sk3 = __uint_as_float(p1 ? k1.y : k2.y) * sc1;
    const int oo = cg * 512 + (2 * (w & 2) + (w & 1)) * 64 + (lane ^ (g >> 1));
    uint4* O = P.S->O + (J * 4096 + oo);
    keep(oo, pin & M & __float_as_uint(sk2) & __float_as_uint(sk3) & __float_as_uint(sc0));
    mbar_wait(B_F + 24, layer);
    float L[4][4];
#pragma unroll
    for (int z = 0; z < 4; ++z) {
      float S[4];
      mma16z(L[z], Q[z][0], Q[z][1], Q[z][2], Q[z][3], K[z][1][0], K[z][1][1]);
      mma16z(S, Q[z][0], Q[z][1], Q[z][2], Q[z][3], K[z][2][0], K[z][2][1]);
      L[z][2] = (p0 ? L[z][2] : S[2]) * sk2; L[z][3] = (p1 ? L[z][3] : S[3]) * sk3;
      if (QPIN) pin &= __float_as_uint(L[z][2]) & __float_as_uint(L[z][3]);
    }
    bar_sync(NB_H + pos + pin, pos ? 128 : 160);
    const uint4 k0 = lds4(ra - 192 + 16 * t);
#pragma unroll
    for (int z = 0; z < 4; ++z) {
      const uint4 hv = lds4(kvslot(cg, pos) + (w & 1) * 2048 + lane * 16 + z * 512);
      K[z][0][0] = hv.x; K[z][0][1] = hv.y; V[z][0][0] = hv.z; V[z][0][1] = hv.w;
    }
    PROF(20, m_halo);
    const float sk0 = __uint_as_float(p0 ? k0.x : k1.x) * sc0, sk1 = __uint_as_float(p1 ? k0.y : k1.y) * sc0;
    const uint32_t rm[4] = {k0.z & M, k1.z & ~M, k1.z & M, k2.z & ~M}, s0 = k0.w | P.zero, s1 = k1.w | P.zero;
#pragma unroll
    for (int h2 = 0; h2 < 2; ++h2) {
      uint32_t A[2], B[2], mx[2];
#pragma unroll
      for (int z = 0; z < 2; ++z) {
        const int h = 2 * h2 + z;
        float S[4];
        mma16z(S, Q[h][0], Q[h][1], Q[h][2], Q[h][3], K[h][0][0], K[h][0][1]);
        if (first) { S[0] = __uint_as_float(0xFF800000u); S[1] = S[0]; }
        A[z] = pack2((p0 ? S[0] : L[h][0]) * sk0, L[h][2]);
        B[z] = pack2((p1 ? S[1] : L[h][1]) * sk1, L[h][3]);
      }
#pragma unroll
      for (int z = 0; z < 2; ++z) mx[z] = hmax2(A[z], B[z]);
#pragma unroll
      for (int z = 0; z < 2; ++z) mx[z] = hmax2(mx[z], __shfl_xor_sync(0xffffffffu, mx[z], 1));
#pragma unroll
      for (int z = 0; z < 2; ++z) mx[z] = hmax2(mx[z], __shfl_xor_sync(0xffffffffu, mx[z], 2));
      float Oa[2][3][4];
#pragma unroll
      for (int z = 0; z < 2; ++z) {
        const int h = 2 * h2 + z;
        const uint32_t a = hsub2(A[z], mx[z]), b = hsub2(B[z], mx[z]);
        const uint32_t w0 = pack2(ex2(bflo(a)), ex2(bflo(b))), w1 = pack2(ex2(bfhi(a)), ex2(bfhi(b)));
        const uint32_t u0 = hmul2(w0, rm[0]), u1 = hmul2(w0, rm[1]), u2 = hmul2(w1, rm[2]), u3 = hmul2(w1, rm[3]);
        const uint32_t z0 = w0 & P.zero, z1 = w1 & P.zero;
        mma16z(Oa[z][2], u0, z0, u1, u2, s0, s1);
#pragma unroll
        for (int d = 0; d < 2; ++d) mma16z(Oa[z][d], u0, z0, u1, u2, V[h][0][d], V[h][1][d]);
        mma8(Oa[z][2], z1, u3, k2.w);
#pragma unroll
        for (int d = 0; d < 2; ++d) mma8(Oa[z][d], z1, u3, V[h][2][d]);
      }
#pragma unroll
      for (int r = 0; r < 4; r += 2) {
        const float i0 = rcp(Oa[0][2][r]), i1 = rcp(Oa[1][2][r]);
        const uint32_t o0 = pack2(Oa[0][0][r] * i0, Oa[0][0][r + 1] * i0), o1 = pack2(Oa[0][1][r] * i0, Oa[0][1][r + 1] * i0);
        const uint32_t o2 = pack2(Oa[1][0][r] * i1, Oa[1][0][r + 1] * i1), o3 = pack2(Oa[1][1][r] * i1, Oa[1][1][r + 1] * i1);
        str4(O + h2 * 32 + r * 64, o0, o1, o2, o3);
        sts4(ob + oo * 16 + h2 * 512 + r * 1024, o0, o1, o2, o3);
      }
    }
  }
  bar_arrive(NB_T + 1 + e, 160);
  fence_async_smem();
  PROF(21, m_att);
  lane = lane_here(P.zero); g = lane >> 2; t = lane & 3;
  uint32_t res[8][2];
  mbar_wait(B_RES, layer);
  {
    const uint32_t a = SM_RES + e * 8192 + (lane >> 4) * 1024 + (lane & 7) * 128 + (((2 * (w & 2) + ((lane >> 2) & 2) + (w & 1)) ^ (lane & 7)) * 16);
#pragma unroll
    for (int j = 0; j < 8; j += 2) ldsm4t(res[j][0], res[j][1], res[j + 1][0], res[j + 1][1], a + j * 1024);
  }
  PROF(26, m_res);
  if (WGATE) bar_sync(NB_T, 256); else bar_sync(NB_WG + e, 128);
  XgAddr xa = xg_addr<true>(P.S->XG + (64 * cg * 256 + 8 * J), ob, w, lane, P.zero);
  uint4* ps = &P.S->PS[((4 * J + w) * 8 + cg) * 8 + g];
  keep(ps, P.zero);
  if (layer) {
    xa.a = ob + w * 2048 + (lane & 15) * 128 + (((lane >> 4) ^ (lane & 7)) * 16);
    xa.b = ob + w * 2048 + (lane >> 3) * 128 + (((lane & 7) ^ (lane >> 3)) * 16);
    xa.dst = (uint4*)P.out + ((64 * J + 16 * w + 2 * (lane >> 3)) * 64 + 8 * cg + (lane & 7));
  }
  uint32_t y[8][2];
#pragma unroll 1
  for (int it = 0;; ++it) {
    float ac[32];
#pragma unroll
    for (int j = 0; j < 16; ++j) {
      asm volatile("shl.b32 %0,%1,16;" : "=f"(ac[2 * j]) : "r"(res[j >> 1][j & 1]));
      asm volatile("and.b32 %0,%1,0xFFFF0000;" : "=f"(ac[2 * j + 1]) : "r"(res[j >> 1][j & 1]));
    }
#pragma unroll 1
    for (int n = 0; n < 8; ++n) {
      const int s = n == 0 ? cg : n - (n <= cg);
      mbar_wait(n ? B_O + 64 * e + 8 * s : B_WO, layer);
      if (n == 1) PROF(22, m_o1);
      if (n == 7) PROF(23, m_o7);
      const uint64_t da = mkdesc(ob + s * 8192, 16, 1024, 2), db = mkdesc(SM_R + s * 8192, 16, 1024, 1);
      wg_fence();
#pragma unroll
      for (int k = 0; k < 4; ++k) wg_ss64(ac, da + (k >> 1) * 32 + (k & 1) * 2, db + k * 128, 1);
      wg_commit();
    }
    wg_wait<0>();
    const bool bad = ac[0] != ac[0] || ac[2] != ac[2];
#pragma unroll
    for (int j = 0; j < 8; ++j) {
      y[j][0] = pack2(ac[4 * j], ac[4 * j + 1]); y[j][1] = pack2(ac[4 * j + 2], ac[4 * j + 3]);
    }
    if (!bar_any(NB_WG + e, 128, bad) || it == 16) break;
    EVENT(24 + 2 * layer + e);
    refetch(ob, P.S->O + J * 4096, 32768, e, w);
  }
  PROF(24, m_wo);
  if (layer == 0) {
    const float4 s = gram(y, g, P.zero);
    xg_put<true>(xa, y);
    str4_if(ps, nz(__float_as_uint(s.x)), __float_as_uint(s.y), __float_as_uint(s.z), __float_as_uint(s.w), t == (g >> 1));
    mbar_arrive1(B_ED + 8 * e);
    bar_sync(NB_WG + e, 128);
    xg_store(xa, 0);
    bar_arrive(NB_T + 3, 288);
  } else {
#pragma unroll
    for (int j = 0; j < 8; j += 2) stsm4(xa.a ^ (j * 16), y[j][0], y[j][1], y[j + 1][0], y[j + 1][1]);
    __syncwarp();
#pragma unroll
    for (int k = 0; k < 4; ++k) {
      const uint4 v = lds4((xa.b ^ ((k & 1) * 64)) + k * 512);
      stw4(xa.dst + ((k & 1) * 8 + (k >> 1)) * 64, v.x, v.y, v.z, v.w);
    }
  }
  PROF(25, m_epi);
}

#define HDELAY 300
#define ODELAY 200
#define PDELAY 0
#define FDELAY 300
#define CSP 0
#define CSU 4
#define XDEL 300
#define PZB B_X + 48
#define WOQ 2
#define H5 1
#define SRDELAY 350

DEV void o_load(const Params& P, int c, int e, int lane, int layer) {
  PW(8 + e)
  const int J = 2 * (c >> 3) + 1 - e;
#pragma unroll 1
  for (int s = 0; s < 8; ++s) mbar_expect1(B_O + 64 * e + 8 * s, s == (c & 7) ? 0 : 8192);
  const uint4* src = P.S->O + J * 4096;
  const uint32_t* fp = P.S->F + (J * 32 + (lane & 28));
  keep(fp, P.zero);
  bar_sync(NB_T + 1 + e, 160);
  flag_set1(P.S->F + (J * 32 + 4 * (c & 7)));
  if (ODELAY) delay(ODELAY);
  PROF(26, a_go);
  poll(fp, 1);
  PROF(25, h_seen);
  bar_sync_if(NB_Q, 64, e);
#pragma unroll 1
  for (int n = 0; n < 7; ++n) {
    const int s = n + (n >= (c & 7));
    bulk((e ? SM_S1 : SM_XA) + s * 8192, src + s * 512, 8192, B_O + 64 * e + 8 * s);
  }
  bar_arrive_if(NB_Q, 64, !e);
  PROF(28, a_o);
}

DEV void stats(const Params& P, int c, int w, int lane, int layer) {
  PW(12 + w)
  lane = opq(lane);
  const int r = (lane & 6) + ((lane >> 3) & 1), k = (2 * (c & 3) + (lane & 1)) ^ r, e = 1 - ((c >> 2) & 1);
  const uint32_t o = (32 * w + 8 * (lane >> 4) + r) * 128 + k * 16;
  const uint32_t mk = ((k & 1) == (r >> 2)) << (r & 3), tag = 1 - layer;
  float v[16];
#pragma unroll
  for (int z = 0; z < 16; ++z) v[z] = 0.f;
#pragma unroll 1
  for (int q = 0; q < 4; ++q) {
    mbar_wait(B_X + 16 * q + 8 * e, layer);
    PROF(19 + q, s_l);
    uint4 x, y;
    for (int it = 0;; ++it) {
      x = lds4v(xstage(q, e) + o); y = lds4v(xstage(q, e) + o + 2048);
      const uint32_t bad = (((x.x ^ tag) | (y.x ^ tag)) & mk) | (((x.y ^ tag) | (y.y ^ tag)) & (mk >> 1)) |
                           (((x.z ^ tag) | (y.z ^ tag)) & (mk >> 2)) | (((x.w ^ tag) | (y.w ^ tag)) & (mk >> 3));
      if (!__any_sync(0xffffffffu, bad & 1)) break;
      spin_guard(it);
    }
    mbar_arrive1(B_F + 8 * q);
    const uint32_t ws[8] = {x.x, x.y, x.z, x.w, y.x, y.y, y.z, y.w};
#pragma unroll
    for (int z = 0; z < 8; ++z) {
      const float lo = bflo(ws[z]), hi = bfhi(ws[z]);
      float* u = v + 4 * (z & 3);
      u[0] += lo; u[1] += lo * lo; u[2] += hi; u[3] += hi * hi;
    }
  }
  PROFD(14, s_part, __float_as_uint(v[0]));
  fold<8>(v, lane, 16); fold<4>(v, lane, 8); fold<2>(v, lane, 4); fold<1>(v, lane, 2);
  PROFD(16, s_fold, __float_as_uint(v[0]));
  if (w) {
    sts1(SM_MISC - 128 + w * 128 + lane * 4, __float_as_uint(v[0]));
    bar_arrive(NB_P, 128);
  } else {
    bar_sync(NB_P, 128);
    v[0] += lds1f(SM_MISC + lane * 4) + lds1f(SM_MISC + 128 + lane * 4) + lds1f(SM_MISC + 256 + lane * 4);
    float m;
    const float sd = ln_sd(v[0], __shfl_xor_sync(0xffffffffu, v[0], 2), m);
    mbar_wait(B_ST + 8, layer);
    if (!(lane & 2)) str1((uint32_t*)P.S->ST + (16 * c + 8 * (lane & 1) + (lane >> 2)), pack2(m, sd));
    sts4(SM_STAT - 32 + min(lane, 17) * 16, 0x3F800000u, 0x3F800000u, 0x3F803F80u, 0x3F803F80u);
    fence_async_smem();
    PROF(17, s_pub);
    uint4 s;
    for (int it = 0;; ++it) {
      s = ldr4(P.S->ST + ((c >> 3) * 32 + lane));
      if (__all_sync(0xffffffffu, min4(s) != 0u)) break;
      spin_guard(it);
    }
    PROF(18, s_seen);
    const float r0 = rcp(bfhi(s.x)), r1 = rcp(bfhi(s.y)), r2 = rcp(bfhi(s.z)), r3 = rcp(bfhi(s.w));
    const uint32_t sg = 0x80008000u;
    sts4(SM_MISC + lane * 16, prmt(s.x, s.x, 0x1010) ^ sg, prmt(s.y, s.y, 0x1010) ^ sg, prmt(s.z, s.z, 0x1010) ^ sg, prmt(s.w, s.w, 0x1010) ^ sg);
    sts4(SM_STAT + 256 + lane * 32, __float_as_uint(r0), __float_as_uint(r1), pack2(r0, r1), prmt(s.x, s.y, 0x7632));
    sts4(SM_STAT + 272 + lane * 32, __float_as_uint(r2), __float_as_uint(r3), pack2(r2, r3), prmt(s.z, s.w, 0x7632));
    __syncwarp();
    mbar_arrive1(B_ST);
  }
  PROF(15, s_stat);
  if (w == 1) {
    mbar_wait(B_ST, layer);
    if (c >= 8) {
      uint2 s;
      for (int it = 0;; ++it) {
        s = ldr2((const uint2*)P.S->ST + ((c >> 3) * 64 - 12 + (lane & 11)));
        if (__all_sync(0xffffffffu, min(s.x, s.y) != 0u)) break;
        spin_guard(it);
      }
      const float r0 = rcp(bfhi(s.x)), r1 = rcp(bfhi(s.y));
      sts4(SM_STAT + 64 + (lane & 11) * 16, __float_as_uint(r0), __float_as_uint(r1), pack2(r0, r1), prmt(s.x, s.y, 0x7632));
    }
    bar_arrive(NB_H, 160);
  }
  if (w >= 2) {
    const uint4* h = P.S->H + (c * 256 + (w & 1) * 128 + lane);
    uint4 hv[4];
#pragma unroll
    for (int z = 0; z < 4; ++z) hv[z] = make_uint4(0, 0, 0, 0);
    bar_sync(NB_RL, 128);
    PROFD(26, s_hb, lds1v(SM_MISC));
    delay(HDELAY);
    for (int it = 0; c >= 8; ++it) {
#pragma unroll
      for (int z = 0; z < 4; ++z) hv[z] = ldr4(h + z * 32);
      if (__all_sync(0xffffffffu, min(min(hv[0].x, hv[1].x), min(hv[2].x, hv[3].x)) != 0u)) break;
      spin_guard(it);
    }
    mbar_wait(B_F + 24, layer);
#pragma unroll
    for (int z = 0; z < 4; ++z) sts4(kvslot(c & 7, 0) + (w & 1) * 2048 + lane * 16 + z * 512, hv[z].x, hv[z].y, movm(hv[z].z), movm(hv[z].w));
    bar_arrive(NB_H, 160);
    PROF(25, s_halo);
  }
}

DEV void finalize(const Params& P, int c, int lane, int layer) {
  PW(12)
  uint2* so = (uint2*)P.S->SR[layer] + ((lane >> 3) * 1024 + (lane & 2) * 256 + 4 * c + ((lane >> 1) & 2) + (lane & 1));
  const uint4* ps = &P.S->PS[c * 64 + lane];
  keep(so, P.zero); keep(ps, P.zero);
  uint4 a, b;
  if (layer == 0) {
    bar_sync(NB_P, 256);
    a = lds4(SM_RES + 8192 + lane * 16); b = lds4(SM_RES + 8704 + lane * 16);
  } else {
    mbar_wait(B_ED + 8 - 2 * (c & 4), 0);
    delay(FDELAY);
    for (int it = 0;; ++it) {
      a = ldr4(ps); b = ldr4(ps + 32);
      if (__all_sync(0xffffffffu, min(a.x, b.x) != 0u)) break;
      spin_guard(it);
    }
  }
  float z[4] = {__uint_as_float(a.x) + __uint_as_float(b.x), __uint_as_float(a.y) + __uint_as_float(b.y),
                __uint_as_float(a.z) + __uint_as_float(b.z), __uint_as_float(a.w) + __uint_as_float(b.w)};
#pragma unroll
  for (int o = 8; o < 32; o <<= 1)
#pragma unroll
    for (int k = 0; k < 4; ++k) z[k] += __shfl_xor_sync(0xffffffffu, z[k], o);
  const float m0 = z[0] * (1.f / 512.f), m1 = z[2] * (1.f / 512.f);
  const float r0 = rsq(fmaxf(z[1] * (1.f / 512.f) - m0 * m0, 0.f) + 1e-5f), r1 = rsq(fmaxf(z[3] * (1.f / 512.f) - m1 * m1, 0.f) + 1e-5f);
  const uint32_t wr = nz(pack2(r0, r1)), wm = pack2(m0, m1);
  str2(so, wr, wm); str2(so + 4096, wr, wm);
  bar_arrive_if(NB_Q, 448, !layer);
  PROF(23, s_sr);
}

DEV void announce(const Params& P, int c, int lane, int layer) {
  PW(13)
  uint32_t* cp = cnt_at(P, 5 * layer, c, lane);
  keep(cp, P.zero);
  bar_sync(NB_T + 3, layer ? 288 : 160);
  cnt_add(cp, 1, lane < NCOPY);
  if (!layer) { bar_sync(NB_Q, 448); fence_async_smem(); }
  PROF(24, s_own);
}

DEV void fetch(const Params& P, int c, int lane, int layer) {
  PW(13)
  mbar_expect1(B_E, 24576);
  cnt_wait(P, 5 * layer, c, lane);
#pragma unroll
  for (int k = 0; k < 4; ++k) bulk(SM_R + k * 16384 + R_B, P.S->XG + (128 * k + c) * 256, 4096, B_E);
  if (layer) delay(SRDELAY);
  bulk(SM_RES, P.S->SR[layer][c >> 4], 8192, B_E);
  if (!layer) { if (!CSP) l2_prefetch(P.wqkv + c * 6144, 12288); l2_prefetch(P.wo + c * 2048, 4096); }
  PROF(25, s_all);
}

DEV void cs_part(const Params& P, int c, int w, int lane, int layer) {
  float cs[8];
#pragma unroll
  for (int k = 0; k < 8; ++k) cs[k] = 0.f;
  const int col = w * 512 + 64 * (c & 7) + 8 * (lane & 7);
#pragma unroll 1
  for (int r = 8 * layer; r < 8; r += CSU) {
    uint4 v[CSU];
#pragma unroll
    for (int k = 0; k < CSU; ++k) v[k] = ldnc4(P.wqkv + ((32 * (c >> 3) + 4 * r + (lane >> 3)) * 1536 + col) + 4 * k * 1536);
#pragma unroll
    for (int k = 0; k < CSU; ++k) {
      cs[0] += bflo(v[k].x); cs[1] += bfhi(v[k].x); cs[2] += bflo(v[k].y); cs[3] += bfhi(v[k].y);
      cs[4] += bflo(v[k].z); cs[5] += bfhi(v[k].z); cs[6] += bflo(v[k].w); cs[7] += bfhi(v[k].w);
    }
  }
  fold<4>(cs, lane, 16); fold<2>(cs, lane, 8);
  str2((float*)P.S->CS + ((c >> 3) * 1536 + col + 2 * (lane >> 3)), max(__float_as_uint(cs[0]), 1u - layer), __float_as_uint(cs[1]));
}

DEV void cs_sum(const Params& P, int c, int w, int lane) {
  float a, b;
  for (int it = 0;; ++it) {
    uint32_t m = ~0u;
    a = b = 0.f;
#pragma unroll
    for (int k = 0; k < 16; ++k) {
      const uint2 u = ldr2((const float*)P.S->CS + (w * 512 + 64 * (c & 7) + 2 * lane) + k * 1536);
      a += __uint_as_float(u.x); b += __uint_as_float(u.y); m = min(m, u.x);
    }
    if (__all_sync(0xffffffffu, m != 0u)) break;
    spin_guard(it);
  }
  const uint32_t hi = pack2(a, b), ad = SM_CS + w * 256 + (lane >> 2) * 32 + (lane & 3) * 4;
  sts1(ad, hi); sts1(ad + 16, pack2(a - bflo(hi), b - bfhi(hi)));
  fence_async_smem();
  __syncwarp();
  mbar_arrive1(B_CS);
}

DEV void x0_get(uint32_t (&x)[8][2], uint32_t a) {
  asm volatile("cp.async.wait_group 0;" ::: "memory");
#pragma unroll
  for (int z = 0; z < 4; ++z) {
    const uint4 v = lds4(a + z * 512);
    x[2 * (z & 2)][z & 1] = v.x; x[2 * (z & 2) + 1][z & 1] = v.y; x[2 * (z & 2) + 2][z & 1] = v.z; x[2 * (z & 2) + 3][z & 1] = v.w;
  }
}

DEV void par_load(const Params& P, int ch, int m, uint32_t (&pv)[8]) {
  const int mo = ch * 128 + m;
  pv[0] = ldnc16(P.Are + mo); pv[1] = ldnc16(P.Aim + mo); pv[2] = ldnc16(P.Bre + mo); pv[3] = ldnc16(P.Bim + mo);
  pv[4] = ldnc16(P.Cre + mo); pv[5] = ldnc16(P.Cim + mo); pv[6] = ldnc16(P.logdt + ch); pv[7] = ldnc16(P.dskip + ch);
}

__global__ void __launch_bounds__(NTHR, 1)
fused_kernel(const __grid_constant__ Params P, const __grid_constant__ CUtensorMap mapW,
             const __grid_constant__ CUtensorMap mapWo) {
  extern __shared__ __align__(1024) uint8_t smem_raw[];
  if (s2u(smem_raw) != SB) __trap();
  const int warp0 = __shfl_sync(0xffffffffu, threadIdx.x >> 5, 0), lane0 = threadIdx.x & 31;
  uint32_t smid; asm volatile("mov.u32 %0,%%smid;" : "=r"(smid));
  const int c = __shfl_sync(0xffffffffu, P.by_sm ? P.role[smid] : blockIdx.x, 0);
  if (c == 255) {
    if (threadIdx.x < NCOPY * NSUB)
#pragma unroll 1
      for (int it = 0; it < 256 && ldr1(P.S->C + 32 * threadIdx.x) < 128 / NSUB; ++it) __nanosleep(200);
    return;
  }
  const int cg = c & 7;
  PW(warp0)
  uint32_t dskip;
  {
    [[maybe_unused]] const int layer = 0;
    const int lane = lane0, g = lane >> 2, t = lane & 3, warp = warp0, k4 = warp >> 2, w = warp & 3;
    uint32_t pv[8];
    if (k4 < 3) par_load(P, 128 * k4 + c, 32 * w + lane, pv);
    else {
#pragma unroll
      for (int n = 0; n < 8; ++n) pv[n] = 0;
    }
    __syncthreads();
    if (XDEL) delay(XDEL);
    const uint16_t* r = P.x0 + ((k4 < 2 ? 8192 * c + 64 * warp : (128 * (c >> 3) + 16 * w) * 512 + 64 * cg) + 1024 * g + 8 * t);
    const uint32_t xa = SM_R + k4 * 16384 + w * 2048 + lane * 16;
    if (k4 != 2) {
#pragma unroll
      for (int z = 0; z < 4; ++z) cp16(xa + z * 512, r + (z & 1) * 512 + (z & 2) * 16);
    }
    sts4(SM_TAP + k4 * TAP_SZ + (32 * w + lane) * 16, 0, 0, 0, 0);
    sts4z_if(SM_TAP + k4 * TAP_SZ + 2048 + (32 * w + lane) * 16, w < 3);
    uint32_t x[8][2];
    if (k4 == 3) {
#pragma unroll
      for (int z = 0; z < 4; ++z) cp16(xa - 16384 + z * 512, r + 32768 + (z & 1) * 512 + (z & 2) * 16);
      asm volatile("cp.async.commit_group;" ::: "memory");
      if (threadIdx.x == 448) {
        asm volatile("prefetch.tensormap [%0];" :: "l"(&mapW) : "memory");
        asm volatile("prefetch.tensormap [%0];" :: "l"(&mapWo) : "memory");
      }
      __syncwarp();
      if (PDELAY) delay(PDELAY);
      par_load(P, 128 * k4 + c, 32 * w + lane, pv);
      XgAddr xd = xg_addr<false>(P.S->XG + (64 * cg * 256 + 16 * (c >> 3)), SM_R + 3 * 16384 + 8192, w, lane, P.zero);
      x0_get(x, xa);
      PROF(27, a_ld);
      xg_put<false>(xd, x);
      x0_get(x, xa - 16384);
      xd.a -= 16384;
      xg_put<false>(xd, x);
      bar_sync(NB_WG + 3, 128);
      xg_store(xd, 1);
      xd.b -= 16384; xd.dst += 8;
      xg_store(xd, 1);
      bar_arrive(NB_T + 3, 160);
      bar_sync(NB_Q, 448);
    } else asm volatile("cp.async.commit_group;" ::: "memory");
    tables(pv, k4, w, lane);
    if (k4 < 2) {
      x0_get(x, xa);
      const float4 s = gram(x, g, P.zero);
      if (t == (g >> 1)) sts4f(SM_RES + 8192 + (warp * 8 + g) * 16, s.x, s.y, s.z, s.w);
      __syncwarp();
      bar_arrive_if(NB_P, 256, warp != 7);
    }
    if (k4 == 2) {
#pragma unroll
      for (int n = 0; n < 14; ++n) mbar_init1(SM_BAR + (n < 10 ? w * 80 : 240 + w * 32) + n * 8, n < 10 ? 1 : (CNT >> (8 * w + 2 * (n - 10 & 2))) & 15);
    }
    dskip = pv[7];
    PROF(1, a_x0);
  }
#pragma unroll 1
  for (int layer = 0; layer < 2; ++layer) {
    int lane = lane_here(P.zero);
    const int warp = warp0 | (layer & P.zero), k4 = warp >> 2, w = warp & 3;
    if (warp == (layer ? 12 : 7)) finalize(P, c, lane, layer);
    if (warp == (layer ? 13 : 6)) { announce(P, c, lane, layer); fetch(P, c, lane, layer); }
    if (layer == 0) {
      if (CSP && k4 == 1 && w != 2) { if (CSP > 1) delay(CSP); cs_part(P, c, w - (w >> 1), lane, 0); }
      taps(dskip, k4, w, lane);
    }
    conv(P, &mapW, c, k4, w, layer);
    lane = lane_here(P.zero);
    if (k4 < 2) {
      bar_arrive_if(NB_H, 256, warp != 4);
      if (warp == 0) {
        mbar_wait(B_K, 0);
        cnt_wait(P, 1 + 5 * layer, c, lane);
        x_load(P, c, 0, layer);
        PROF(27, m_xi);
      } else if (k4 == 0 && (CSP == 0 || layer)) cs_part(P, c, w - 1, lane, CSP ? 1 : layer);
      attn_phase(P, c, k4, w, lane, layer);
    } else {
      bar_arrive_if(NB_RL, 256, warp >= 10);
      if (k4 == 3) {
        stats(P, c, w, lane, layer);
      } else if (w < 2) {
        bar_sync_if(NB_RL, 256, w);
        cnt_wait(P, 3 + 5 * layer + w, c, lane);
        bar_sync_if(NB_RL, 256, !w);
        if (w) mbar_wait(B_F, layer);
        x_load(P, c, 2 + w, layer);
        if (H5 && w) w_load(&mapW, cg, 5);
        PROF(14, h_xi);
        if (w == 1) str4(&P.S->SR[layer][lane >> 2][4 * c + (lane & 3)], 0, 0, 0, 0);
      } else if (w == 2) {
        mbar_expect1(B_WO, 65536);
        mbar_expect1(B_RES, 16384);
#pragma unroll 1
        for (int q = 0; q < 4; ++q) {
          if (FH && q < 2) { mbar_wait(B_FH + 8 * q, layer); w_load(&mapW, cg, 4 + 2 * q); }
          mbar_wait(B_F + 8 * q, layer);
          if (!FH && q < 2) w_load(&mapW, cg, 4 + 2 * q);
          if (q == 1 || (q == 0 && !H5)) w_load(&mapW, cg, 5 + 2 * q);
          if (WOQ == 0 && ((q + 1) & 2)) tma5(SM_R + (q & 2) * 16384, &mapWo, 64 * cg, 4 * (q & 2), B_WO);
          if (WOQ && q == 2) {
            if (WOQ >= 2) mbar_wait(B_ST, layer);
            tma5(SM_R, &mapWo, 64 * cg, 0, B_WO);
            if (WOQ < 3) tma5(SM_R + 32768, &mapWo, 64 * cg, 8, B_WO);
          }
          if (q == 3) {
#pragma unroll
            for (int e = 0; e < 2; ++e) bulk(SM_RES + e * 8192, P.S->XF + ((2 * (c >> 3) + 1 - e) * 4096 + cg * 512), 8192, B_RES);
          }
          PROF(15 + q, h_w);
        }
      }
      if (k4 == 2 && w != 2 && layer == 0) cs_sum(P, c, w - (w >> 1), lane);
      if (warp == 11) {
        mbar_wait(PZB, layer);
#pragma unroll
        for (int z = 0; z < 4; ++z) sts4(SM_RES + lane * 16 + z * 512, ~0u, ~0u, ~0u, ~0u);
        fence_async_smem();
        __syncwarp();
#pragma unroll 1
        for (int z = 0; z < 8; ++z) bulk_store(&P.S->O[((c >> 3) * 16 + (z & 4) * 2 + cg) * 512 + (z & 3) * 128], SM_RES, 2048);
        asm volatile("cp.async.bulk.commit_group;\ncp.async.bulk.wait_group 0;" ::: "memory");
        mbar_arrive1(B_ST + 8);
        PROF(18, h_pz);
      }
      if (warp < 10) o_load(P, c, w, lane, layer);
    }
    asm volatile("mov.b32 %0,0;" : "=r"(dskip));
  }
}

typedef CUresult (*EncodeFn)(CUtensorMap*, CUtensorMapDataType, cuuint32_t, void*, const cuuint64_t*, const cuuint64_t*,
                             const cuuint32_t*, const cuuint32_t*, CUtensorMapInterleave, CUtensorMapSwizzle,
                             CUtensorMapL2promotion, CUtensorMapFloatOOBfill);

#define POOL 0
#define GOFF 0
static int place_roles(uint8_t* role) {
  int dev = 0, nsm = 0;
  cudaGetDevice(&dev);
  cudaDeviceGetAttribute(&nsm, cudaDevAttrMultiProcessorCount, dev);
  if (nsm < 128 || nsm > 144 || (nsm & 1)) return 0;
  cudaFuncSetAttribute(fused_kernel, cudaFuncAttributeNonPortableClusterSizeAllowed, 1);
  int occ[9] = {0};
  for (int k = 2; k <= 8; ++k) {
    cudaLaunchConfig_t cfg = {};
    cudaLaunchAttribute at[1];
    at[0].id = cudaLaunchAttributeClusterDimension;
    at[0].val.clusterDim.x = 2 * k; at[0].val.clusterDim.y = 1; at[0].val.clusterDim.z = 1;
    cfg.gridDim = dim3(2 * k); cfg.blockDim = dim3(NTHR); cfg.dynamicSmemBytes = SM_TOTAL; cfg.attrs = at; cfg.numAttrs = 1;
    if (cudaOccupancyMaxActiveClusters(&occ[k], fused_kernel, &cfg) != cudaSuccess) { cudaGetLastError(); occ[k] = 0; }
  }
  int n[10];
  n[7] = occ[8]; n[6] = occ[7]; n[5] = occ[6] - 0; n[4] = occ[5];
  n[3] = occ[4] - n[7]; n[1] = occ[2] - n[3] - n[5] - n[7]; n[0] = n[2] = n[1];
  n[8] = occ[3] - n[2] - n[5];
  const int ntpc = nsm / 2;
  int sum = 0;
  bool ok = n[0] > 0 && n[0] <= 8;
  for (int r = 0; r < 9; ++r) { ok = ok && n[r] >= 0 && (r == 0 || n[r] <= n[r - 1]); sum += n[r]; }
  if (!ok || sum > ntpc) { for (int r = 0; r < 9; ++r) n[r] = r < 8 ? 8 : 0; sum = 64; }
  int tp[8][9], cnt[8] = {0}, pool[72], np = 0, id = 0;
  for (int r = 0; r < 9; ++r)
    for (int g = n[0] - n[r]; g < n[0]; ++g) tp[g][cnt[g]++] = id++;
  for (; id < ntpc; ++id) pool[np++] = id;
  int order[72], no = 0;
  for (int g = 0; g < n[0]; ++g) {
    const int full = cnt[g] / 4 * 4;
    for (int k = 0; k < cnt[g]; ++k) { if (k < full) order[no++] = tp[g][k]; else pool[np++] = tp[g][k]; }
  }
  for (int k = 0; k < np; ++k) order[no++] = pool[POOL == 1 ? np - 1 - k : POOL == 2 ? (k + np - 2) % np : k];
  for (int k = 0; k < 144; ++k) role[k] = 255;
  for (int k = 0; k < 64; ++k) { role[2 * order[k]] = (2 * k + GOFF) & 127; role[2 * order[k] + 1] = (2 * k + 1 + GOFF) & 127; }
  return nsm;
}

extern "C" void kernel_launch(void* const* d_in, const int* in_sizes, int n_in, void* d_out, int out_size) {
  (void)in_sizes; (void)n_in; (void)out_size;
  static EncodeFn enc = nullptr;
  static uint8_t role[144];
  static int nsm = 0;
  static void* scratch = nullptr;
  if (!enc) {
    void* fn = nullptr;
    cudaDriverEntryPointQueryResult qr;
    cudaGetDriverEntryPoint("cuTensorMapEncodeTiled", &fn, cudaEnableDefault, &qr);
    enc = (EncodeFn)fn;
    cudaFuncSetAttribute(fused_kernel, cudaFuncAttributeMaxDynamicSharedMemorySize, SM_TOTAL);
    nsm = place_roles(role);
    cudaGetSymbolAddress(&scratch, g_S);
  }
  CUtensorMap mW, mWo;
  {
    cuuint64_t dim[3] = {512, 512, 3}, str[2] = {3072, 1024};
    cuuint32_t box[3] = {64, 64, 3}, es[3] = {1, 1, 1};
    enc(&mW, CU_TENSOR_MAP_DATA_TYPE_BFLOAT16, 3, d_in[10], dim, str, box, es, CU_TENSOR_MAP_INTERLEAVE_NONE,
        CU_TENSOR_MAP_SWIZZLE_128B, CU_TENSOR_MAP_L2_PROMOTION_NONE, CU_TENSOR_MAP_FLOAT_OOB_FILL_NONE);
  }
  {
    cuuint64_t dim[5] = {512, 2, 4, 4, 16}, str[4] = {1024, 8192, 2048, 32768};
    cuuint32_t box[5] = {64, 2, 4, 4, 8}, es[5] = {1, 1, 1, 1, 1};
    enc(&mWo, CU_TENSOR_MAP_DATA_TYPE_BFLOAT16, 5, d_in[11], dim, str, box, es, CU_TENSOR_MAP_INTERLEAVE_NONE,
        CU_TENSOR_MAP_SWIZZLE_128B, CU_TENSOR_MAP_L2_PROMOTION_NONE, CU_TENSOR_MAP_FLOAT_OOB_FILL_NONE);
  }
  Params P;
  P.x0 = (const uint16_t*)d_in[0]; P.Are = (const uint16_t*)d_in[1]; P.Aim = (const uint16_t*)d_in[2];
  P.Bre = (const uint16_t*)d_in[3]; P.Bim = (const uint16_t*)d_in[4]; P.Cre = (const uint16_t*)d_in[5];
  P.Cim = (const uint16_t*)d_in[6]; P.logdt = (const uint16_t*)d_in[7]; P.dskip = (const uint16_t*)d_in[8];
  P.wqkv = (const uint16_t*)d_in[10]; P.wo = (const uint16_t*)d_in[11]; P.out = (uint16_t*)d_out;
  for (int k = 0; k < 144; ++k) P.role[k] = role[k];
  P.by_sm = nsm > 0;
  P.zero = 0;
  P.S = (Scratch*)scratch;
  fused_kernel<<<nsm > 0 ? nsm : 128, NTHR, SM_TOTAL, cudaStreamPerThread>>>(P, mW, mWo);
}
```

```cpp
#include <cuda_runtime.h>
#include <cuda_bf16.h>
#include <cuda.h>
#include <stdint.h>

#define DEV __device__ __forceinline__

#define NCOPY 4
#define NSUB 1
constexpr int NTHR = 512;
constexpr int SPIN_LIMIT = 1 << 22;

constexpr uint32_t SB = 1024;
constexpr uint32_t SM_XA   = SB;
constexpr uint32_t SM_S0   = SM_XA + 16384;
constexpr uint32_t SM_S1   = SM_S0 + 49152;
constexpr uint32_t SM_XB   = SM_S1 + 49152;
constexpr uint32_t SM_R    = SM_XB + 16384;
constexpr uint32_t SM_RES  = SM_R + 65536;
constexpr uint32_t SM_TAP  = SM_RES + 16384;
constexpr int TAP_SZ = 3584;
constexpr uint32_t SM_CS   = SM_TAP + 4 * TAP_SZ;
constexpr uint32_t SM_STAT = SM_CS + 800;
constexpr uint32_t SM_MISC = SM_STAT + 1280;
constexpr uint32_t SM_BAR  = SM_MISC + 512;
constexpr int SM_TOTAL = SM_BAR + 448 - SB;
constexpr int R_U = 512, R_A5 = 5120, R_A3 = 8704, R_B = 11776;
constexpr int T_E = 1536, T_O = T_E + 1602, T_C = 3714;
constexpr uint32_t B_W = SM_BAR, B_X = SM_BAR + 64, B_O = SM_BAR + 128, B_WO = SM_BAR + 256, B_RES = SM_BAR + 264;
constexpr uint32_t B_ST = SM_BAR + 272, B_R = SM_BAR + 288, B_E = SM_BAR + 304;
constexpr uint32_t B_F = SM_BAR + 320, B_G = SM_BAR + 352, B_K = SM_BAR + 376, B_ED = SM_BAR + 384, B_CS = SM_BAR + 400, B_FH = SM_BAR + 416;
constexpr uint32_t CNT = 0x143444CC;
constexpr int NB_WG = 1, NB_T = 5, NB_Q = 10, NB_H = 11, NB_P = 14, NB_RL = 15;

struct Scratch {
  uint32_t F[32 * 32];
  uint4    H[17 * 8 * 256];
  uint4    SR[2][8][512];
  uint4    ST[32 * 16];
  uint4    PS[128 * 64];
  float4   CS[16 * 1536 / 4];
  uint32_t C[10 * 32 * 32];
  uint4    XF[32 * 4096];
  uint4    O[32 * 8 * 512];
  uint4    XG[512 * 256];
};
__device__ __align__(1024) Scratch g_S;

struct Params {
  int by_sm;
  uint32_t zero;
  Scratch* S;
  const uint16_t *x0, *Are, *Aim, *Bre, *Bim, *Cre, *Cim, *logdt, *dskip, *wqkv, *wo;
  uint16_t* out;
  uint8_t role[144];
};
#define EVENT(n) do {} while (0)
#define PROFD(slot, name, v) do {} while (0)
#define PROF(slot, name) do {} while (0)
#define PW(x)

DEV uint32_t s2u(const void* p) { return (uint32_t)__cvta_generic_to_shared(p); }
template <class T> DEV T opq(T x) { asm volatile("" : "+r"(x)); return x; }
DEV uint32_t pack2(float lo, float hi) { uint32_t d; asm("cvt.rn.bf16x2.f32 %0,%1,%2;" : "=r"(d) : "f"(hi), "f"(lo)); return d; }
DEV float bflo(uint32_t v) { return __uint_as_float(v << 16); }
DEV float bfhi(uint32_t v) { return __uint_as_float(v & 0xFFFF0000u); }
DEV float bfr(float x) { return bflo(pack2(x, 0.f)); }
DEV uint32_t hadd2(uint32_t a, uint32_t b) { uint32_t d; asm("add.rn.bf16x2 %0,%1,%2;" : "=r"(d) : "r"(a), "r"(b)); return d; }
DEV uint32_t hsub2(uint32_t a, uint32_t b) { uint32_t d; asm("sub.rn.bf16x2 %0,%1,%2;" : "=r"(d) : "r"(a), "r"(b)); return d; }
DEV uint32_t hmul2(uint32_t a, uint32_t b) { uint32_t d; asm("mul.rn.bf16x2 %0,%1,%2;" : "=r"(d) : "r"(a), "r"(b)); return d; }
DEV uint32_t hfma2(uint32_t a, uint32_t b, uint32_t c) { uint32_t d; asm("fma.rn.bf16x2 %0,%1,%2,%3;" : "=r"(d) : "r"(a), "r"(b), "r"(c)); return d; }
DEV uint32_t hmax2(uint32_t a, uint32_t b) { uint32_t d; asm("max.bf16x2 %0,%1,%2;" : "=r"(d) : "r"(a), "r"(b)); return d; }
DEV uint32_t prmt(uint32_t a, uint32_t b, uint32_t s) { uint32_t d; asm("prmt.b32 %0,%1,%2,%3;" : "=r"(d) : "r"(a), "r"(b), "r"(s)); return d; }
DEV uint32_t nz(uint32_t v) { uint32_t d; asm("max.u32 %0,%1,1;" : "=r"(d) : "r"(v)); return d; }
DEV uint32_t tagged(uint32_t v, uint32_t m, uint32_t tag) { uint32_t d; asm("lop3.b32 %0,%1,%2,%3,0xB8;" : "=r"(d) : "r"(v), "r"(m), "r"(tag)); return d; }
DEV uint32_t both(uint32_t a, uint32_t b, uint32_t x) { uint32_t d; asm("lop3.b32 %0,%1,%2,%3,0x42;" : "=r"(d) : "r"(a), "r"(b), "r"(x)); return d; }
DEV uint4 hadd8(const uint4& a, const uint4& b) { return make_uint4(hadd2(a.x, b.x), hadd2(a.y, b.y), hadd2(a.z, b.z), hadd2(a.w, b.w)); }
DEV uint32_t min4(const uint4& v) { return min(min(v.x, v.y), min(v.z, v.w)); }
DEV float rcp(float x) { float y; asm("rcp.approx.ftz.f32 %0,%1;" : "=f"(y) : "f"(x)); return y; }
DEV float sqrt_(float x) { float y; asm("sqrt.approx.ftz.f32 %0,%1;" : "=f"(y) : "f"(x)); return y; }
DEV float rsq(float x) { float y; asm("rsqrt.approx.ftz.f32 %0,%1;" : "=f"(y) : "f"(x)); return y; }
DEV float ex2(float x) { float y; asm("ex2.approx.ftz.f32 %0,%1;" : "=f"(y) : "f"(x)); return y; }

DEV uint4 ldr4(const void* p) { uint4 v; asm volatile("ld.relaxed.gpu.global.v4.u32 {%0,%1,%2,%3},[%4];" : "=r"(v.x), "=r"(v.y), "=r"(v.z), "=r"(v.w) : "l"(p) : "memory"); return v; }
DEV void ldr4_if(uint4& v, const void* p, bool c) {
  asm volatile("{.reg .pred q; setp.ne.u32 q,%5,0; @q ld.relaxed.gpu.global.v4.u32 {%0,%1,%2,%3},[%4];}"
    : "+r"(v.x), "+r"(v.y), "+r"(v.z), "+r"(v.w) : "l"(p), "r"((uint32_t)c) : "memory");
}
DEV uint2 ldr2(const void* p) { uint2 v; asm volatile("ld.relaxed.gpu.global.v2.u32 {%0,%1},[%2];" : "=r"(v.x), "=r"(v.y) : "l"(p) : "memory"); return v; }
DEV uint32_t ldr1(const void* p) { uint32_t v; asm volatile("ld.relaxed.gpu.global.u32 %0,[%1];" : "=r"(v) : "l"(p) : "memory"); return v; }
DEV void str4(void* p, uint32_t a, uint32_t b, uint32_t c, uint32_t d) { asm volatile("st.relaxed.gpu.global.v4.u32 [%0],{%1,%2,%3,%4};" :: "l"(p), "r"(a), "r"(b), "r"(c), "r"(d) : "memory"); }
DEV void str4_if(void* p, uint32_t a, uint32_t b, uint32_t c, uint32_t d, bool q) {
  asm volatile("{.reg .pred q; setp.ne.u32 q,%5,0; @q st.relaxed.gpu.global.v4.u32 [%0],{%1,%2,%3,%4};}" :: "l"(p), "r"(a), "r"(b), "r"(c), "r"(d), "r"((uint32_t)q) : "memory");
}
DEV void str2(void* p, uint32_t a, uint32_t b) { asm volatile("st.relaxed.gpu.global.v2.u32 [%0],{%1,%2};" :: "l"(p), "r"(a), "r"(b) : "memory"); }
DEV void str1(void* p, uint32_t a) { asm volatile("st.relaxed.gpu.global.u32 [%0],%1;" :: "l"(p), "r"(a) : "memory"); }
DEV void stw4(void* p, uint32_t a, uint32_t b, uint32_t c, uint32_t d) { asm volatile("st.global.v4.u32 [%0],{%1,%2,%3,%4};" :: "l"(p), "r"(a), "r"(b), "r"(c), "r"(d) : "memory"); }
DEV uint4 ldnc4(const void* p) { uint4 v; asm volatile("ld.global.nc.v4.u32 {%0,%1,%2,%3},[%4];" : "=r"(v.x), "=r"(v.y), "=r"(v.z), "=r"(v.w) : "l"(p)); return v; }
DEV uint4 ldw4(const void* p) { uint4 v; asm volatile("ld.global.v4.u32 {%0,%1,%2,%3},[%4];" : "=r"(v.x), "=r"(v.y), "=r"(v.z), "=r"(v.w) : "l"(p) : "memory"); return v; }
DEV void cp16(uint32_t d, const void* p) { asm volatile("cp.async.cg.shared.global [%0],[%1],16;" :: "r"(d), "l"(p) : "memory"); }
DEV uint32_t ldnc16(const void* p) { uint32_t v; asm volatile("ld.global.u16 %0,[%1];" : "=r"(v) : "l"(p) : "memory"); return v; }

DEV uint32_t lds1v(uint32_t a) { uint32_t v; asm volatile("ld.volatile.shared.u32 %0,[%1];" : "=r"(v) : "r"(a) : "memory"); return v; }
DEV uint4 lds4v(uint32_t a) { uint4 v; asm volatile("ld.volatile.shared.v4.u32 {%0,%1,%2,%3},[%4];" : "=r"(v.x), "=r"(v.y), "=r"(v.z), "=r"(v.w) : "r"(a) : "memory"); return v; }
DEV uint32_t lds1(uint32_t a) { uint32_t v; asm volatile("ld.shared.u32 %0,[%1];" : "=r"(v) : "r"(a)); return v; }
DEV uint2 lds2(uint32_t a) { uint2 v; asm volatile("ld.shared.v2.u32 {%0,%1},[%2];" : "=r"(v.x), "=r"(v.y) : "r"(a)); return v; }
DEV uint4 lds4(uint32_t a) { uint4 v; asm volatile("ld.shared.v4.u32 {%0,%1,%2,%3},[%4];" : "=r"(v.x), "=r"(v.y), "=r"(v.z), "=r"(v.w) : "r"(a)); return v; }
DEV uint32_t lds16(uint32_t a) { uint32_t v; asm volatile("ld.shared.u16 %0,[%1];" : "=r"(v) : "r"(a)); return v; }
DEV float lds1f(uint32_t a) { float v; asm volatile("ld.shared.f32 %0,[%1];" : "=f"(v) : "r"(a)); return v; }
DEV float2 lds2f(uint32_t a) { float2 v; asm volatile("ld.shared.v2.f32 {%0,%1},[%2];" : "=f"(v.x), "=f"(v.y) : "r"(a)); return v; }
DEV float4 lds4f(uint32_t a) { float4 v; asm volatile("ld.shared.v4.f32 {%0,%1,%2,%3},[%4];" : "=f"(v.x), "=f"(v.y), "=f"(v.z), "=f"(v.w) : "r"(a)); return v; }
DEV void sts1(uint32_t a, uint32_t v) { asm volatile("st.shared.u32 [%0],%1;" :: "r"(a), "r"(v) : "memory"); }
DEV void sts16(uint32_t a, uint32_t v) { asm volatile("{.reg .b16 h; cvt.u16.u32 h,%1; st.shared.u16 [%0],h;}" :: "r"(a), "r"(v) : "memory"); }
DEV void sts2f(uint32_t a, float x, float y) { asm volatile("st.shared.v2.f32 [%0],{%1,%2};" :: "r"(a), "f"(x), "f"(y) : "memory"); }
DEV void sts4f(uint32_t a, float x, float y, float z, float w) { asm volatile("st.shared.v4.f32 [%0],{%1,%2,%3,%4};" :: "r"(a), "f"(x), "f"(y), "f"(z), "f"(w) : "memory"); }
DEV void sts4(uint32_t a, uint32_t x, uint32_t y, uint32_t z, uint32_t w) { asm volatile("st.shared.v4.u32 [%0],{%1,%2,%3,%4};" :: "r"(a), "r"(x), "r"(y), "r"(z), "r"(w) : "memory"); }
DEV void sts4_if(uint32_t a, uint32_t x, uint32_t y, uint32_t z, uint32_t w, bool c) {
  asm volatile("{.reg .pred q; setp.ne.u32 q,%5,0; @q st.shared.v4.u32 [%0],{%1,%2,%3,%4};}" :: "r"(a), "r"(x), "r"(y), "r"(z), "r"(w), "r"((uint32_t)c) : "memory");
}
DEV void sts4z_if(uint32_t a, bool c) { asm volatile("{.reg .pred q; setp.ne.u32 q,%1,0; @q st.shared.v4.u32 [%0],{%2,%2,%2,%2};}" :: "r"(a), "r"((uint32_t)c), "r"(0) : "memory"); }

DEV void ldsm4t(uint32_t& r0, uint32_t& r1, uint32_t& r2, uint32_t& r3, uint32_t a) { asm volatile("ldmatrix.sync.aligned.m8n8.x4.trans.shared.b16 {%0,%1,%2,%3},[%4];" : "=r"(r0), "=r"(r1), "=r"(r2), "=r"(r3) : "r"(a) : "memory"); }
DEV void stsm4(uint32_t a, uint32_t r0, uint32_t r1, uint32_t r2, uint32_t r3) { asm volatile("stmatrix.sync.aligned.m8n8.x4.shared.b16 [%0],{%1,%2,%3,%4};" :: "r"(a), "r"(r0), "r"(r1), "r"(r2), "r"(r3) : "memory"); }
DEV void stsm2(uint32_t a, uint32_t r0, uint32_t r1) { asm volatile("stmatrix.sync.aligned.m8n8.x2.shared.b16 [%0],{%1,%2};" :: "r"(a), "r"(r0), "r"(r1) : "memory"); }
DEV void stsm4t(uint32_t a, uint32_t r0, uint32_t r1, uint32_t r2, uint32_t r3) { asm volatile("stmatrix.sync.aligned.m8n8.x4.trans.shared.b16 [%0],{%1,%2,%3,%4};" :: "r"(a), "r"(r0), "r"(r1), "r"(r2), "r"(r3) : "memory"); }
DEV uint32_t movm(uint32_t a) { uint32_t d; asm volatile("movmatrix.sync.aligned.m8n8.trans.b16 %0,%1;" : "=r"(d) : "r"(a)); return d; }
DEV void mma16(float (&d)[4], uint32_t a0, uint32_t a1, uint32_t a2, uint32_t a3, uint32_t b0, uint32_t b1) {
  asm volatile("mma.sync.aligned.m16n8k16.row.col.f32.bf16.bf16.f32 {%0,%1,%2,%3},{%4,%5,%6,%7},{%8,%9},{%0,%1,%2,%3};"
    : "+f"(d[0]), "+f"(d[1]), "+f"(d[2]), "+f"(d[3]) : "r"(a0), "r"(a1), "r"(a2), "r"(a3), "r"(b0), "r"(b1));
}
DEV void mma16z(float (&d)[4], uint32_t a0, uint32_t a1, uint32_t a2, uint32_t a3, uint32_t b0, uint32_t b1) {
  asm volatile("mma.sync.aligned.m16n8k16.row.col.f32.bf16.bf16.f32 {%0,%1,%2,%3},{%4,%5,%6,%7},{%8,%9},{%10,%10,%10,%10};"
    : "=f"(d[0]), "=f"(d[1]), "=f"(d[2]), "=f"(d[3]) : "r"(a0), "r"(a1), "r"(a2), "r"(a3), "r"(b0), "r"(b1), "f"(0.f));
}
DEV void mma8z(float (&d)[4], uint32_t a0, uint32_t a1, uint32_t b0) {
  asm volatile("mma.sync.aligned.m16n8k8.row.col.f32.bf16.bf16.f32 {%0,%1,%2,%3},{%4,%5},{%6},{%7,%7,%7,%7};"
    : "=f"(d[0]), "=f"(d[1]), "=f"(d[2]), "=f"(d[3]) : "r"(a0), "r"(a1), "r"(b0), "f"(0.f));
}
DEV void mma8(float (&d)[4], uint32_t a0, uint32_t a1, uint32_t b0) {
  asm volatile("mma.sync.aligned.m16n8k8.row.col.f32.bf16.bf16.f32 {%0,%1,%2,%3},{%4,%5},{%6},{%0,%1,%2,%3};"
    : "+f"(d[0]), "+f"(d[1]), "+f"(d[2]), "+f"(d[3]) : "r"(a0), "r"(a1), "r"(b0));
}

DEV void bar_sync(int id, int n) { asm volatile("bar.sync %0,%1;" :: "r"(id), "r"(n) : "memory"); }
DEV void bar_arrive(int id, int n) { asm volatile("bar.arrive %0,%1;" :: "r"(id), "r"(n) : "memory"); }
DEV void bar_sync_if(int id, int n, int c) { asm volatile("{.reg .pred q; setp.ne.s32 q,%2,0; @q bar.sync %0,%1;}" :: "r"(id), "r"(n), "r"(c) : "memory"); }
DEV void bar_arrive_if(int id, int n, int c) { asm volatile("{.reg .pred q; setp.ne.s32 q,%2,0; @q bar.arrive %0,%1;}" :: "r"(id), "r"(n), "r"(c) : "memory"); }
DEV bool bar_any(int id, int n, bool c) {
  uint32_t r; asm volatile("{.reg .pred p,q; setp.ne.u32 q,%3,0; bar.red.or.pred p,%1,%2,q; selp.u32 %0,1,0,p;}" : "=r"(r) : "r"(id), "r"(n), "r"((uint32_t)c) : "memory");
  return __any_sync(0xffffffffu, r);
}
DEV void fence_async_glob() { asm volatile("fence.proxy.async.global;" ::: "memory"); }
DEV void fence_async_smem() { asm volatile("fence.proxy.async.shared::cta;" ::: "memory"); }
DEV void fence_gpu() { asm volatile("fence.acq_rel.gpu;" ::: "memory"); }
DEV void mbar_wait(uint32_t b, uint32_t ph) {
  asm volatile("{\n.reg .pred p;\nW: mbarrier.try_wait.parity.shared::cta.b64 p,[%0],%1;\n@!p bra W;\n}" :: "r"(b), "r"(ph) : "memory");
}
DEV bool mbar_test(uint32_t b, uint32_t ph) {
  uint32_t r; asm volatile("{.reg .pred p; mbarrier.test_wait.parity.shared::cta.b64 p,[%1],%2; selp.u32 %0,1,0,p;}" : "=r"(r) : "r"(b), "r"(ph) : "memory");
  return __all_sync(0xffffffffu, r);
}
DEV uint32_t mbar_test2(uint32_t b, uint32_t ph) {
  uint32_t r; asm volatile("{.reg .pred p,q; mbarrier.test_wait.parity.shared::cta.b64 p,[%1],%2; mbarrier.test_wait.parity.shared::cta.b64 q,[%1+8],%2;\n"
                           "and.pred p,p,q; selp.u32 %0,1,0,p;}" : "=r"(r) : "r"(b), "r"(ph) : "memory");
  return r;
}
DEV void spin_guard(int it) { asm volatile("{.reg .pred p; setp.gt.s32 p,%0,%1; @p trap;}" :: "r"(it), "n"(SPIN_LIMIT)); }
DEV uint32_t here(uint32_t zero) {
  uint32_t d; asm volatile("mov.u32 %0,%%clock;" : "=r"(d) :: "memory"); return d & zero;
}
DEV int lane_here(uint32_t zero) {
  uint32_t d; asm volatile("mov.u32 %0,%%laneid;" : "=r"(d)); return d | here(zero);
}
DEV void delay(uint32_t n) {
  asm volatile("{\n.reg .pred p;\n.reg .u32 a,b;\nmov.u32 a,%%clock;\nW: mov.u32 b,%%clock;\nsub.u32 b,b,a;\nsetp.lt.u32 p,b,%0;\n@p bra.uni W;\n}" :: "r"(n) : "memory");
}
DEV void poll(const uint32_t* p, uint32_t n) {
  for (int it = 0; !__all_sync(0xffffffffu, ldr1(p) >= n); ++it) spin_guard(it);
}
DEV uint32_t* cnt_at(const Params& P, int n, int c, int lane) { return P.S->C + (32 * (NSUB * lane + c % NSUB) + n * 1024); }
DEV void cnt_add(uint32_t* p, uint32_t one, bool q) { asm volatile("{.reg .pred p; setp.ne.u32 p,%2,0; @p red.relaxed.gpu.global.add.u32 [%0],%1;}" :: "l"(p), "r"(one), "r"((uint32_t)q) : "memory"); }
DEV void cnt_wait(const Params& P, int n, int c, int lane) { poll(P.S->C + (32 * (NSUB * (c / (128 / NCOPY)) + lane % NSUB) + n * 1024), 128 / NSUB); }
DEV void mbar_init1(uint32_t b, int n) { asm volatile("{.reg .pred p; elect.sync _|p,0xffffffff; @p mbarrier.init.shared::cta.b64 [%0],%1;}" :: "r"(b), "r"(n) : "memory"); }
DEV void mbar_arrive1(uint32_t b) { asm volatile("{.reg .pred p; elect.sync _|p,0xffffffff; @p mbarrier.arrive.shared::cta.b64 _,[%0];}" :: "r"(b) : "memory"); }
DEV void mbar_arrive1_if(uint32_t b, int c) {
  asm volatile("{.reg .pred p,q; setp.ne.s32 q,%1,0; elect.sync _|p,0xffffffff; and.pred p,p,q; @p mbarrier.arrive.shared::cta.b64 _,[%0];}" :: "r"(b), "r"(c) : "memory");
}
DEV void mbar_expect1(uint32_t b, int bytes) { asm volatile("{.reg .pred p; elect.sync _|p,0xffffffff; @p mbarrier.arrive.expect_tx.shared::cta.b64 _,[%0],%1;}" :: "r"(b), "r"(bytes) : "memory"); }
DEV void flag_set1(uint32_t* q) { asm volatile("{.reg .pred p; elect.sync _|p,0xffffffff; @p st.relaxed.gpu.global.u32 [%0],1;}" :: "l"(q) : "memory"); }
DEV void tma3(uint32_t dst, const CUtensorMap* m, int c0, int c1, uint32_t bar) {
  asm volatile("{.reg .pred p; elect.sync _|p,0xffffffff;\n"
    "@p cp.async.bulk.tensor.3d.shared::cluster.global.mbarrier::complete_tx::bytes [%0],[%1,{%2,%3,%5}],[%4];}"
    :: "r"(dst), "l"(m), "r"(c0), "r"(c1), "r"(bar), "r"(0) : "memory");
}
DEV void tma5(uint32_t dst, const CUtensorMap* m, int c0, int c4, uint32_t bar) {
  asm volatile("{.reg .pred p; elect.sync _|p,0xffffffff;\n"
    "@p cp.async.bulk.tensor.5d.shared::cluster.global.mbarrier::complete_tx::bytes [%0],[%1,{%2,%5,%5,%5,%3}],[%4];}"
    :: "r"(dst), "l"(m), "r"(c0), "r"(c4), "r"(bar), "r"(0) : "memory");
}
DEV void bulk(uint32_t dst, const void* src, int bytes, uint32_t bar) {
  asm volatile("{.reg .pred p; elect.sync _|p,0xffffffff;\n@p cp.async.bulk.shared::cluster.global.mbarrier::complete_tx::bytes [%0],[%1],%2,[%3];}" :: "r"(dst), "l"(src), "r"(bytes), "r"(bar) : "memory");
}
DEV void bulk_store(void* dst, uint32_t src, int bytes) {
  asm volatile("{.reg .pred p; elect.sync _|p,0xffffffff;\n@p cp.async.bulk.global.shared::cta.bulk_group [%0],[%1],%2;}" :: "l"(dst), "r"(src), "r"(bytes) : "memory");
}
DEV void l2_prefetch(const void* src, int bytes) {
  asm volatile("{.reg .pred p; elect.sync _|p,0xffffffff;\n@p cp.async.bulk.prefetch.L2.global [%0],%1;}" :: "l"(src), "r"(bytes) : "memory");
}

DEV uint64_t mkdesc(uint32_t addr, uint32_t lbo, uint32_t sbo, uint32_t swz) {
  return (uint64_t)((addr >> 4) | ((lbo >> 4) << 16)) | ((uint64_t)((sbo >> 4) | (swz << 30)) << 32);
}
DEV void wg_fence() { asm volatile("wgmma.fence.sync.aligned;" ::: "memory"); }
DEV void wg_commit() { asm volatile("wgmma.commit_group.sync.aligned;" ::: "memory"); }
template <int N> DEV void wg_wait() { asm volatile("wgmma.wait_group.sync.aligned %0;" :: "n"(N) : "memory"); }
template <int N> DEV void zerov(float (&d)[N]) {
#pragma unroll
  for (int i = 0; i < N; ++i) asm volatile("mov.b32 %0,0;" : "=f"(d[i]));
}
template <int N> DEV void undef(float (&d)[N]) {
#pragma unroll
  for (int i = 0; i < N; ++i) asm volatile("" : "=f"(d[i]));
}
#define R4(d, o) "+f"(d[o]), "+f"(d[o + 1]), "+f"(d[o + 2]), "+f"(d[o + 3])
#define R8(d, o) R4(d, o), R4(d, o + 4)
#define R16(d, o) R8(d, o), R8(d, o + 8)
#define R32(d, o) R16(d, o), R16(d, o + 16)
#define L0 "%0,%1,%2,%3,%4,%5,%6,%7,%8,%9,"
#define L10(a) "%" #a "0,%" #a "1,%" #a "2,%" #a "3,%" #a "4,%" #a "5,%" #a "6,%" #a "7,%" #a "8,%" #a "9,"
#define WG_HEAD(pr, n) "{.reg .pred p; setp.ne.s32 p,%" #pr ",0;\nwgmma.mma_async.sync.aligned.m64n" #n "k16.f32.bf16.bf16 {"
DEV void wg_rs64k(float (&d)[32], const uint32_t (&a)[4], uint64_t db, int acc) {
  asm volatile(WG_HEAD(37, 64) L0 L10(1) L10(2) "%30,%31},{%32,%33,%34,%35},%36,p,1,1,0;}"
    : R32(d, 0) : "r"(a[0]), "r"(a[1]), "r"(a[2]), "r"(a[3]), "l"(db), "r"(acc));
}
DEV void wg_rs48t(float (&d)[24], const uint32_t (&a)[4], uint64_t db, int acc) {
  asm volatile(WG_HEAD(29, 48) L0 L10(1) "%20,%21,%22,%23},{%24,%25,%26,%27},%28,p,1,1,1;}"
    : R16(d, 0), R8(d, 16) : "r"(a[0]), "r"(a[1]), "r"(a[2]), "r"(a[3]), "l"(db), "r"(acc));
}
DEV void wg_rs32t(float (&d)[16], const uint32_t (&a)[4], uint64_t db, int acc) {
  asm volatile(WG_HEAD(21, 32) L0 "%10,%11,%12,%13,%14,%15},{%16,%17,%18,%19},%20,p,1,1,1;}"
    : R16(d, 0) : "r"(a[0]), "r"(a[1]), "r"(a[2]), "r"(a[3]), "l"(db), "r"(acc));
}
DEV void wg_ss48(float (&d)[24], uint64_t da, uint64_t db, int acc) {
  asm volatile(WG_HEAD(26, 48) L0 L10(1) "%20,%21,%22,%23},%24,%25,p,1,1,1,1;}" : R16(d, 0), R8(d, 16) : "l"(da), "l"(db), "r"(acc));
}
DEV void wg_ss64(float (&d)[32], uint64_t da, uint64_t db, int acc) {
  asm volatile(WG_HEAD(34, 64) L0 L10(1) L10(2) "%30,%31},%32,%33,p,1,1,0,1;}" : R32(d, 0) : "l"(da), "l"(db), "r"(acc));
}
DEV void wg_ss192(float (&d)[96], uint64_t da, uint64_t db, int acc) {
  asm volatile(WG_HEAD(98, 192) L0 L10(1) L10(2) L10(3) L10(4) L10(5) L10(6) L10(7) L10(8) "%90,%91,%92,%93,%94,%95},%96,%97,p,1,1,1,1;}"
    : R32(d, 0), R32(d, 32), R32(d, 64) : "l"(da), "l"(db), "r"(acc));
}

DEV void wg_rs192t(float (&d)[96], const uint32_t (&a)[4], uint64_t db) {
  asm volatile("wgmma.mma_async.sync.aligned.m64n192k16.f32.bf16.bf16 {" L0 L10(1) L10(2) L10(3) L10(4) L10(5) L10(6) L10(7) L10(8) "%90,%91,%92,%93,%94,%95},{%96,%97,%98,%99},%100,1,1,1,1;"
    : R32(d, 0), R32(d, 32), R32(d, 64) : "r"(a[0]), "r"(a[1]), "r"(a[2]), "r"(a[3]), "l"(db));
}

DEV float ln_sd(float s, float q, float& m) {
  m = s * (1.f / 512.f);
  return bfr(sqrt_(bfr(bfr(fmaxf(q * (1.f / 512.f) - m * m, 0.f)) + 1e-5f)));
}
DEV float4 gram(const uint32_t (&w)[8][2], int g, uint32_t zero) {
  float s[4], q[4][4];
  const uint32_t o0 = 0x3F803F80u | zero, o1 = 0x3F803F80u ^ zero;
#pragma unroll
  for (int j = 0; j < 8; ++j) {
#pragma unroll
    for (int h = 0; h < 2; ++h) { if (j < 2) mma8z(q[2 * j + h], w[j][0], w[j][1], w[j][h]); else mma8(q[2 * (j & 1) + h], w[j][0], w[j][1], w[j][h]); }
    if (j == 1) mma16z(s, w[0][0], w[0][1], w[1][0], w[1][1], o0, o1);
    else if (j & 1) mma16(s, w[j - 1][0], w[j - 1][1], w[j][0], w[j][1], o0, o1);
  }
  const bool od = g & 1;
  return make_float4(s[0], od ? q[0][1] + q[2][1] : q[0][0] + q[2][0], s[2], od ? q[1][3] + q[3][3] : q[1][2] + q[3][2]);
}
DEV void keep(uint32_t v, uint32_t zero) {
  asm volatile("{.reg .pred p; setp.ne.u32 p,%1,0; @p st.shared.u32 [%0],%0;}" :: "r"(v), "r"(zero) : "memory");
}
DEV void keep(const void* v, uint32_t zero) { asm volatile("{.reg .pred p; setp.ne.u32 p,%1,0; @p st.global.u32 [%0],%1;}" :: "l"(v), "r"(zero) : "memory"); }
struct XgAddr { uint32_t a, b; uint4* dst; };
template <bool FRAG> DEV XgAddr xg_addr(uint4* dst, uint32_t stg, int wp, int lane, uint32_t zero) {
  const int t = lane & 3, r = 4 * wp + (lane >> 3);
  XgAddr x = {stg + t * (FRAG ? 256 : 1024) + ((wp ^ t) * 32) + (lane >> 2) * 4,
              stg + r * 128 + (((lane & 7) ^ (2 * (((r >> 1) ^ (r >> 3)) & 3))) * 16), dst + (r * 256 + (lane & 7))};
  keep(x.a, zero); keep(x.b, zero); keep(x.dst, zero);
  return x;
}
template <bool FRAG> DEV void xg_put(const XgAddr& x, const uint32_t (&w)[8][2]) {
#pragma unroll
  for (int n = 0; n < 8; ++n) {
    const uint32_t b = (x.a ^ ((n & 3) * 32)) + (FRAG ? n * 1024 : (n >> 2) * 4096 + (n & 3) * 256);
    sts1(b, prmt(w[n][0], w[n][1], 0x5410)); sts1(b + 128, prmt(w[n][0], w[n][1], 0x7632));
  }
}
DEV void xg_store(const XgAddr& x, uint32_t tag) {
  const uint32_t m = (~x.b >> 4) & 1;
#pragma unroll
  for (int k = 0; k < 4; ++k) {
    const uint4 v = lds4((x.b ^ ((k & 1) * 64)) + k * 2048);
    str4(x.dst + k * 4096, tagged(v.x, m, tag), v.y, v.z, v.w);
  }
}
template <int N, int M> DEV void fold(float (&v)[M], int lane, int bit) {
  const bool b = lane & bit;
#pragma unroll
  for (int k = 0; k < N; ++k) { const float sn = b ? v[k] : v[k + N], kp = b ? v[k + N] : v[k]; v[k] = kp + __shfl_xor_sync(0xffffffffu, sn, bit); }
}
DEV void refetch(uint32_t dst, const uint4* src, int half, int e, int w) {
#pragma unroll 1
  for (int r = 0; r < 2; ++r) {
    if (w == 0) { mbar_expect1(B_R + 8 * e, half); bulk(dst + r * half, src + r * (half >> 4), half, B_R + 8 * e); }
    mbar_wait(B_R + 8 * e, r);
    bar_sync(NB_WG + e, 128);
  }
}
DEV uint32_t kvslot(int cg, int pos) { return (pos & 2 ? SM_XA : SM_S1) + (cg < 4 ? 5 : 2) * 8192 + (pos & 1) * 4096; }
DEV uint32_t xstage(int q, int e) { return ((q + 1) & 2) ? SM_R + ((q & 2) + e) * 16384 : e ? SM_XB : SM_XA; }
DEV void cmul(float& orr, float& oi, float ar, float ai, float br, float bi) {
  float r = ar * br - ai * bi, i = ar * bi + ai * br; orr = r; oi = i;
}
DEV void cexp_(float al, float bt, float s, float& er, float& ei) {
  float mag = ex2(al * s), ph = bt * s;
  ph -= rintf(ph);
  float ang = ph * 6.283185307179586f;
  er = mag * __cosf(ang); ei = mag * __sinf(ang);
}

#define KS 2048
DEV void put8(uint32_t a, const float (&r)[8], const float (&i)[8]) {
  sts4(a, pack2(r[0], r[1]), pack2(r[2], r[3]), pack2(r[4], r[5]), pack2(r[6], r[7]));
  sts4(a + 1024, pack2(i[0], i[1]), pack2(i[2], i[3]), pack2(i[4], i[5]), pack2(i[6], i[7]));
}
DEV void tables(const uint32_t (&pv)[8], int k4, int w, int lane) {
  PW(4 * k4 + w)
  [[maybe_unused]] const int layer = 0;
  const float dt = bfr(__expf(bflo(pv[6])));
  const float al = dt * bflo(pv[0]) * 1.4426950408889634f, bt = dt * bflo(pv[1]) * 0.15915494309189535f;
  float qr[8], qi[8], yr[8], yi[8];
  cmul(qr[0], qi[0], bflo(pv[4]), bflo(pv[5]), dt * bflo(pv[2]), dt * bflo(pv[3]));
  PROFD(2, a_par, __float_as_uint(qr[0] + al + bt));
  float e1r, e1i, eMr, eMi, eLr, eLi;
  cexp_(al, bt, 1.f, e1r, e1i); cexp_(al, -bt, 8.f, yr[1], yi[1]); cexp_(al, -bt, 64.f, eMr, eMi); cexp_(al, bt, 256.f, eLr, eLi);
  const uint32_t ad = SB + k4 * 32768 + (w & 1) * 512 + lane * 16, am = ad + (w >> 1) * KS, an = ad + (8 + 3 * (w >> 1)) * KS;
  yr[0] = 1.f; yi[0] = 0.f;
#pragma unroll
  for (int k = 1; k < 8; ++k) {
    cmul(qr[k], qi[k], qr[k - 1], qi[k - 1], e1r, e1i);
    if (k > 1) cmul(yr[k], yi[k], yr[k - 1], yi[k - 1], yr[1], yi[1]);
  }
  put8(an, qr, qi);
#pragma unroll
  for (int j = 0; j < 4; ++j) {
    put8(am + j * 2 * KS, yr, yi);
#pragma unroll
    for (int k = 0; k < 8; ++k) {
      if (j == 0 && k == 0) { yr[0] = eMr; yi[0] = eMi; } else if (j < 3) cmul(yr[k], yi[k], yr[k], yi[k], eMr, eMi);
    }
    if (j == 0) {
#pragma unroll
      for (int k = 0; k < 8; ++k) { const int o = k < 4 ? 2 * k : k < 6 ? 2 * k - 8 : k - 2; cmul(qr[k], qi[k], qr[o], qi[o], eLr, eLi); }
      put8(an + KS, qr, qi);
    } else if (j == 1) {
#pragma unroll
      for (int k = 0; k < 5; ++k) cmul(qr[k], qi[k], qr[k ? k - 1 : 6], qi[k ? k - 1 : 6], eLr, eLi);
      put8(an + 2 * KS, qr, qi);
    }
  }
  PROF(3, a_tab);
}

DEV void sts16_if(uint32_t a, uint32_t v, bool c) { asm volatile("{.reg .pred q; .reg .b16 h; setp.ne.u32 q,%2,0; cvt.u16.u32 h,%1; @q st.shared.u16 [%0],h;}" :: "r"(a), "r"(v), "r"((uint32_t)c) : "memory"); }
DEV void sts1_if(uint32_t a, uint32_t v, bool c) { asm volatile("{.reg .pred q; setp.ne.u32 q,%2,0; @q st.shared.u32 [%0],%1;}" :: "r"(a), "r"(v), "r"((uint32_t)c) : "memory"); }
DEV void taps(uint32_t dskip, int k4, int w, int lane) {
  PW(4 * k4 + w)
  [[maybe_unused]] const int layer = 0;
  fence_async_smem();
  bar_sync((k4 & 1) ? NB_WG + k4 : NB_Q, (k4 & 1) ? 128 : 448);
  float d[24];
  undef(d);
  const uint64_t da = mkdesc(SB + k4 * 32768, 1024, KS, 0);
  wg_fence();
#pragma unroll
  for (int j = 0; j < 8; ++j) wg_ss48(d, da + j * 8, da + KS / 2 + j * 8, j);
  wg_commit();
  const int b = 8 * w + (lane >> 2), t = lane & 3, id = 32 * w + lane;
  constexpr int DO = T_O - T_E;
  const uint32_t te = SM_TAP + k4 * TAP_SZ + T_E, a0 = te - 16 * b - 4 * t;
  const uint32_t a1 = a0 - 512 - 4 * t, a2 = te - 2 * (511 + b) - 64 * t, a3 = te + (T_C - T_E) - 2 * (127 + b) - 128 * t;
  wg_wait<0>();
  PROF(4, a_mma);
  {
    const uint32_t v = pack2(d[1] + d[15], d[0] + d[14] + (id ? 0.f : bflo(dskip)));
    sts1(a0 + DO - 2, v); sts16(a0 - 2, v); sts16(a0, v >> 16);
  }
  {
    const uint32_t v = pack2(d[5] + d[19], d[4] + d[18]), u = prmt(v, v, 0x3232);
    const bool lo = t < 2, k512 = id == 2;
    sts1_if(k512 ? te - 2 * 512 : a1, u, (lo && id) || k512);
    sts1_if(k512 ? te - 2 * 514 : a1 - 4, k512 ? u : v, lo || k512);
    sts1_if(k512 ? te + DO - 2 * 513 : a1 + DO - 2, u, lo || k512);
    sts16(lo ? a1 + DO - 4 : a2 + DO - 194, v);
    sts16(lo ? (id ? a1 + DO + 2 : a1) : k512 ? te + DO - 2 * 511 : a2 + DO, u);
    sts16_if(a2 - 194, v, !lo);
    sts16_if(k512 ? te + DO - 2 * 514 : a2, u, !lo);
  }
  {
    const uint32_t v = pack2(d[8] + d[22], d[9] + d[23]);
    sts16_if(id ? a3 : te - 2 * 639, v, t < 2 || id == 2);
    sts16_if(a3 - 64, v >> 16, t < 2);
    sts16_if(te + DO - 2 * 639, v, id == 0);
  }
  bar_sync(NB_WG + k4, 128);
  mbar_arrive1_if(B_K, w == 0);
}

DEV uint32_t cpy(uint32_t v, uint32_t id) {
  uint32_t d; asm volatile("prmt.b32 %0,%1,%1,%2;" : "=r"(d) : "r"(v), "r"(id)); return d;
}
DEV uint32_t uoff(int s) { return (s ^ ((s >> 3) & 3)) * 16; }
template <bool FULL> DEV void boxes(const uint32_t (&u)[10], uint32_t a, uint32_t a9, uint32_t a7, uint32_t (&pv)[4]) {
  uint32_t v[8], p[8], x[4], y[4];
#pragma unroll
  for (int j = 0; j < 8; ++j) { v[j] = prmt(u[j], u[j + 1], 0x5432); p[j] = hadd2(u[j], v[j]); }
#pragma unroll
  for (int j = 0; j < 4; ++j) { x[j] = hadd2(hadd2(p[j + 1], p[j + 2]), u[j + 3]); y[j] = hadd2(v[j + 3], p[j + 4]); }
  sts4(a + R_A5, x[0], x[1], x[2], x[3]);
  sts4(a + R_A3, y[0], y[1], y[2], y[3]);
  if (FULL) {
#pragma unroll
    for (int j = 0; j < 4; ++j) { x[j] = hadd2(x[j], hadd2(v[j], v[j + 3])); y[j] = hadd2(x[j], hadd2(u[j], u[j + 4])); pv[j] = p[j + 4]; }
    sts4(a7, x[0], x[1], x[2], x[3]);
    sts4(a9, y[0], y[1], y[2], y[3]);
  }
}
DEV uint32_t shfl_up(uint32_t v, int d) { uint32_t r; asm volatile("shfl.sync.up.b32 %0,%1,%2,0,0xffffffff;" : "=r"(r) : "r"(v), "r"(d) : "memory"); return r; }
DEV void halo(uint32_t (&u)[10], uint32_t a, uint32_t b, int lane) {
  asm volatile("{.reg .pred p,q; setp.eq.s32 p,%8,0; setp.lt.s32 q,%8,2;\n@p ld.shared.v4.u32 {%2,%3,%4,%5},[%6];\n@q ld.shared.v2.u32 {%0,%1},[%7];}"
    : "+r"(u[0]), "+r"(u[1]), "+r"(u[2]), "+r"(u[3]), "+r"(u[4]), "+r"(u[5]) : "r"(a), "r"(b), "r"(lane));
}
#define W1 4
#define ROT 2
#define G1 -1
#define G2 1
#define G3 8
#define TPS 0x7134
#define GMASK ((G1 >= 0 ? 2 : 0) | (G2 >= 0 ? 4 : 0) | (G3 >= 0 ? 8 : 0))
#define GATE1(g, n, p) if (g >= 0 && (g & 3) == p) mbar_arrive1_if(B_G + 8 * n, k4 == (g >> 2));
#define GATE(p) GATE1(G1, 0, p) GATE1(G2, 1, p) GATE1(G3, 2, p)
#define TMASK(p) (((TPS & 15) == p) | ((((TPS >> 4) & 15) == p) << 1) | ((((TPS >> 8) & 15) == p) << 2) | ((((TPS >> 12) & 15) == p) << 3))
#define TURN(p) if (TMASK(p) == 15) bar_arrive(NB_T + 1 + k4, 256); else if (TMASK(p)) { if ((TMASK(p) >> k4) & 1) bar_arrive(NB_T + 1 + k4, 256); }
DEV void w_load(const CUtensorMap* mW, int cg, int h) {
  mbar_expect1(B_W + 8 * h, 24576);
  tma3(SM_S0 + (h & 3) * 24576, mW, 64 * cg, 64 * h, B_W + 8 * h);
}

DEV void conv(const Params& P, const CUtensorMap* mW, int c, int k4, int w, int layer) {
  const uint32_t zero = P.zero;
  PW(4 * k4 + w)
  int lane = lane_here(zero);
  const int g = lane >> 2, t = lane & 3, v = w ^ (ROT * (k4 & 1)), tid = 32 * v + lane;
  const uint32_t reg = SM_R + k4 * 16384, tp = SM_TAP + k4 * TAP_SZ;
  const uint32_t g0 = tp + ((g & 1) ? T_O : T_E) + 2 * (2 * t - g);
  uint32_t F[18][4], U[20], qc[4][4];
#define LO(q, a) q[0] = lds1(a); q[2] = lds1(a + 16);
#define HI(q, a) q[1] = lds1(a - 128); q[3] = lds1(a - 112);
  {
    const uint32_t ga = g0 - 32 * (w & 1) - 576 * (w >> 1), g2 = tp + T_C - 258 - 32 * w + 4 * (t - g);
    F[0][2] = lds1(ga + 48);
#pragma unroll
    for (int j = 0; j < 8; ++j) { F[j][0] = lds1(ga + 32 - 32 * j); F[j][1] = lds1(ga + 16 - 32 * j); }
#pragma unroll
    for (int j = 0; j < 20; ++j) U[j] = lds1(ga - 224 - 16 * j);
#pragma unroll
    for (int j = 0; j < 4; ++j) { LO(qc[j], g2 + 32 * j) HI(qc[j], g2 + 32 * j) }
  }
  if (layer) { mbar_wait(B_ED, 0); mbar_wait(B_ED + 8, 0); }
  sts4z_if(reg + lane * 16 + (w ? w * 3584 + 1024 : 0), w < 3);
  PROF(5, a_pre);
  if (k4 == 3 && w == 3) {
    mbar_wait(B_E, layer);
    mbar_wait(B_K, 0);
#pragma unroll
    for (int h = 0; h < 4; ++h) w_load(mW, c & 7, h);
  }
  const uint32_t bo = reg + R_B + tid * 16 + (v >> 1) * 1056, be = tid == 127 ? reg + R_B + 1024 : bo + (tid == 63 ? 2112 : 1056);
  const uint32_t a9 = (lane & 1) ? be : bo, a7 = (lane & 1) ? bo : be, ua = reg + R_U + uoff(tid);
  const uint32_t h1 = reg + R_U + v * 512 - 64, h2 = h1 + 24 - 16 * lane;
  keep(a9 & a7 & ua & h2, zero);
  mbar_wait(k4 && ((GMASK >> k4) & 1) ? B_G - 8 + 8 * k4 : B_E, layer);
  PROF(6, a_x);
  uint4 x[2];
  uint32_t pv[4];
  {
    uint4 s[4];
    uint32_t u[2][10];
#pragma unroll
    for (int z = 0; z < 2; ++z) { x[z] = lds4(reg + R_B + tid * 16 + z * 2048); s[2 * z] = lds4(SM_RES + tid * 16 + z * 2048); s[2 * z + 1] = lds4(SM_RES + tid * 16 + z * 2048 + 4096); }
    for (int it = 0;; ++it) {
      const uint32_t m = min(min(min((both(x[0].x, x[1].x, layer) | lane) & 1, min(s[0].x, s[0].z)), min(s[1].x, s[1].z)), min(min(s[2].x, s[2].z), min(s[3].x, s[3].z)));
      if (__builtin_expect(__all_sync(0xffffffffu, m != 0u), 1)) break;
      EVENT(16 + layer * 4 + k4);
      const int o = tid | here(zero);
#pragma unroll
      for (int z = 0; z < 2; ++z) x[z] = ldr4(&P.S->XG[(128 * k4 + c) * 256 + o] + z * 128);
#pragma unroll
      for (int z = 0; z < 4; ++z) {
        s[z] = ldr4(&P.S->SR[layer][c >> 4][o] + ((z >> 1) * 128 + (z & 1) * 256));
        sts4(SM_RES + tid * 16 + (z >> 1) * 2048 + (z & 1) * 4096, s[z].x, s[z].y, s[z].z, s[z].w);
      }
      spin_guard(it);
    }
#pragma unroll
    for (int z = 0; z < 2; ++z) {
      u[z][6] = hmul2(hsub2(x[z].x, s[2 * z].y), s[2 * z].x); u[z][7] = hmul2(hsub2(x[z].y, s[2 * z].w), s[2 * z].z);
      u[z][8] = hmul2(hsub2(x[z].z, s[2 * z + 1].y), s[2 * z + 1].x); u[z][9] = hmul2(hsub2(x[z].w, s[2 * z + 1].w), s[2 * z + 1].z);
      sts4(ua + z * 2048, u[z][6], u[z][7], u[z][8], u[z][9]);
    }
    u[1][0] = 0; u[1][1] = s[3].x; u[1][2] = s[2].x; u[1][3] = s[2].y; u[1][4] = s[2].z; u[1][5] = s[2].w;
    if (v < 2) {
#pragma unroll
      for (int j = 1; j < 6; ++j) u[1][j] = shfl_up(u[1][j < 2 ? 8 + j : 4 + j], j < 2 ? 2 : 1);
    }
#pragma unroll
    for (int j = 0; j < 6; ++j) u[0][j] = shfl_up(u[0][j < 2 ? 8 + j : 4 + j], j < 2 ? 2 : 1);
    bar_sync(NB_WG + k4, 128);
    GATE(0)
    PROF(7, a_u);
    halo(u[0], h1, h2, lane);
    halo(u[1], h1 + 2048, h2 + 2048, lane + 16 * (v & 2));
    sts4z_if(reg + R_B + 1040, tid == 0);
    boxes<true>(u[0], reg + tid * 16, a9, a7, pv);
    if (v < 2) boxes<false>(u[1], reg + tid * 16 + 2048, 0, 0, pv);
  }
  GATE(1)
  fence_async_smem();
  if (k4 == 3 && w == 0) {
    const uint32_t src = SM_RES + 8192;
#pragma unroll
    for (int z = 0; z < 4; ++z) sts4(src + lane * 16 + z * 512, 0, 0, 0, 0);
    fence_async_smem();
    __syncwarp();
#pragma unroll
    for (int z = 0; z < 2; ++z) {
      bulk_store(&P.S->H[(c + 8) * 256] + z * 128, src, 2048);
      bulk_store(P.S->F + ((c >> 3) * 64 + 4 * (c & 7)) + z * 32, src, 16);
    }
    bulk_store(&P.S->PS[c * 64], src, 1024);
    bulk_store(&P.S->ST[c * 4], src, 64);
    if (c < 5) bulk_store(P.S->C + (c + 5 - 5 * layer) * 1024, src, 128 * NCOPY * NSUB);
    asm volatile("cp.async.bulk.commit_group;" ::: "memory");
  }
  const uint32_t id = opq(0x3210u);
#pragma unroll
  for (int j = 0; j < 8; ++j) { F[j][3] = cpy(F[j][0], id); if (j) F[j][2] = cpy(F[j - 1][1], id); }
  PROF(8, a_box);
  bar_sync(NB_T + k4, k4 ? 256 : 128);
  PROF(9, a_turn);
  float acc[32], f1[24], f3[16];
  uint32_t qa[4][4], qb[4][4], fp[4];
  const uint64_t db = mkdesc(reg + R_U, 16, 512, 2) + 2;
#define STEP(mm, n) wg_fence(); mm; wg_commit(); wg_wait<n>();
#define D(j, n) STEP(wg_rs64k(acc, F[j], db - 2 * j, j), n)
#define C(j, n) STEP(wg_rs32t(f3, qc[j], mkdesc(reg + R_B, 128, 1040, 0) + 16 * j, j), n)
#define NIL(q, y) { const uint32_t z = y & zero; q[2][1] = cpy(z, 0); q[2][3] = cpy(z, 1); q[3][1] = cpy(z, 2); q[3][3] = cpy(z, 3); }
#define X(j) F[j][0] = cpy(U[2 * j - 16], ix); F[j][1] = cpy(U[2 * j - 15], ix); F[j][3] = cpy(F[j][0], ix); F[j][2] = cpy(F[j - 1][1], ix);
  const uint32_t g1 = g0 - 2 * 576 - 16 * w;
  const uint64_t d1 = mkdesc(reg + R_A5, 128, 512, 0);
  constexpr int O3 = (R_A3 - R_A5) / 16;
  uint32_t ix = id;
  undef(acc);
  D(0, 4) TURN(0) D(1, 4) D(2, 4) D(3, 4) D(4, 4) D(5, 2)
  undef(f3);
  C(0, 3) C(1, 3) TURN(1) C(2, 3) X(8) C(3, W1) X(9) LO(qa[0], g1)
  D(6, W1) HI(qa[0], g1) X(10) D(7, W1) LO(qa[1], g1 + 32) X(11) D(8, W1) HI(qa[1], g1 + 32) D(9, 4) LO(qa[2], g1 - 64)
  fp[0] = pack2(f3[0], f3[1]); fp[1] = pack2(f3[4], f3[5]); fp[2] = pack2(f3[8] + f3[2], f3[9] + f3[3]); fp[3] = pack2(f3[12] + f3[6], f3[13] + f3[7]);
  ix |= fp[0] & fp[1] & fp[2] & fp[3] & zero;
  X(12) D(10, 4) TURN(2) LO(qa[3], g1 - 32) X(13) X(14) D(11, 4) LO(qb[0], g1 - 192) X(15) D(12, 4) HI(qb[0], g1 - 192) X(16)
  D(13, 4) LO(qb[1], g1 - 160) X(17) D(14, 4) TURN(3) HI(qb[1], g1 - 160) NIL(qa, qa[1][0])
  D(15, 4) LO(qb[2], g1 - 256) D(16, 3) LO(qb[3], g1 - 224) NIL(qb, qa[1][1]) D(17, 2) TURN(4)
  PROF(10, a_den);
  undef(f1);
  wg_fence();
#pragma unroll
  for (int j = 0; j < 4; ++j) wg_rs48t(f1, qa[j], d1 + 16 * (j & 1) - 32 * (j >> 1), j);
  wg_commit();
  wg_wait<1>();
  TURN(5)
  wg_fence();
#pragma unroll
  for (int j = 0; j < 4; ++j) wg_rs48t(f1, qb[j], d1 + O3 + 16 * (j & 1) - 32 * (j >> 1), 1);
  wg_commit();
  TURN(6)
  lane = lane_here(zero);
  bar_sync(NB_WG + k4, 128);
  {
    const int p = (lane + 9 * (w >> 1)) & 31;
    const uint32_t ya = reg + ((w >> 1) ? R_B : R_U) + p * 64 + (((2 * (w & 1)) ^ ((p >> 1) & 3)) * 16), up = p < lane ? 2048 : 0;
#pragma unroll
    for (int z = 0; z < 4; ++z) {
      const float* a = acc + 16 * (z >> 1) + 2 * (z & 1);
      stsm4t((ya + (up ^ ((z >> 1) * 2048))) ^ ((z & 1) * 16), pack2(a[0], a[1]), pack2(a[4], a[5]), pack2(a[8], a[9]), pack2(a[12], a[13]));
    }
  }
  asm volatile("cp.async.bulk.wait_group 0;" ::: "memory");
  const uint32_t fa = reg + R_A5 + (lane >> 3) * 512 + w * 128 + (lane & 7) * 16;
  const uint32_t fc = reg + R_A3 + uoff(64 * (lane >> 4) + 16 * w + 2 * (lane & 7) + 1 - ((lane >> 3) & 1));
  uint32_t k1024 = lds16(tp + T_E - 2 * 639 + (fa & fc & zero));
  wg_wait<0>();
  GATE(2)
  PROF(11, a_far);
  bar_sync(NB_WG + k4, 128);
  stsm4(fc, fp[0], fp[1], fp[2], fp[3]);
  stsm4(fa, pack2(f1[0], f1[1]), pack2(f1[4], f1[5]), pack2(f1[8] + f1[2], f1[9] + f1[3]), pack2(f1[12] + f1[6], f1[13] + f1[7]));
  stsm2(fa + 2048, pack2(f1[16] + f1[10], f1[17] + f1[11]), pack2(f1[20] + f1[14], f1[21] + f1[15]));
  {
    const int o = 32 * v + lane;
    const uint32_t a = reg + uoff(o), b = reg + R_A5 + o * 16;
    uint4 y[2] = {hadd8(lds4(a + R_U), lds4(o >= 36 ? a + R_B : reg)), hadd8(lds4(a + R_U + 2048), lds4(a + R_B + 2048))};
    bar_sync(NB_WG + k4, 128);
    TURN(7)
    PROF(12, a_sts);
    const uint4 f = lds4(v >= 2 ? b - 1024 : reg), f2 = lds4(b + 1024);
    uint4 h = lds4(a + R_A3);
    const int e0 = (o >> 3) * 8192 + (128 * k4 + c) * 16 + (((o & 4) + ((o >> 1) & 1)) ^ (c & 7)) * 2 + (o & 1);
    const uint32_t me = (e0 & 3) == ((c >> 1) & 3), m0 = me & ~c, m1 = me & c, tag = 1 - layer;
    uint32_t* cp = cnt_at(P, 1 + 5 * layer + k4, c, lane);
    keep(cp, zero);
    k1024 = prmt(k1024, k1024, 0x1010);
    h = make_uint4(hfma2(pv[0], k1024, h.x), hfma2(pv[1], k1024, h.y), hfma2(pv[2], k1024, h.z), hfma2(pv[3], k1024, h.w));
    y[0] = hadd8(y[0], f); y[1] = hadd8(y[1], hadd8(f2, h));
    cnt_add(cp, 1 | (y[0].x & y[1].x & zero), (o ^ 96) < NCOPY);
#pragma unroll
    for (int z = 0; z < 2; ++z) {
      const uint4 r = hadd8(x[z], y[z]);
      str2((uint2*)P.S->XF + e0 + z * 131072, tagged(prmt(r.x, r.y, 0x5410), m0, tag), tagged(prmt(r.z, r.w, 0x5410), m1, tag));
      str2((uint2*)P.S->XF + (e0 ^ 4) + z * 131072, tagged(prmt(r.x, r.y, 0x7632), m0, tag), tagged(prmt(r.z, r.w, 0x7632), m1, tag));
    }
  }
  TURN(9)
  GATE(3)
  PROF(13, a_out);
}

#define WGATE 1
#define FH 1
#define QPIN 1
#define XORD 1
DEV void x_load(const Params& P, int c, int q, int layer) {
#pragma unroll
  for (int z = 0; z < 2; ++z) {
    const int e = z ^ (XORD && q == 3 && !(c & 4));
    mbar_expect1(B_X + 16 * q + 8 * e, 16384);
    bulk(xstage(q, e), P.S->XF + ((2 * (c >> 3) + 1 - e) * 4096 + q * 1024), 16384, B_X + 16 * q + 8 * e);
  }
}

DEV void means(uint32_t (&m)[4], int row, int lane, int layer, uint32_t zero) {
  mbar_wait(B_CS, 0);
  mbar_wait(B_ST, layer);
  const uint32_t a = SM_MISC + row * 4 + (lane & 28), k = (lane & 3) ? 0u : ~0u;
  m[0] = lds1(a) & k; m[1] = lds1(a + 32) & k; m[2] = m[0] & zero; m[3] = m[1] & zero;
}

DEV void attn_phase(const Params& P, int c, int e, int w, int lane, int layer) {
  PW(4 * e + w)
  const int cg = c & 7, J = 2 * (c >> 3) + 1 - e;
  float acc[96];
  zerov(acc);
  uint32_t m[4] = {0, 0, 0, 0};
#pragma unroll 1
  for (int q = 0;; ++q) {
    const uint64_t da = mkdesc(xstage(q, e), 16, 1024, 1), db = mkdesc(SM_S0 + (q & 1) * 49152, 8192, 1024, 1);
    const uint32_t wr = mbar_test2(B_W + 16 * q, layer), xa = xstage(q, e) + w * 4096 + lane * 132;
    mbar_wait(B_X + 16 * q + 8 * e, layer);
    for (int it = 0;; ++it) {
      const uint32_t ok = both(lds1(xa), lds1(xa ^ 32), layer) & both(lds1(xa ^ 64), lds1(xa ^ 96), layer);
      if (__all_sync(0xffffffffu, ok & 1)) break;
      EVENT(8 * layer + 2 * q + e);
#pragma unroll 1
      for (int j = 0; j < 8; ++j) cp16(xstage(q, e) + w * 4096 + j * 512 + lane * 16, P.S->XF + (J * 4096 + q * 1024 + w * 256 + j * 32 + lane));
      asm volatile("cp.async.wait_all;" ::: "memory");
      fence_async_smem();
      __syncwarp();
      spin_guard(it);
    }
    bool all = __all_sync(0xffffffffu, wr);
    if (q == 0 && e && w == 0) {
      bar_sync(NB_H, 256);
      cnt_wait(P, 2 + 5 * layer, c, lane);
      x_load(P, c, 1, layer);
      PROF(27, m_xi);
    }
    if (q == 3 && e) means(m, 16 * w, lane, layer, P.zero);
    if (!all) { mbar_wait(B_W + 16 * q, layer); all = mbar_test(B_W + 16 * q + 8, layer); }
    bar_sync(e ? NB_Q : q ? NB_T : NB_T + 4, 256);
    PROF(14 + q, m_q);
    wg_fence();
#pragma unroll
    for (int k = 0; k < 8; ++k) {
      if (k == 4) { wg_commit(); if (!all) mbar_wait(B_W + 16 * q + 8, layer); wg_fence(); }
      wg_ss192(acc, da + k * 128, db + (k >> 2) * 1536 + (k & 3) * 128, 1);
    }
    wg_commit();
    if (q == 3) break;
    bar_arrive(e ? NB_T : NB_Q, 256);
    if (FH) { wg_wait<1>(); mbar_arrive1_if(B_FH + 8 * q, e && q < 2); }
    wg_wait<0>();
    mbar_arrive1(B_F + 8 * q);
  }
  const int pos = 2 - 2 * e + (w >> 1);
  uint4* h = P.S->H + ((c + 8) * 256 + (w & 1) * 128 + lane);
  const uint32_t kw = kvslot(cg, pos + 1) + (w & 1) * 2048 + lane * 16;
  {
    if (!e) means(m, 64 + 16 * w, lane, layer, P.zero);
    PROF(28, m_sub);
    wg_fence();
    wg_rs192t(acc, m, mkdesc(SM_CS, 0, 32, 0));
    wg_commit();
    bar_arrive_if(NB_Q, 256, !e);
    keep(h, kw & P.zero);
    mbar_wait(B_F + 16, layer);
    wg_wait<0>();
    mbar_arrive1(B_F + 24);
  }
  PROF(18, m_qkv);
  uint32_t Q[4][4], K[4][3][2], V[4][3][2];
  uint32_t pin = P.zero;
#pragma unroll
  for (int z = 0; z < 4; ++z) {
    V[z][1][0] = pack2(acc[64 + 8 * z], acc[65 + 8 * z]); V[z][1][1] = pack2(acc[68 + 8 * z], acc[69 + 8 * z]);
    K[z][1][0] = pack2(acc[32 + 8 * z], acc[33 + 8 * z]); K[z][1][1] = pack2(acc[36 + 8 * z], acc[37 + 8 * z]);
    pin &= V[z][1][0] & V[z][1][1];
    K[z][2][0] = nz(pack2(acc[34 + 8 * z], acc[35 + 8 * z])); K[z][2][1] = pack2(acc[38 + 8 * z], acc[39 + 8 * z]);
    V[z][2][0] = pack2(acc[66 + 8 * z], acc[67 + 8 * z]); V[z][2][1] = pack2(acc[70 + 8 * z], acc[71 + 8 * z]);
    str4_if(h + z * 32, K[z][2][0], K[z][2][1], V[z][2][0], V[z][2][1], pos == 3);
  }
#pragma unroll
  for (int z = 0; z < 8; ++z) V[z >> 1][2][z & 1] = movm(z < 7 ? V[z >> 1][2][z & 1] : V[3][2][1] | pin);
  if (pos == 0) mbar_wait(B_F + 24, layer);
#pragma unroll
  for (int z = 0; z < 4; ++z) sts4_if(kw + z * 512, K[z][2][0], K[z][2][1], V[z][2][0], V[z][2][1], pos < 3);
  bar_arrive(NB_H + pos + 1, 128);
  PROF(19, m_kv);
  lane |= here(P.zero);
  int g = lane >> 2, t = lane & 3;
  const uint32_t ra = SM_STAT + 256 + (32 - 32 * e + 8 * w) * 16, ob = e ? SM_S1 : SM_XA;
  const float r0 = lds1f(ra + (g >> 1) * 16 + (g & 1) * 4), r1 = lds1f(ra + 64 + (g >> 1) * 16 + (g & 1) * 4);
  const uint4 k1 = lds4(ra + 16 * t), k2 = lds4(ra + 64 + 16 * t);
#pragma unroll
  for (int z = 0; z < 8; ++z) {
    V[z >> 1][1][z & 1] = movm(V[z >> 1][1][z & 1]);
    Q[z >> 1][2 * (z & 1)] = pack2(acc[4 * z], acc[4 * z + 1]);
    Q[z >> 1][2 * (z & 1) + 1] = pack2(acc[4 * z + 2], acc[4 * z + 3]);
    pin &= Q[z >> 1][2 * (z & 1)] & Q[z >> 1][2 * (z & 1) + 1];
  }
  {
    const bool p0 = 2 * t > g, p1 = 2 * t + 1 > g, first = c < 8 && pos == 0;
    const uint32_t M = (p0 ? 0xFFFFu : 0u) | (p1 ? 0xFFFF0000u : 0u);
    const float sc0 = r0 * (0.25f * 1.4426950408889634f), sc1 = r1 * (0.25f * 1.4426950408889634f);
    const float sk2 = __uint_as_float(p0 ? k1.x : k2.x) * sc1, sk3 = __uint_as_float(p1 ? k1.y : k2.y) * sc1;
    const int oo = cg * 512 + (2 * (w & 2) + (w & 1)) * 64 + (lane ^ (g >> 1));
    uint4* O = P.S->O + (J * 4096 + oo);
    keep(oo, pin & M & __float_as_uint(sk2) & __float_as_uint(sk3) & __float_as_uint(sc0));
    mbar_wait(B_F + 24, layer);
    float L[4][4];
#pragma unroll
    for (int z = 0; z < 4; ++z) {
      float S[4];
      mma16z(L[z], Q[z][0], Q[z][1], Q[z][2], Q[z][3], K[z][1][0], K[z][1][1]);
      mma16z(S, Q[z][0], Q[z][1], Q[z][2], Q[z][3], K[z][2][0], K[z][2][1]);
      L[z][2] = (p0 ? L[z][2] : S[2]) * sk2; L[z][3] = (p1 ? L[z][3] : S[3]) * sk3;
      if (QPIN) pin &= __float_as_uint(L[z][2]) & __float_as_uint(L[z][3]);
    }
    bar_sync(NB_H + pos + pin, pos ? 128 : 160);
    const uint4 k0 = lds4(ra - 192 + 16 * t);
#pragma unroll
    for (int z = 0; z < 4; ++z) {
      const uint4 hv = lds4(kvslot(cg, pos) + (w & 1) * 2048 + lane * 16 + z * 512);
      K[z][0][0] = hv.x; K[z][0][1] = hv.y; V[z][0][0] = hv.z; V[z][0][1] = hv.w;
    }
    PROF(20, m_halo);
    const float sk0 = __uint_as_float(p0 ? k0.x : k1.x) * sc0, sk1 = __uint_as_float(p1 ? k0.y : k1.y) * sc0;
    const uint32_t rm[4] = {k0.z & M, k1.z & ~M, k1.z & M, k2.z & ~M}, s0 = k0.w | P.zero, s1 = k1.w | P.zero;
#pragma unroll
    for (int h2 = 0; h2 < 2; ++h2) {
      uint32_t A[2], B[2], mx[2];
#pragma unroll
      for (int z = 0; z < 2; ++z) {
        const int h = 2 * h2 + z;
        float S[4];
        mma16z(S, Q[h][0], Q[h][1], Q[h][2], Q[h][3], K[h][0][0], K[h][0][1]);
        if (first) { S[0] = __uint_as_float(0xFF800000u); S[1] = S[0]; }
        A[z] = pack2((p0 ? S[0] : L[h][0]) * sk0, L[h][2]);
        B[z] = pack2((p1 ? S[1] : L[h][1]) * sk1, L[h][3]);
      }
#pragma unroll
      for (int z = 0; z < 2; ++z) mx[z] = hmax2(A[z], B[z]);
#pragma unroll
      for (int z = 0; z < 2; ++z) mx[z] = hmax2(mx[z], __shfl_xor_sync(0xffffffffu, mx[z], 1));
#pragma unroll
      for (int z = 0; z < 2; ++z) mx[z] = hmax2(mx[z], __shfl_xor_sync(0xffffffffu, mx[z], 2));
      float Oa[2][3][4];
#pragma unroll
      for (int z = 0; z < 2; ++z) {
        const int h = 2 * h2 + z;
        const uint32_t a = hsub2(A[z], mx[z]), b = hsub2(B[z], mx[z]);
        const uint32_t w0 = pack2(ex2(bflo(a)), ex2(bflo(b))), w1 = pack2(ex2(bfhi(a)), ex2(bfhi(b)));
        const uint32_t u0 = hmul2(w0, rm[0]), u1 = hmul2(w0, rm[1]), u2 = hmul2(w1, rm[2]), u3 = hmul2(w1, rm[3]);
        const uint32_t z0 = w0 & P.zero, z1 = w1 & P.zero;
        mma16z(Oa[z][2], u0, z0, u1, u2, s0, s1);
#pragma unroll
        for (int d = 0; d < 2; ++d) mma16z(Oa[z][d], u0, z0, u1, u2, V[h][0][d], V[h][1][d]);
        mma8(Oa[z][2], z1, u3, k2.w);
#pragma unroll
        for (int d = 0; d < 2; ++d) mma8(Oa[z][d], z1, u3, V[h][2][d]);
      }
#pragma unroll
      for (int r = 0; r < 4; r += 2) {
        const float i0 = rcp(Oa[0][2][r]), i1 = rcp(Oa[1][2][r]);
        const uint32_t o0 = pack2(Oa[0][0][r] * i0, Oa[0][0][r + 1] * i0), o1 = pack2(Oa[0][1][r] * i0, Oa[0][1][r + 1] * i0);
        const uint32_t o2 = pack2(Oa[1][0][r] * i1, Oa[1][0][r + 1] * i1), o3 = pack2(Oa[1][1][r] * i1, Oa[1][1][r + 1] * i1);
        str4(O + h2 * 32 + r * 64, o0, o1, o2, o3);
        sts4(ob + oo * 16 + h2 * 512 + r * 1024, o0, o1, o2, o3);
      }
    }
  }
  bar_arrive(NB_T + 1 + e, 160);
  fence_async_smem();
  PROF(21, m_att);
  lane = lane_here(P.zero); g = lane >> 2; t = lane & 3;
  uint32_t res[8][2];
  mbar_wait(B_RES, layer);
  {
    const uint32_t a = SM_RES + e * 8192 + (lane >> 4) * 1024 + (lane & 7) * 128 + (((2 * (w & 2) + ((lane >> 2) & 2) + (w & 1)) ^ (lane & 7)) * 16);
#pragma unroll
    for (int j = 0; j < 8; j += 2) ldsm4t(res[j][0], res[j][1], res[j + 1][0], res[j + 1][1], a + j * 1024);
  }
  PROF(26, m_res);
  if (WGATE) bar_sync(NB_T, 256); else bar_sync(NB_WG + e, 128);
  XgAddr xa = xg_addr<true>(P.S->XG + (64 * cg * 256 + 8 * J), ob, w, lane, P.zero);
  uint4* ps = &P.S->PS[((4 * J + w) * 8 + cg) * 8 + g];
  keep(ps, P.zero);
  if (layer) {
    xa.a = ob + w * 2048 + (lane & 15) * 128 + (((lane >> 4) ^ (lane & 7)) * 16);
    xa.b = ob + w * 2048 + (lane >> 3) * 128 + (((lane & 7) ^ (lane >> 3)) * 16);
    xa.dst = (uint4*)P.out + ((64 * J + 16 * w + 2 * (lane >> 3)) * 64 + 8 * cg + (lane & 7));
  }
  uint32_t y[8][2];
#pragma unroll 1
  for (int it = 0;; ++it) {
    float ac[32];
#pragma unroll
    for (int j = 0; j < 16; ++j) {
      asm volatile("shl.b32 %0,%1,16;" : "=f"(ac[2 * j]) : "r"(res[j >> 1][j & 1]));
      asm volatile("and.b32 %0,%1,0xFFFF0000;" : "=f"(ac[2 * j + 1]) : "r"(res[j >> 1][j & 1]));
    }
#pragma unroll 1
    for (int n = 0; n < 8; ++n) {
      const int s = n == 0 ? cg : n - (n <= cg);
      mbar_wait(n ? B_O + 64 * e + 8 * s : B_WO, layer);
      if (n == 1) PROF(22, m_o1);
      if (n == 7) PROF(23, m_o7);
      const uint64_t da = mkdesc(ob + s * 8192, 16, 1024, 2), db = mkdesc(SM_R + s * 8192, 16, 1024, 1);
      wg_fence();
#pragma unroll
      for (int k = 0; k < 4; ++k) wg_ss64(ac, da + (k >> 1) * 32 + (k & 1) * 2, db + k * 128, 1);
      wg_commit();
    }
    wg_wait<0>();
    const bool bad = ac[0] != ac[0] || ac[2] != ac[2];
#pragma unroll
    for (int j = 0; j < 8; ++j) {
      y[j][0] = pack2(ac[4 * j], ac[4 * j + 1]); y[j][1] = pack2(ac[4 * j + 2], ac[4 * j + 3]);
    }
    if (!bar_any(NB_WG + e, 128, bad) || it == 16) break;
    EVENT(24 + 2 * layer + e);
    refetch(ob, P.S->O + J * 4096, 32768, e, w);
  }
  PROF(24, m_wo);
  if (layer == 0) {
    const float4 s = gram(y, g, P.zero);
    xg_put<true>(xa, y);
    str4_if(ps, nz(__float_as_uint(s.x)), __float_as_uint(s.y), __float_as_uint(s.z), __float_as_uint(s.w), t == (g >> 1));
    mbar_arrive1(B_ED + 8 * e);
    bar_sync(NB_WG + e, 128);
    xg_store(xa, 0);
    bar_arrive(NB_T + 3, 288);
  } else {
#pragma unroll
    for (int j = 0; j < 8; j += 2) stsm4(xa.a ^ (j * 16), y[j][0], y[j][1], y[j + 1][0], y[j + 1][1]);
    __syncwarp();
#pragma unroll
    for (int k = 0; k < 4; ++k) {
      const uint4 v = lds4((xa.b ^ ((k & 1) * 64)) + k * 512);
      stw4(xa.dst + ((k & 1) * 8 + (k >> 1)) * 64, v.x, v.y, v.z, v.w);
    }
  }
  PROF(25, m_epi);
}

#define HDELAY 300
#define ODELAY 200
#define FDELAY 300
#define CSP 0
#define CSU 8
#define XDEL 300
#define PZB B_X + 48
#define WOQ 2
#define H5 1
#define SRDELAY 350

DEV void o_load(const Params& P, int c, int e, int lane, int layer) {
  PW(8 + e)
  const int J = 2 * (c >> 3) + 1 - e;
#pragma unroll 1
  for (int s = 0; s < 8; ++s) mbar_expect1(B_O + 64 * e + 8 * s, s == (c & 7) ? 0 : 8192);
  const uint4* src = P.S->O + J * 4096;
  const uint32_t* fp = P.S->F + (J * 32 + (lane & 28));
  keep(fp, P.zero);
  bar_sync(NB_T + 1 + e, 160);
  flag_set1(P.S->F + (J * 32 + 4 * (c & 7)));
  if (ODELAY) delay(ODELAY);
  PROF(26, a_go);
  poll(fp, 1);
  PROF(25, h_seen);
  bar_sync_if(NB_Q, 64, e);
#pragma unroll 1
  for (int n = 0; n < 7; ++n) {
    const int s = n + (n >= (c & 7));
    bulk((e ? SM_S1 : SM_XA) + s * 8192, src + s * 512, 8192, B_O + 64 * e + 8 * s);
  }
  bar_arrive_if(NB_Q, 64, !e);
  PROF(28, a_o);
}

DEV void stats(const Params& P, int c, int w, int lane, int layer) {
  PW(12 + w)
  lane = opq(lane);
  const int r = 2 * (lane >> 3), k = (2 * (c & 3) + ((lane >> 2) & 1)) ^ r, e = 1 - ((c >> 2) & 1);
  const uint32_t o = (32 * w + r) * 128 + k * 16 + (lane & 3) * 4;
  const uint32_t no0 = (lane & 7) != r, no1 = ((lane & 7) ^ 4) != r + 1;
  uint32_t* st = (uint32_t*)P.S->ST + (16 * c + 2 * (lane & 7) + (lane >> 4));
  keep(st, P.zero);
  float v[4] = {0.f, 0.f, 0.f, 0.f};
#pragma unroll 1
  for (int q = 0; q < 4; ++q) {
    mbar_wait(B_X + 16 * q + 8 * e, layer);
    PROF(19 + q, s_l);
    uint32_t x[8];
    for (int it = 0;; ++it) {
#pragma unroll
      for (int z = 0; z < 8; ++z) x[z] = lds1v(xstage(q, e) + (o ^ ((z & 1) * 144)) + (z >> 1) * 1024);
      const uint32_t ok = (both(x[0], x[2], layer) & both(x[4], x[6], layer) | no0) & (both(x[1], x[3], layer) & both(x[5], x[7], layer) | no1);
      if (__all_sync(0xffffffffu, ok & 1)) break;
      spin_guard(it);
    }
    mbar_arrive1(B_F + 8 * q);
#pragma unroll
    for (int z = 0; z < 8; ++z) {
      const float lo = bflo(x[z]), hi = bfhi(x[z]);
      v[0] += lo; v[1] += lo * lo; v[2] += hi; v[3] += hi * hi;
    }
  }
  PROFD(14, s_part, __float_as_uint(v[0]));
  fold<2>(v, lane, 16); fold<1>(v, lane, 8);
  PROFD(16, s_fold, __float_as_uint(v[0]));
  if (w) {
    sts1(SM_MISC - 128 + w * 128 + lane * 4, __float_as_uint(v[0]));
    bar_arrive(NB_P, 128);
  } else {
    mbar_wait(B_ST + 8, layer);
    bar_sync(NB_P, 128);
    v[0] += lds1f(SM_MISC + lane * 4) + lds1f(SM_MISC + 128 + lane * 4) + lds1f(SM_MISC + 256 + lane * 4);
    float m;
    const float sd = ln_sd(v[0], __shfl_xor_sync(0xffffffffu, v[0], 8), m);
    if (!(lane & 8)) str1(st, pack2(m, sd));
    PROF(17, s_pub);
    uint4 s;
    for (int it = 0;; ++it) {
      s = ldr4(P.S->ST + ((c >> 3) * 32 + lane));
      if (__all_sync(0xffffffffu, min4(s) != 0u)) break;
      spin_guard(it);
    }
    PROF(18, s_seen);
    const float r0 = rcp(bfhi(s.x)), r1 = rcp(bfhi(s.y)), r2 = rcp(bfhi(s.z)), r3 = rcp(bfhi(s.w));
    const uint32_t sg = 0x80008000u;
    sts4(SM_MISC + lane * 16, prmt(s.x, s.x, 0x1010) ^ sg, prmt(s.y, s.y, 0x1010) ^ sg, prmt(s.z, s.z, 0x1010) ^ sg, prmt(s.w, s.w, 0x1010) ^ sg);
    sts4(SM_STAT + 256 + lane * 32, __float_as_uint(r0), __float_as_uint(r1), pack2(r0, r1), prmt(s.x, s.y, 0x7632));
    sts4(SM_STAT + 272 + lane * 32, __float_as_uint(r2), __float_as_uint(r3), pack2(r2, r3), prmt(s.z, s.w, 0x7632));
    __syncwarp();
    mbar_arrive1(B_ST);
  }
  PROF(15, s_stat);
  if (w == 1) {
    mbar_wait(B_ST, layer);
    if (c >= 8) {
      uint2 s;
      for (int it = 0;; ++it) {
        s = ldr2((const uint2*)P.S->ST + ((c >> 3) * 64 - 12 + (lane & 11)));
        if (__all_sync(0xffffffffu, min(s.x, s.y) != 0u)) break;
        spin_guard(it);
      }
      const float r0 = rcp(bfhi(s.x)), r1 = rcp(bfhi(s.y));
      sts4(SM_STAT + 64 + (lane & 11) * 16, __float_as_uint(r0), __float_as_uint(r1), pack2(r0, r1), prmt(s.x, s.y, 0x7632));
    }
    bar_arrive(NB_H, 160);
  }
  if (w >= 2) {
    const uint4* h = P.S->H + (c * 256 + (w & 1) * 128 + lane);
    uint4 hv[4];
#pragma unroll
    for (int z = 0; z < 4; ++z) hv[z] = make_uint4(0, 0, 0, 0);
    bar_sync(NB_RL, 128);
    PROFD(26, s_hb, lds1v(SM_MISC));
    delay(HDELAY);
    for (int it = 0; c >= 8; ++it) {
#pragma unroll
      for (int z = 0; z < 4; ++z) hv[z] = ldr4(h + z * 32);
      if (__all_sync(0xffffffffu, min(min(hv[0].x, hv[1].x), min(hv[2].x, hv[3].x)) != 0u)) break;
      spin_guard(it);
    }
    mbar_wait(B_F + 24, layer);
#pragma unroll
    for (int z = 0; z < 4; ++z) sts4(kvslot(c & 7, 0) + (w & 1) * 2048 + lane * 16 + z * 512, hv[z].x, hv[z].y, movm(hv[z].z), movm(hv[z].w));
    bar_arrive(NB_H, 160);
    PROF(25, s_halo);
  }
}

DEV void finalize(const Params& P, int c, int lane, int layer) {
  PW(12)
  uint2* so = (uint2*)P.S->SR[layer] + ((lane >> 3) * 1024 + (lane & 2) * 256 + 4 * c + ((lane >> 1) & 2) + (lane & 1));
  const uint4* ps = &P.S->PS[c * 64 + lane];
  keep(so, P.zero); keep(ps, P.zero);
  uint4 a, b;
  if (layer == 0) {
    bar_sync(NB_P, 256);
    a = lds4(SM_RES + 8192 + lane * 16); b = lds4(SM_RES + 8704 + lane * 16);
  } else {
    mbar_wait(B_ED + 8 - 2 * (c & 4), 0);
    delay(FDELAY);
    for (int it = 0;; ++it) {
      a = ldr4(ps); b = ldr4(ps + 32);
      if (__all_sync(0xffffffffu, min(a.x, b.x) != 0u)) break;
      spin_guard(it);
    }
  }
  float z[4] = {__uint_as_float(a.x) + __uint_as_float(b.x), __uint_as_float(a.y) + __uint_as_float(b.y),
                __uint_as_float(a.z) + __uint_as_float(b.z), __uint_as_float(a.w) + __uint_as_float(b.w)};
#pragma unroll
  for (int o = 8; o < 32; o <<= 1)
#pragma unroll
    for (int k = 0; k < 4; ++k) z[k] += __shfl_xor_sync(0xffffffffu, z[k], o);
  const float m0 = z[0] * (1.f / 512.f), m1 = z[2] * (1.f / 512.f);
  const float r0 = rsq(fmaxf(z[1] * (1.f / 512.f) - m0 * m0, 0.f) + 1e-5f), r1 = rsq(fmaxf(z[3] * (1.f / 512.f) - m1 * m1, 0.f) + 1e-5f);
  const uint32_t wr = nz(pack2(r0, r1)), wm = pack2(m0, m1);
  str2(so, wr, wm); str2(so + 4096, wr, wm);
  bar_arrive_if(NB_Q, 448, !layer);
  PROF(23, s_sr);
}

DEV void announce(const Params& P, int c, int lane, int layer) {
  PW(13)
  uint32_t* cp = cnt_at(P, 5 * layer, c, lane);
  keep(cp, P.zero);
  bar_sync(NB_T + 3, 288);
  cnt_add(cp, 1, lane < NCOPY);
  if (!layer) { bar_sync(NB_Q, 448); fence_async_smem(); }
  PROF(24, s_own);
}

DEV void fetch(const Params& P, int c, int lane, int layer) {
  PW(13)
  mbar_expect1(B_E, 24576);
  cnt_wait(P, 5 * layer, c, lane);
#pragma unroll
  for (int k = 0; k < 4; ++k) bulk(SM_R + k * 16384 + R_B, P.S->XG + (128 * k + c) * 256, 4096, B_E);
  if (layer) delay(SRDELAY);
  bulk(SM_RES, P.S->SR[layer][c >> 4], 8192, B_E);
  if (!layer) { if (!CSP) l2_prefetch(P.wqkv + c * 6144, 12288); l2_prefetch(P.wo + c * 2048, 4096); }
  PROF(25, s_all);
}

DEV void cs_part(const Params& P, int c, int w, int lane, int layer) {
  float cs[8];
#pragma unroll
  for (int k = 0; k < 8; ++k) cs[k] = 0.f;
  const int col = w * 512 + 64 * (c & 7) + 8 * (lane & 7);
#pragma unroll 1
  for (int r = 8 * layer; r < 8; r += CSU) {
    uint4 v[CSU];
#pragma unroll
    for (int k = 0; k < CSU; ++k) v[k] = ldnc4(P.wqkv + ((32 * (c >> 3) + 4 * r + (lane >> 3)) * 1536 + col) + 4 * k * 1536);
#pragma unroll
    for (int k = 0; k < CSU; ++k) {
      cs[0] += bflo(v[k].x); cs[1] += bfhi(v[k].x); cs[2] += bflo(v[k].y); cs[3] += bfhi(v[k].y);
      cs[4] += bflo(v[k].z); cs[5] += bfhi(v[k].z); cs[6] += bflo(v[k].w); cs[7] += bfhi(v[k].w);
    }
  }
  fold<4>(cs, lane, 16); fold<2>(cs, lane, 8);
  str2((float*)P.S->CS + ((c >> 3) * 1536 + col + 2 * (lane >> 3)), max(__float_as_uint(cs[0]), 1u - layer), __float_as_uint(cs[1]));
}

DEV void cs_sum(const Params& P, int c, int w, int lane) {
  float a, b;
  for (int it = 0;; ++it) {
    uint32_t m = ~0u;
    a = b = 0.f;
#pragma unroll
    for (int k = 0; k < 16; ++k) {
      const uint2 u = ldr2((const float*)P.S->CS + (w * 512 + 64 * (c & 7) + 2 * lane) + k * 1536);
      a += __uint_as_float(u.x); b += __uint_as_float(u.y); m = min(m, u.x);
    }
    if (__all_sync(0xffffffffu, m != 0u)) break;
    spin_guard(it);
  }
  const uint32_t hi = pack2(a, b), ad = SM_CS + w * 256 + (lane >> 2) * 32 + (lane & 3) * 4;
  sts1(ad, hi); sts1(ad + 16, pack2(a - bflo(hi), b - bfhi(hi)));
  fence_async_smem();
  __syncwarp();
  mbar_arrive1(B_CS);
}

DEV void x0_get(uint32_t (&x)[8][2], uint32_t a) {
  asm volatile("cp.async.wait_group 0;" ::: "memory");
#pragma unroll
  for (int z = 0; z < 4; ++z) {
    const uint4 v = lds4(a + z * 512);
    x[2 * (z & 2)][z & 1] = v.x; x[2 * (z & 2) + 1][z & 1] = v.y; x[2 * (z & 2) + 2][z & 1] = v.z; x[2 * (z & 2) + 3][z & 1] = v.w;
  }
}

DEV void par_load(const Params& P, int ch, int m, uint32_t (&pv)[8]) {
  const int mo = ch * 128 + m;
  pv[0] = ldnc16(P.Are + mo); pv[1] = ldnc16(P.Aim + mo); pv[2] = ldnc16(P.Bre + mo); pv[3] = ldnc16(P.Bim + mo);
  pv[4] = ldnc16(P.Cre + mo); pv[5] = ldnc16(P.Cim + mo); pv[6] = ldnc16(P.logdt + ch); pv[7] = ldnc16(P.dskip + ch);
}

__global__ void __launch_bounds__(NTHR, 1)
fused_kernel(const __grid_constant__ Params P, const __grid_constant__ CUtensorMap mapW,
             const __grid_constant__ CUtensorMap mapWo) {
  extern __shared__ __align__(1024) uint8_t smem_raw[];
  if (s2u(smem_raw) != SB) __trap();
  const int warp0 = __shfl_sync(0xffffffffu, threadIdx.x >> 5, 0), lane0 = threadIdx.x & 31;
  uint32_t smid; asm volatile("mov.u32 %0,%%smid;" : "=r"(smid));
  const int c = __shfl_sync(0xffffffffu, P.by_sm ? P.role[smid] : blockIdx.x, 0);
  if (c == 255) {
    if (threadIdx.x < NCOPY * NSUB)
#pragma unroll 1
      for (int it = 0; it < 256 && ldr1(P.S->C + 32 * threadIdx.x) < 128 / NSUB; ++it) __nanosleep(200);
    return;
  }
  const int cg = c & 7;
  PW(warp0)
  uint32_t dskip;
  {
    [[maybe_unused]] const int layer = 0;
    const int lane = lane0, g = lane >> 2, t = lane & 3, warp = warp0, k4 = warp >> 2, w = warp & 3;
    uint32_t pv[8];
    if (k4 < 3) par_load(P, 128 * k4 + c, 32 * w + lane, pv);
    else {
#pragma unroll
      for (int n = 0; n < 8; ++n) pv[n] = 0;
    }
    __syncthreads();
    if (XDEL) delay(XDEL);
    const uint16_t* r = P.x0 + ((k4 < 2 ? 8192 * c + 64 * warp : (128 * (c >> 3) + 16 * (warp - 8)) * 512 + 64 * cg) + 1024 * g + 8 * t);
    const uint32_t xa = SM_R + k4 * 16384 + w * 2048 + lane * 16;
#pragma unroll
    for (int z = 0; z < 4; ++z) cp16(xa + z * 512, r + (z & 1) * 512 + (z & 2) * 16);
    asm volatile("cp.async.commit_group;" ::: "memory");
    sts4(SM_TAP + k4 * TAP_SZ + (32 * w + lane) * 16, 0, 0, 0, 0);
    sts4z_if(SM_TAP + k4 * TAP_SZ + 2048 + (32 * w + lane) * 16, w < 3);
    const XgAddr xd = xg_addr<false>(P.S->XG + (64 * cg * 256 + 16 * (c >> 3) + 8 * (k4 & 1)), SM_R + k4 * 16384 + 8192, w, lane, P.zero);
    uint32_t x[8][2];
    if (k4 == 3) {
      if (threadIdx.x == 448) {
        asm volatile("prefetch.tensormap [%0];" :: "l"(&mapW) : "memory");
        asm volatile("prefetch.tensormap [%0];" :: "l"(&mapWo) : "memory");
      }
      __syncwarp();
      par_load(P, 128 * k4 + c, 32 * w + lane, pv);
      sts4(SM_STAT - 32 + min(lane, 17) * 16, 0x3F800000u, 0x3F800000u, 0x3F803F80u, 0x3F803F80u);
      x0_get(x, xa);
      PROF(27, a_ld);
      xg_put<false>(xd, x);
      bar_sync(NB_WG + 3, 128);
      xg_store(xd, 1);
      bar_arrive(NB_T + 3, 288);
#pragma unroll
      for (int n = 0; n < 14; ++n) mbar_init1(SM_BAR + (n < 10 ? w * 80 : 240 + w * 32) + n * 8, n < 10 ? 1 : (CNT >> (8 * w + 2 * (n - 10 & 2))) & 15);
      bar_sync(NB_Q, 448);
    }
    tables(pv, k4, w, lane);
    if (k4 < 3) {
      x0_get(x, xa);
      if (k4 < 2) {
        const float4 s = gram(x, g, P.zero);
        if (t == (g >> 1)) sts4f(SM_RES + 8192 + (warp * 8 + g) * 16, s.x, s.y, s.z, s.w);
        __syncwarp();
        bar_arrive_if(NB_P, 256, warp != 7);
      } else {
        xg_put<false>(xd, x);
        bar_sync(NB_WG + 2, 128);
        xg_store(xd, 1);
        bar_arrive(NB_T + 3, 288);
      }
    }
    dskip = pv[7];
    PROF(1, a_x0);
  }
#pragma unroll 1
  for (int layer = 0; layer < 2; ++layer) {
    int lane = lane_here(P.zero);
    const int warp = warp0 | (layer & P.zero), k4 = warp >> 2, w = warp & 3;
    if (warp == (layer ? 12 : 7)) finalize(P, c, lane, layer);
    if (warp == (layer ? 13 : 6)) { announce(P, c, lane, layer); fetch(P, c, lane, layer); }
    if (layer == 0) {
      if (CSP && k4 == 1 && w != 2) { if (CSP > 1) delay(CSP); cs_part(P, c, w - (w >> 1), lane, 0); }
      taps(dskip, k4, w, lane);
    }
    conv(P, &mapW, c, k4, w, layer);
    lane = lane_here(P.zero);
    if (k4 < 2) {
      bar_arrive_if(NB_H, 256, warp != 4);
      if (warp == 0) {
        mbar_wait(B_K, 0);
        cnt_wait(P, 1 + 5 * layer, c, lane);
        x_load(P, c, 0, layer);
        PROF(27, m_xi);
      } else if (k4 == 0 && (CSP == 0 || layer)) cs_part(P, c, w - 1, lane, CSP ? 1 : layer);
      attn_phase(P, c, k4, w, lane, layer);
    } else {
      bar_arrive_if(NB_RL, 256, warp >= 10);
      if (k4 == 3) {
        stats(P, c, w, lane, layer);
      } else if (w < 2) {
        bar_sync_if(NB_RL, 256, w);
        cnt_wait(P, 3 + 5 * layer + w, c, lane);
        bar_sync_if(NB_RL, 256, !w);
        if (w) mbar_wait(B_F, layer);
        x_load(P, c, 2 + w, layer);
        if (H5 && w) w_load(&mapW, cg, 5);
        PROF(14, h_xi);
        if (w == 1) str4(&P.S->SR[layer][lane >> 2][4 * c + (lane & 3)], 0, 0, 0, 0);
      } else if (w == 2) {
        mbar_expect1(B_WO, 65536);
        mbar_expect1(B_RES, 16384);
#pragma unroll 1
        for (int q = 0; q < 4; ++q) {
          if (FH && q < 2) { mbar_wait(B_FH + 8 * q, layer); w_load(&mapW, cg, 4 + 2 * q); }
          mbar_wait(B_F + 8 * q, layer);
          if (!FH && q < 2) w_load(&mapW, cg, 4 + 2 * q);
          if (q == 1 || (q == 0 && !H5)) w_load(&mapW, cg, 5 + 2 * q);
          if (WOQ == 0 && ((q + 1) & 2)) tma5(SM_R + (q & 2) * 16384, &mapWo, 64 * cg, 4 * (q & 2), B_WO);
          if (WOQ && q == 2) {
            if (WOQ >= 2) mbar_wait(B_ST, layer);
            tma5(SM_R, &mapWo, 64 * cg, 0, B_WO);
            if (WOQ < 3) tma5(SM_R + 32768, &mapWo, 64 * cg, 8, B_WO);
          }
          if (q == 3) {
#pragma unroll
            for (int e = 0; e < 2; ++e) bulk(SM_RES + e * 8192, P.S->XF + ((2 * (c >> 3) + 1 - e) * 4096 + cg * 512), 8192, B_RES);
          }
          PROF(15 + q, h_w);
        }
      }
      if (k4 == 2 && w != 2 && layer == 0) cs_sum(P, c, w - (w >> 1), lane);
      if (warp == 11) {
#pragma unroll
        for (int z = 0; z < 8; ++z) sts4(SM_RES + 10240 + lane * 16 + z * 512, ~0u, ~0u, ~0u, ~0u);
        fence_async_smem();
        mbar_wait(PZB, layer);
#pragma unroll
        for (int z = 0; z < 4; ++z) bulk_store(&P.S->O[((c >> 3) * 16 + cg) * 512] + ((z >> 1) * 4096 + (z & 1) * 256), SM_RES + 10240, 4096);
        asm volatile("cp.async.bulk.commit_group;\ncp.async.bulk.wait_group 0;" ::: "memory");
        mbar_arrive1(B_ST + 8);
        PROF(18, h_pz);
      }
      if (warp < 10) o_load(P, c, w, lane, layer);
    }
    asm volatile("mov.b32 %0,0;" : "=r"(dskip));
  }
}

typedef CUresult (*EncodeFn)(CUtensorMap*, CUtensorMapDataType, cuuint32_t, void*, const cuuint64_t*, const cuuint64_t*,
                             const cuuint32_t*, const cuuint32_t*, CUtensorMapInterleave, CUtensorMapSwizzle,
                             CUtensorMapL2promotion, CUtensorMapFloatOOBfill);

#define POOL 0
#define GOFF 0
static int place_roles(uint8_t* role) {
  int dev = 0, nsm = 0;
  cudaGetDevice(&dev);
  cudaDeviceGetAttribute(&nsm, cudaDevAttrMultiProcessorCount, dev);
  if (nsm < 128 || nsm > 144 || (nsm & 1)) return 0;
  cudaFuncSetAttribute(fused_kernel, cudaFuncAttributeNonPortableClusterSizeAllowed, 1);
  int occ[9] = {0};
  for (int k = 2; k <= 8; ++k) {
    cudaLaunchConfig_t cfg = {};
    cudaLaunchAttribute at[1];
    at[0].id = cudaLaunchAttributeClusterDimension;
    at[0].val.clusterDim.x = 2 * k; at[0].val.clusterDim.y = 1; at[0].val.clusterDim.z = 1;
    cfg.gridDim = dim3(2 * k); cfg.blockDim = dim3(NTHR); cfg.dynamicSmemBytes = SM_TOTAL; cfg.attrs = at; cfg.numAttrs = 1;
    if (cudaOccupancyMaxActiveClusters(&occ[k], fused_kernel, &cfg) != cudaSuccess) { cudaGetLastError(); occ[k] = 0; }
  }
  int n[10];
  n[7] = occ[8]; n[6] = occ[7]; n[5] = occ[6] - 0; n[4] = occ[5];
  n[3] = occ[4] - n[7]; n[1] = occ[2] - n[3] - n[5] - n[7]; n[0] = n[2] = n[1];
  n[8] = occ[3] - n[2] - n[5];
  const int ntpc = nsm / 2;
  int sum = 0;
  bool ok = n[0] > 0 && n[0] <= 8;
  for (int r = 0; r < 9; ++r) { ok = ok && n[r] >= 0 && (r == 0 || n[r] <= n[r - 1]); sum += n[r]; }
  if (!ok || sum > ntpc) { for (int r = 0; r < 9; ++r) n[r] = r < 8 ? 8 : 0; sum = 64; }
  int tp[8][9], cnt[8] = {0}, pool[72], np = 0, id = 0;
  for (int r = 0; r < 9; ++r)
    for (int g = n[0] - n[r]; g < n[0]; ++g) tp[g][cnt[g]++] = id++;
  for (; id < ntpc; ++id) pool[np++] = id;
  int order[72], no = 0;
  for (int g = 0; g < n[0]; ++g) {
    const int full = cnt[g] / 4 * 4;
    for (int k = 0; k < cnt[g]; ++k) { if (k < full) order[no++] = tp[g][k]; else pool[np++] = tp[g][k]; }
  }
  for (int k = 0; k < np; ++k) order[no++] = pool[POOL == 1 ? np - 1 - k : POOL == 2 ? (k + np - 2) % np : k];
  for (int k = 0; k < 144; ++k) role[k] = 255;
  for (int k = 0; k < 64; ++k) { role[2 * order[k]] = (2 * k + GOFF) & 127; role[2 * order[k] + 1] = (2 * k + 1 + GOFF) & 127; }
  return nsm;
}

extern "C" void kernel_launch(void* const* d_in, const int* in_sizes, int n_in, void* d_out, int out_size) {
  (void)in_sizes; (void)n_in; (void)out_size;
  static EncodeFn enc = nullptr;
  static uint8_t role[144];
  static int nsm = 0;
  static void* scratch = nullptr;
  if (!enc) {
    void* fn = nullptr;
    cudaDriverEntryPointQueryResult qr;
    cudaGetDriverEntryPoint("cuTensorMapEncodeTiled", &fn, cudaEnableDefault, &qr);
    enc = (EncodeFn)fn;
    cudaFuncSetAttribute(fused_kernel, cudaFuncAttributeMaxDynamicSharedMemorySize, SM_TOTAL);
    nsm = place_roles(role);
    cudaGetSymbolAddress(&scratch, g_S);
  }
  CUtensorMap mW, mWo;
  {
    cuuint64_t dim[3] = {512, 512, 3}, str[2] = {3072, 1024};
    cuuint32_t box[3] = {64, 64, 3}, es[3] = {1, 1, 1};
    enc(&mW, CU_TENSOR_MAP_DATA_TYPE_BFLOAT16, 3, d_in[10], dim, str, box, es, CU_TENSOR_MAP_INTERLEAVE_NONE,
        CU_TENSOR_MAP_SWIZZLE_128B, CU_TENSOR_MAP_L2_PROMOTION_NONE, CU_TENSOR_MAP_FLOAT_OOB_FILL_NONE);
  }
  {
    cuuint64_t dim[5] = {512, 2, 4, 4, 16}, str[4] = {1024, 8192, 2048, 32768};
    cuuint32_t box[5] = {64, 2, 4, 4, 8}, es[5] = {1, 1, 1, 1, 1};
    enc(&mWo, CU_TENSOR_MAP_DATA_TYPE_BFLOAT16, 5, d_in[11], dim, str, box, es, CU_TENSOR_MAP_INTERLEAVE_NONE,
        CU_TENSOR_MAP_SWIZZLE_128B, CU_TENSOR_MAP_L2_PROMOTION_NONE, CU_TENSOR_MAP_FLOAT_OOB_FILL_NONE);
  }
  Params P;
  P.x0 = (const uint16_t*)d_in[0]; P.Are = (const uint16_t*)d_in[1]; P.Aim = (const uint16_t*)d_in[2];
  P.Bre = (const uint16_t*)d_in[3]; P.Bim = (const uint16_t*)d_in[4]; P.Cre = (const uint16_t*)d_in[5];
  P.Cim = (const uint16_t*)d_in[6]; P.logdt = (const uint16_t*)d_in[7]; P.dskip = (const uint16_t*)d_in[8];
  P.wqkv = (const uint16_t*)d_in[10]; P.wo = (const uint16_t*)d_in[11]; P.out = (uint16_t*)d_out;
  for (int k = 0; k < 144; ++k) P.role[k] = role[k];
  P.by_sm = nsm > 0;
  P.zero = 0;
  P.S = (Scratch*)scratch;
  fused_kernel<<<nsm > 0 ? nsm : 128, NTHR, SM_TOTAL, cudaStreamPerThread>>>(P, mW, mWo);
}
```

```cpp
#include <cuda_runtime.h>
#include <cuda_bf16.h>
#include <cuda.h>
#include <stdint.h>

#define DEV __device__ __forceinline__

#define NCOPY 4
#define NSUB 1
constexpr int NTHR = 512;
constexpr int SPIN_LIMIT = 1 << 22;

constexpr uint32_t SB = 1024;
constexpr uint32_t SM_XA   = SB;
constexpr uint32_t SM_S0   = SM_XA + 16384;
constexpr uint32_t SM_S1   = SM_S0 + 49152;
constexpr uint32_t SM_XB   = SM_S1 + 49152;
constexpr uint32_t SM_R    = SM_XB + 16384;
constexpr uint32_t SM_RES  = SM_R + 65536;
constexpr uint32_t SM_TAP  = SM_RES + 16384;
constexpr int TAP_SZ = 3584;
constexpr uint32_t SM_CS   = SM_TAP + 4 * TAP_SZ;
constexpr uint32_t SM_STAT = SM_CS + 800;
constexpr uint32_t SM_MISC = SM_STAT + 1280;
constexpr uint32_t SM_BAR  = SM_MISC + 512;
constexpr int SM_TOTAL = SM_BAR + 448 - SB;
constexpr int R_U = 512, R_A5 = 5120, R_A3 = 8704, R_B = 11776;
constexpr int T_E = 1536, T_O = T_E + 1602, T_C = 3714;
constexpr uint32_t B_W = SM_BAR, B_X = SM_BAR + 64, B_O = SM_BAR + 128, B_WO = SM_BAR + 256, B_RES = SM_BAR + 264;
constexpr uint32_t B_ST = SM_BAR + 272, B_R = SM_BAR + 288, B_E = SM_BAR + 304;
constexpr uint32_t B_F = SM_BAR + 320, B_G = SM_BAR + 352, B_K = SM_BAR + 376, B_ED = SM_BAR + 384, B_CS = SM_BAR + 400, B_FH = SM_BAR + 416;
constexpr uint32_t CNT = 0x143444CC;
constexpr int NB_WG = 1, NB_T = 5, NB_Q = 10, NB_H = 11, NB_P = 14, NB_RL = 15;

struct Scratch {
  uint32_t F[32 * 32];
  uint4    H[17 * 8 * 256];
  uint4    SR[2][8][512];
  uint4    ST[32 * 16];
  uint4    PS[128 * 64];
  float4   CS[16 * 1536 / 4];
  uint32_t C[10 * 32 * 32];
  uint4    XF[32 * 4096];
  uint4    O[32 * 8 * 512];
  uint4    XG[512 * 256];
};
__device__ __align__(1024) Scratch g_S;

struct Params {
  const uint16_t *logdt, *dskip, *Are, *Aim, *Bre, *Bim, *Cre, *Cim, *x0, *wqkv, *wo;
  uint16_t* out;
  Scratch* S;
  uint32_t zero, pad;
  uint8_t role[144];
};
#define EVENT(n) do {} while (0)
#define PROFD(slot, name, v) do {} while (0)
#define PROF(slot, name) do {} while (0)
#define PW(x)

DEV uint32_t s2u(const void* p) { return (uint32_t)__cvta_generic_to_shared(p); }
template <class T> DEV T opq(T x) { asm volatile("" : "+r"(x)); return x; }
DEV uint32_t pack2(float lo, float hi) { uint32_t d; asm("cvt.rn.bf16x2.f32 %0,%1,%2;" : "=r"(d) : "f"(hi), "f"(lo)); return d; }
DEV float bflo(uint32_t v) { return __uint_as_float(v << 16); }
DEV float bfhi(uint32_t v) { return __uint_as_float(v & 0xFFFF0000u); }
DEV float bfr(float x) { return bflo(pack2(x, 0.f)); }
DEV uint32_t hadd2(uint32_t a, uint32_t b) { uint32_t d; asm("add.rn.bf16x2 %0,%1,%2;" : "=r"(d) : "r"(a), "r"(b)); return d; }
DEV uint32_t hsub2(uint32_t a, uint32_t b) { uint32_t d; asm("sub.rn.bf16x2 %0,%1,%2;" : "=r"(d) : "r"(a), "r"(b)); return d; }
DEV uint32_t hmul2(uint32_t a, uint32_t b) { uint32_t d; asm("mul.rn.bf16x2 %0,%1,%2;" : "=r"(d) : "r"(a), "r"(b)); return d; }
DEV uint32_t hfma2(uint32_t a, uint32_t b, uint32_t c) { uint32_t d; asm("fma.rn.bf16x2 %0,%1,%2,%3;" : "=r"(d) : "r"(a), "r"(b), "r"(c)); return d; }
DEV uint32_t hmax2(uint32_t a, uint32_t b) { uint32_t d; asm("max.bf16x2 %0,%1,%2;" : "=r"(d) : "r"(a), "r"(b)); return d; }
DEV uint32_t prmt(uint32_t a, uint32_t b, uint32_t s) { uint32_t d; asm("prmt.b32 %0,%1,%2,%3;" : "=r"(d) : "r"(a), "r"(b), "r"(s)); return d; }
DEV uint32_t nz(uint32_t v) { uint32_t d; asm("max.u32 %0,%1,1;" : "=r"(d) : "r"(v)); return d; }
DEV uint32_t tagged(uint32_t v, uint32_t m, uint32_t tag) { uint32_t d; asm("lop3.b32 %0,%1,%2,%3,0xB8;" : "=r"(d) : "r"(v), "r"(m), "r"(tag)); return d; }
DEV uint32_t both(uint32_t a, uint32_t b, uint32_t x) { uint32_t d; asm("lop3.b32 %0,%1,%2,%3,0x42;" : "=r"(d) : "r"(a), "r"(b), "r"(x)); return d; }
DEV uint4 hadd8(const uint4& a, const uint4& b) { return make_uint4(hadd2(a.x, b.x), hadd2(a.y, b.y), hadd2(a.z, b.z), hadd2(a.w, b.w)); }
DEV uint32_t min4(const uint4& v) { return min(min(v.x, v.y), min(v.z, v.w)); }
DEV float rcp(float x) { float y; asm("rcp.approx.ftz.f32 %0,%1;" : "=f"(y) : "f"(x)); return y; }
DEV float sqrt_(float x) { float y; asm("sqrt.approx.ftz.f32 %0,%1;" : "=f"(y) : "f"(x)); return y; }
DEV float rsq(float x) { float y; asm("rsqrt.approx.ftz.f32 %0,%1;" : "=f"(y) : "f"(x)); return y; }
DEV float ex2(float x) { float y; asm("ex2.approx.ftz.f32 %0,%1;" : "=f"(y) : "f"(x)); return y; }

DEV uint4 ldr4(const void* p) { uint4 v; asm volatile("ld.relaxed.gpu.global.v4.u32 {%0,%1,%2,%3},[%4];" : "=r"(v.x), "=r"(v.y), "=r"(v.z), "=r"(v.w) : "l"(p) : "memory"); return v; }
DEV void ldr4_if(uint4& v, const void* p, bool c) {
  asm volatile("{.reg .pred q; setp.ne.u32 q,%5,0; @q ld.relaxed.gpu.global.v4.u32 {%0,%1,%2,%3},[%4];}"
    : "+r"(v.x), "+r"(v.y), "+r"(v.z), "+r"(v.w) : "l"(p), "r"((uint32_t)c) : "memory");
}
DEV uint2 ldr2(const void* p) { uint2 v; asm volatile("ld.relaxed.gpu.global.v2.u32 {%0,%1},[%2];" : "=r"(v.x), "=r"(v.y) : "l"(p) : "memory"); return v; }
DEV uint32_t ldr1(const void* p) { uint32_t v; asm volatile("ld.relaxed.gpu.global.u32 %0,[%1];" : "=r"(v) : "l"(p) : "memory"); return v; }
DEV void str4(void* p, uint32_t a, uint32_t b, uint32_t c, uint32_t d) { asm volatile("st.relaxed.gpu.global.v4.u32 [%0],{%1,%2,%3,%4};" :: "l"(p), "r"(a), "r"(b), "r"(c), "r"(d) : "memory"); }
DEV void str4_if(void* p, uint32_t a, uint32_t b, uint32_t c, uint32_t d, bool q) {
  asm volatile("{.reg .pred q; setp.ne.u32 q,%5,0; @q st.relaxed.gpu.global.v4.u32 [%0],{%1,%2,%3,%4};}" :: "l"(p), "r"(a), "r"(b), "r"(c), "r"(d), "r"((uint32_t)q) : "memory");
}
DEV void str2(void* p, uint32_t a, uint32_t b) { asm volatile("st.relaxed.gpu.global.v2.u32 [%0],{%1,%2};" :: "l"(p), "r"(a), "r"(b) : "memory"); }
DEV void str1(void* p, uint32_t a) { asm volatile("st.relaxed.gpu.global.u32 [%0],%1;" :: "l"(p), "r"(a) : "memory"); }
DEV void stw4(void* p, uint32_t a, uint32_t b, uint32_t c, uint32_t d) { asm volatile("st.global.v4.u32 [%0],{%1,%2,%3,%4};" :: "l"(p), "r"(a), "r"(b), "r"(c), "r"(d) : "memory"); }
DEV uint4 ldnc4(const void* p) { uint4 v; asm volatile("ld.global.nc.v4.u32 {%0,%1,%2,%3},[%4];" : "=r"(v.x), "=r"(v.y), "=r"(v.z), "=r"(v.w) : "l"(p)); return v; }
DEV uint4 ldw4(const void* p) { uint4 v; asm volatile("ld.global.v4.u32 {%0,%1,%2,%3},[%4];" : "=r"(v.x), "=r"(v.y), "=r"(v.z), "=r"(v.w) : "l"(p) : "memory"); return v; }
DEV void cp16(uint32_t d, const void* p) { asm volatile("cp.async.cg.shared.global [%0],[%1],16;" :: "r"(d), "l"(p) : "memory"); }
DEV uint32_t ld16_if(const void* p, bool c) { uint32_t v = 0; asm volatile("{.reg .pred q; setp.ne.u32 q,%2,0; @q ld.global.u16 %0,[%1];}" : "+r"(v) : "l"(p), "r"((uint32_t)c) : "memory"); return v; }
DEV uint32_t ldnc16(const void* p) { uint32_t v; asm volatile("ld.global.u16 %0,[%1];" : "=r"(v) : "l"(p) : "memory"); return v; }

DEV uint32_t lds1v(uint32_t a) { uint32_t v; asm volatile("ld.volatile.shared.u32 %0,[%1];" : "=r"(v) : "r"(a) : "memory"); return v; }
DEV uint4 lds4v(uint32_t a) { uint4 v; asm volatile("ld.volatile.shared.v4.u32 {%0,%1,%2,%3},[%4];" : "=r"(v.x), "=r"(v.y), "=r"(v.z), "=r"(v.w) : "r"(a) : "memory"); return v; }
DEV uint32_t lds1(uint32_t a) { uint32_t v; asm volatile("ld.shared.u32 %0,[%1];" : "=r"(v) : "r"(a)); return v; }
DEV uint2 lds2(uint32_t a) { uint2 v; asm volatile("ld.shared.v2.u32 {%0,%1},[%2];" : "=r"(v.x), "=r"(v.y) : "r"(a)); return v; }
DEV uint4 lds4(uint32_t a) { uint4 v; asm volatile("ld.shared.v4.u32 {%0,%1,%2,%3},[%4];" : "=r"(v.x), "=r"(v.y), "=r"(v.z), "=r"(v.w) : "r"(a)); return v; }
DEV uint32_t lds16(uint32_t a) { uint32_t v; asm volatile("ld.shared.u16 %0,[%1];" : "=r"(v) : "r"(a)); return v; }
DEV float lds1f(uint32_t a) { float v; asm volatile("ld.shared.f32 %0,[%1];" : "=f"(v) : "r"(a)); return v; }
DEV float2 lds2f(uint32_t a) { float2 v; asm volatile("ld.shared.v2.f32 {%0,%1},[%2];" : "=f"(v.x), "=f"(v.y) : "r"(a)); return v; }
DEV float4 lds4f(uint32_t a) { float4 v; asm volatile("ld.shared.v4.f32 {%0,%1,%2,%3},[%4];" : "=f"(v.x), "=f"(v.y), "=f"(v.z), "=f"(v.w) : "r"(a)); return v; }
DEV void sts1(uint32_t a, uint32_t v) { asm volatile("st.shared.u32 [%0],%1;" :: "r"(a), "r"(v) : "memory"); }
DEV void sts16(uint32_t a, uint32_t v) { asm volatile("{.reg .b16 h; cvt.u16.u32 h,%1; st.shared.u16 [%0],h;}" :: "r"(a), "r"(v) : "memory"); }
DEV void sts2f(uint32_t a, float x, float y) { asm volatile("st.shared.v2.f32 [%0],{%1,%2};" :: "r"(a), "f"(x), "f"(y) : "memory"); }
DEV void sts4f(uint32_t a, float x, float y, float z, float w) { asm volatile("st.shared.v4.f32 [%0],{%1,%2,%3,%4};" :: "r"(a), "f"(x), "f"(y), "f"(z), "f"(w) : "memory"); }
DEV void sts4(uint32_t a, uint32_t x, uint32_t y, uint32_t z, uint32_t w) { asm volatile("st.shared.v4.u32 [%0],{%1,%2,%3,%4};" :: "r"(a), "r"(x), "r"(y), "r"(z), "r"(w) : "memory"); }
DEV void sts4_if(uint32_t a, uint32_t x, uint32_t y, uint32_t z, uint32_t w, bool c) {
  asm volatile("{.reg .pred q; setp.ne.u32 q,%5,0; @q st.shared.v4.u32 [%0],{%1,%2,%3,%4};}" :: "r"(a), "r"(x), "r"(y), "r"(z), "r"(w), "r"((uint32_t)c) : "memory");
}
DEV void sts4z_if(uint32_t a, bool c) { asm volatile("{.reg .pred q; setp.ne.u32 q,%1,0; @q st.shared.v4.u32 [%0],{%2,%2,%2,%2};}" :: "r"(a), "r"((uint32_t)c), "r"(0) : "memory"); }

DEV void ldsm4t(uint32_t& r0, uint32_t& r1, uint32_t& r2, uint32_t& r3, uint32_t a) { asm volatile("ldmatrix.sync.aligned.m8n8.x4.trans.shared.b16 {%0,%1,%2,%3},[%4];" : "=r"(r0), "=r"(r1), "=r"(r2), "=r"(r3) : "r"(a) : "memory"); }
DEV void stsm4(uint32_t a, uint32_t r0, uint32_t r1, uint32_t r2, uint32_t r3) { asm volatile("stmatrix.sync.aligned.m8n8.x4.shared.b16 [%0],{%1,%2,%3,%4};" :: "r"(a), "r"(r0), "r"(r1), "r"(r2), "r"(r3) : "memory"); }
DEV void stsm2(uint32_t a, uint32_t r0, uint32_t r1) { asm volatile("stmatrix.sync.aligned.m8n8.x2.shared.b16 [%0],{%1,%2};" :: "r"(a), "r"(r0), "r"(r1) : "memory"); }
DEV void stsm4t(uint32_t a, uint32_t r0, uint32_t r1, uint32_t r2, uint32_t r3) { asm volatile("stmatrix.sync.aligned.m8n8.x4.trans.shared.b16 [%0],{%1,%2,%3,%4};" :: "r"(a), "r"(r0), "r"(r1), "r"(r2), "r"(r3) : "memory"); }
DEV uint32_t movm(uint32_t a) { uint32_t d; asm volatile("movmatrix.sync.aligned.m8n8.trans.b16 %0,%1;" : "=r"(d) : "r"(a)); return d; }
DEV void mma16(float (&d)[4], uint32_t a0, uint32_t a1, uint32_t a2, uint32_t a3, uint32_t b0, uint32_t b1) {
  asm volatile("mma.sync.aligned.m16n8k16.row.col.f32.bf16.bf16.f32 {%0,%1,%2,%3},{%4,%5,%6,%7},{%8,%9},{%0,%1,%2,%3};"
    : "+f"(d[0]), "+f"(d[1]), "+f"(d[2]), "+f"(d[3]) : "r"(a0), "r"(a1), "r"(a2), "r"(a3), "r"(b0), "r"(b1));
}
DEV void mma16z(float (&d)[4], uint32_t a0, uint32_t a1, uint32_t a2, uint32_t a3, uint32_t b0, uint32_t b1) {
  asm volatile("mma.sync.aligned.m16n8k16.row.col.f32.bf16.bf16.f32 {%0,%1,%2,%3},{%4,%5,%6,%7},{%8,%9},{%10,%10,%10,%10};"
    : "=f"(d[0]), "=f"(d[1]), "=f"(d[2]), "=f"(d[3]) : "r"(a0), "r"(a1), "r"(a2), "r"(a3), "r"(b0), "r"(b1), "f"(0.f));
}
DEV void mma8z(float (&d)[4], uint32_t a0, uint32_t a1, uint32_t b0) {
  asm volatile("mma.sync.aligned.m16n8k8.row.col.f32.bf16.bf16.f32 {%0,%1,%2,%3},{%4,%5},{%6},{%7,%7,%7,%7};"
    : "=f"(d[0]), "=f"(d[1]), "=f"(d[2]), "=f"(d[3]) : "r"(a0), "r"(a1), "r"(b0), "f"(0.f));
}
DEV void mma8(float (&d)[4], uint32_t a0, uint32_t a1, uint32_t b0) {
  asm volatile("mma.sync.aligned.m16n8k8.row.col.f32.bf16.bf16.f32 {%0,%1,%2,%3},{%4,%5},{%6},{%0,%1,%2,%3};"
    : "+f"(d[0]), "+f"(d[1]), "+f"(d[2]), "+f"(d[3]) : "r"(a0), "r"(a1), "r"(b0));
}

DEV void bar_sync(int id, int n) { asm volatile("bar.sync %0,%1;" :: "r"(id), "r"(n) : "memory"); }
DEV void bar_arrive(int id, int n) { asm volatile("bar.arrive %0,%1;" :: "r"(id), "r"(n) : "memory"); }
DEV void bar_sync_if(int id, int n, int c) { asm volatile("{.reg .pred q; setp.ne.s32 q,%2,0; @q bar.sync %0,%1;}" :: "r"(id), "r"(n), "r"(c) : "memory"); }
DEV void bar_arrive_if(int id, int n, int c) { asm volatile("{.reg .pred q; setp.ne.s32 q,%2,0; @q bar.arrive %0,%1;}" :: "r"(id), "r"(n), "r"(c) : "memory"); }
DEV bool bar_any(int id, int n, bool c) {
  uint32_t r; asm volatile("{.reg .pred p,q; setp.ne.u32 q,%3,0; bar.red.or.pred p,%1,%2,q; selp.u32 %0,1,0,p;}" : "=r"(r) : "r"(id), "r"(n), "r"((uint32_t)c) : "memory");
  return __any_sync(0xffffffffu, r);
}
DEV void fence_async_glob() { asm volatile("fence.proxy.async.global;" ::: "memory"); }
DEV void fence_async_smem() { asm volatile("fence.proxy.async.shared::cta;" ::: "memory"); }
DEV void fence_gpu() { asm volatile("fence.acq_rel.gpu;" ::: "memory"); }
DEV void mbar_wait(uint32_t b, uint32_t ph) {
  asm volatile("{\n.reg .pred p;\nW: mbarrier.try_wait.parity.shared::cta.b64 p,[%0],%1;\n@!p bra W;\n}" :: "r"(b), "r"(ph) : "memory");
}
DEV bool mbar_test(uint32_t b, uint32_t ph) {
  uint32_t r; asm volatile("{.reg .pred p; mbarrier.test_wait.parity.shared::cta.b64 p,[%1],%2; selp.u32 %0,1,0,p;}" : "=r"(r) : "r"(b), "r"(ph) : "memory");
  return __all_sync(0xffffffffu, r);
}
DEV uint32_t mbar_test2(uint32_t b, uint32_t ph) {
  uint32_t r; asm volatile("{.reg .pred p,q; mbarrier.test_wait.parity.shared::cta.b64 p,[%1],%2; mbarrier.test_wait.parity.shared::cta.b64 q,[%1+8],%2;\n"
                           "and.pred p,p,q; selp.u32 %0,1,0,p;}" : "=r"(r) : "r"(b), "r"(ph) : "memory");
  return r;
}
DEV void spin_guard(int it) { asm volatile("{.reg .pred p; setp.gt.s32 p,%0,%1; @p trap;}" :: "r"(it), "n"(SPIN_LIMIT)); }
DEV uint32_t here(uint32_t zero) {
  uint32_t d; asm volatile("mov.u32 %0,%%clock;" : "=r"(d) :: "memory"); return d & zero;
}
DEV int lane_here(uint32_t zero) {
  uint32_t d; asm volatile("mov.u32 %0,%%laneid;" : "=r"(d)); return d | here(zero);
}
DEV void delay(uint32_t n) {
  asm volatile("{\n.reg .pred p;\n.reg .u32 a,b;\nmov.u32 a,%%clock;\nW: mov.u32 b,%%clock;\nsub.u32 b,b,a;\nsetp.lt.u32 p,b,%0;\n@p bra.uni W;\n}" :: "r"(n) : "memory");
}
DEV void poll(const uint32_t* p, uint32_t n) {
  for (int it = 0; !__all_sync(0xffffffffu, ldr1(p) >= n); ++it) spin_guard(it);
}
DEV uint32_t* cnt_at(const Params& P, int n, int c, int lane) { return P.S->C + (32 * (NSUB * lane + c % NSUB) + n * 1024); }
DEV void cnt_add(uint32_t* p, uint32_t one, bool q) { asm volatile("{.reg .pred p; setp.ne.u32 p,%2,0; @p red.relaxed.gpu.global.add.u32 [%0],%1;}" :: "l"(p), "r"(one), "r"((uint32_t)q) : "memory"); }
DEV void cnt_wait(const Params& P, int n, int c, int lane) { poll(P.S->C + (32 * (NSUB * (c / (128 / NCOPY)) + lane % NSUB) + n * 1024), 128 / NSUB); }
DEV void mbar_init1(uint32_t b, int n) { asm volatile("{.reg .pred p; elect.sync _|p,0xffffffff; @p mbarrier.init.shared::cta.b64 [%0],%1;}" :: "r"(b), "r"(n) : "memory"); }
DEV void mbar_arrive1(uint32_t b) { asm volatile("{.reg .pred p; elect.sync _|p,0xffffffff; @p mbarrier.arrive.shared::cta.b64 _,[%0];}" :: "r"(b) : "memory"); }
DEV void mbar_arrive1_if(uint32_t b, int c) {
  asm volatile("{.reg .pred p,q; setp.ne.s32 q,%1,0; elect.sync _|p,0xffffffff; and.pred p,p,q; @p mbarrier.arrive.shared::cta.b64 _,[%0];}" :: "r"(b), "r"(c) : "memory");
}
DEV void mbar_expect1(uint32_t b, int bytes) { asm volatile("{.reg .pred p; elect.sync _|p,0xffffffff; @p mbarrier.arrive.expect_tx.shared::cta.b64 _,[%0],%1;}" :: "r"(b), "r"(bytes) : "memory"); }
DEV void flag_set1(uint32_t* q) { asm volatile("{.reg .pred p; elect.sync _|p,0xffffffff; @p st.relaxed.gpu.global.u32 [%0],1;}" :: "l"(q) : "memory"); }
DEV void tma3(uint32_t dst, const CUtensorMap* m, int c0, int c1, uint32_t bar) {
  asm volatile("{.reg .pred p; elect.sync _|p,0xffffffff;\n"
    "@p cp.async.bulk.tensor.3d.shared::cluster.global.mbarrier::complete_tx::bytes [%0],[%1,{%2,%3,%5}],[%4];}"
    :: "r"(dst), "l"(m), "r"(c0), "r"(c1), "r"(bar), "r"(0) : "memory");
}
DEV void tma5(uint32_t dst, const CUtensorMap* m, int c0, int c4, uint32_t bar) {
  asm volatile("{.reg .pred p; elect.sync _|p,0xffffffff;\n"
    "@p cp.async.bulk.tensor.5d.shared::cluster.global.mbarrier::complete_tx::bytes [%0],[%1,{%2,%5,%5,%5,%3}],[%4];}"
    :: "r"(dst), "l"(m), "r"(c0), "r"(c4), "r"(bar), "r"(0) : "memory");
}
DEV void bulk(uint32_t dst, const void* src, int bytes, uint32_t bar) {
  asm volatile("{.reg .pred p; elect.sync _|p,0xffffffff;\n@p cp.async.bulk.shared::cluster.global.mbarrier::complete_tx::bytes [%0],[%1],%2,[%3];}" :: "r"(dst), "l"(src), "r"(bytes), "r"(bar) : "memory");
}
DEV void bulk_store(void* dst, uint32_t src, int bytes) {
  asm volatile("{.reg .pred p; elect.sync _|p,0xffffffff;\n@p cp.async.bulk.global.shared::cta.bulk_group [%0],[%1],%2;}" :: "l"(dst), "r"(src), "r"(bytes) : "memory");
}
DEV void l2_prefetch(const void* src, int bytes) {
  asm volatile("{.reg .pred p; elect.sync _|p,0xffffffff;\n@p cp.async.bulk.prefetch.L2.global [%0],%1;}" :: "l"(src), "r"(bytes) : "memory");
}

DEV uint64_t mkdesc(uint32_t addr, uint32_t lbo, uint32_t sbo, uint32_t swz) {
  return (uint64_t)((addr >> 4) | ((lbo >> 4) << 16)) | ((uint64_t)((sbo >> 4) | (swz << 30)) << 32);
}
DEV void wg_fence() { asm volatile("wgmma.fence.sync.aligned;" ::: "memory"); }
DEV void wg_commit() { asm volatile("wgmma.commit_group.sync.aligned;" ::: "memory"); }
template <int N> DEV void wg_wait() { asm volatile("wgmma.wait_group.sync.aligned %0;" :: "n"(N) : "memory"); }
template <int N> DEV void zerov(float (&d)[N]) {
#pragma unroll
  for (int i = 0; i < N; ++i) asm volatile("mov.b32 %0,0;" : "=f"(d[i]));
}
template <int N> DEV void undef(float (&d)[N]) {
#pragma unroll
  for (int i = 0; i < N; ++i) asm volatile("" : "=f"(d[i]));
}
#define R4(d, o) "+f"(d[o]), "+f"(d[o + 1]), "+f"(d[o + 2]), "+f"(d[o + 3])
#define R8(d, o) R4(d, o), R4(d, o + 4)
#define R16(d, o) R8(d, o), R8(d, o + 8)
#define R32(d, o) R16(d, o), R16(d, o + 16)
#define L0 "%0,%1,%2,%3,%4,%5,%6,%7,%8,%9,"
#define L10(a) "%" #a "0,%" #a "1,%" #a "2,%" #a "3,%" #a "4,%" #a "5,%" #a "6,%" #a "7,%" #a "8,%" #a "9,"
#define WG_HEAD(pr, n) "{.reg .pred p; setp.ne.s32 p,%" #pr ",0;\nwgmma.mma_async.sync.aligned.m64n" #n "k16.f32.bf16.bf16 {"
DEV void wg_rs64k(float (&d)[32], const uint32_t (&a)[4], uint64_t db, int acc) {
  asm volatile(WG_HEAD(37, 64) L0 L10(1) L10(2) "%30,%31},{%32,%33,%34,%35},%36,p,1,1,0;}"
    : R32(d, 0) : "r"(a[0]), "r"(a[1]), "r"(a[2]), "r"(a[3]), "l"(db), "r"(acc));
}
DEV void wg_rs48t(float (&d)[24], const uint32_t (&a)[4], uint64_t db, int acc) {
  asm volatile(WG_HEAD(29, 48) L0 L10(1) "%20,%21,%22,%23},{%24,%25,%26,%27},%28,p,1,1,1;}"
    : R16(d, 0), R8(d, 16) : "r"(a[0]), "r"(a[1]), "r"(a[2]), "r"(a[3]), "l"(db), "r"(acc));
}
DEV void wg_rs32t(float (&d)[16], const uint32_t (&a)[4], uint64_t db, int acc) {
  asm volatile(WG_HEAD(21, 32) L0 "%10,%11,%12,%13,%14,%15},{%16,%17,%18,%19},%20,p,1,1,1;}"
    : R16(d, 0) : "r"(a[0]), "r"(a[1]), "r"(a[2]), "r"(a[3]), "l"(db), "r"(acc));
}
DEV void wg_ss48(float (&d)[24], uint64_t da, uint64_t db, int acc) {
  asm volatile(WG_HEAD(26, 48) L0 L10(1) "%20,%21,%22,%23},%24,%25,p,1,1,1,1;}" : R16(d, 0), R8(d, 16) : "l"(da), "l"(db), "r"(acc));
}
DEV void wg_ss64(float (&d)[32], uint64_t da, uint64_t db, int acc) {
  asm volatile(WG_HEAD(34, 64) L0 L10(1) L10(2) "%30,%31},%32,%33,p,1,1,0,1;}" : R32(d, 0) : "l"(da), "l"(db), "r"(acc));
}
DEV void wg_ss192(float (&d)[96], uint64_t da, uint64_t db, int acc) {
  asm volatile(WG_HEAD(98, 192) L0 L10(1) L10(2) L10(3) L10(4) L10(5) L10(6) L10(7) L10(8) "%90,%91,%92,%93,%94,%95},%96,%97,p,1,1,1,1;}"
    : R32(d, 0), R32(d, 32), R32(d, 64) : "l"(da), "l"(db), "r"(acc));
}

DEV void wg_rs192t(float (&d)[96], const uint32_t (&a)[4], uint64_t db) {
  asm volatile("wgmma.mma_async.sync.aligned.m64n192k16.f32.bf16.bf16 {" L0 L10(1) L10(2) L10(3) L10(4) L10(5) L10(6) L10(7) L10(8) "%90,%91,%92,%93,%94,%95},{%96,%97,%98,%99},%100,1,1,1,1;"
    : R32(d, 0), R32(d, 32), R32(d, 64) : "r"(a[0]), "r"(a[1]), "r"(a[2]), "r"(a[3]), "l"(db));
}

DEV float ln_sd(float s, float q, float& m) {
  m = s * (1.f / 512.f);
  return bfr(sqrt_(bfr(bfr(fmaxf(q * (1.f / 512.f) - m * m, 0.f)) + 1e-5f)));
}
DEV float4 gram(const uint32_t (&w)[8][2], int g, uint32_t zero) {
  float s[4], q[4][4];
  const uint32_t o0 = 0x3F803F80u | zero, o1 = 0x3F803F80u ^ zero;
#pragma unroll
  for (int j = 0; j < 8; ++j) {
#pragma unroll
    for (int h = 0; h < 2; ++h) { if (j < 2) mma8z(q[2 * j + h], w[j][0], w[j][1], w[j][h]); else mma8(q[2 * (j & 1) + h], w[j][0], w[j][1], w[j][h]); }
    if (j == 1) mma16z(s, w[0][0], w[0][1], w[1][0], w[1][1], o0, o1);
    else if (j & 1) mma16(s, w[j - 1][0], w[j - 1][1], w[j][0], w[j][1], o0, o1);
  }
  const bool od = g & 1;
  return make_float4(s[0], od ? q[0][1] + q[2][1] : q[0][0] + q[2][0], s[2], od ? q[1][3] + q[3][3] : q[1][2] + q[3][2]);
}
DEV void keep(uint32_t v, uint32_t zero) {
  asm volatile("{.reg .pred p; setp.ne.u32 p,%1,0; @p st.shared.u32 [%0],%0;}" :: "r"(v), "r"(zero) : "memory");
}
DEV void keep(const void* v, uint32_t zero) { asm volatile("{.reg .pred p; setp.ne.u32 p,%1,0; @p st.global.u32 [%0],%1;}" :: "l"(v), "r"(zero) : "memory"); }
struct XgAddr { uint32_t a, b; uint4* dst; };
template <bool FRAG> DEV XgAddr xg_addr(uint4* dst, uint32_t stg, int wp, int lane, uint32_t zero) {
  const int t = lane & 3, r = 4 * wp + (lane >> 3);
  XgAddr x = {stg + t * (FRAG ? 256 : 1024) + ((wp ^ t) * 32) + (lane >> 2) * 4,
              stg + r * 128 + (((lane & 7) ^ (2 * (((r >> 1) ^ (r >> 3)) & 3))) * 16), dst + (r * 256 + (lane & 7))};
  keep(x.a, zero); keep(x.b, zero); keep(x.dst, zero);
  return x;
}
template <bool FRAG> DEV void xg_put(const XgAddr& x, const uint32_t (&w)[8][2]) {
#pragma unroll
  for (int n = 0; n < 8; ++n) {
    const uint32_t b = (x.a ^ ((n & 3) * 32)) + (FRAG ? n * 1024 : (n >> 2) * 4096 + (n & 3) * 256);
    sts1(b, prmt(w[n][0], w[n][1], 0x5410)); sts1(b + 128, prmt(w[n][0], w[n][1], 0x7632));
  }
}
DEV void xg_store(const XgAddr& x, uint32_t tag) {
  const uint32_t m = (~x.b >> 4) & 1;
#pragma unroll
  for (int k = 0; k < 4; ++k) {
    const uint4 v = lds4((x.b ^ ((k & 1) * 64)) + k * 2048);
    str4(x.dst + k * 4096, tagged(v.x, m, tag), v.y, v.z, v.w);
  }
}
template <int N, int M> DEV void fold(float (&v)[M], int lane, int bit) {
  const bool b = lane & bit;
#pragma unroll
  for (int k = 0; k < N; ++k) { const float sn = b ? v[k] : v[k + N], kp = b ? v[k + N] : v[k]; v[k] = kp + __shfl_xor_sync(0xffffffffu, sn, bit); }
}
DEV void refetch(uint32_t dst, const uint4* src, int half, int e, int w) {
#pragma unroll 1
  for (int r = 0; r < 2; ++r) {
    if (w == 0) { mbar_expect1(B_R + 8 * e, half); bulk(dst + r * half, src + r * (half >> 4), half, B_R + 8 * e); }
    mbar_wait(B_R + 8 * e, r);
    bar_sync(NB_WG + e, 128);
  }
}
DEV uint32_t kvslot(int cg, int pos) { return (pos & 2 ? SM_XA : SM_S1) + (cg < 4 ? 5 : 2) * 8192 + (pos & 1) * 4096; }
DEV uint32_t xstage(int q, int e) { return ((q + 1) & 2) ? SM_R + ((q & 2) + e) * 16384 : e ? SM_XB : SM_XA; }
DEV void cmul(float& orr, float& oi, float ar, float ai, float br, float bi) {
  float r = ar * br - ai * bi, i = ar * bi + ai * br; orr = r; oi = i;
}
DEV void cexp_(float al, float bt, float s, float& er, float& ei) {
  float mag = ex2(al * s), ph = bt * s;
  ph -= rintf(ph);
  float ang = ph * 6.283185307179586f;
  er = mag * __cosf(ang); ei = mag * __sinf(ang);
}

#define KS 2048
DEV void put8(uint32_t a, const float (&r)[8], const float (&i)[8]) {
  sts4(a, pack2(r[0], r[1]), pack2(r[2], r[3]), pack2(r[4], r[5]), pack2(r[6], r[7]));
  sts4(a + 1024, pack2(i[0], i[1]), pack2(i[2], i[3]), pack2(i[4], i[5]), pack2(i[6], i[7]));
}
DEV void tables(const uint32_t (&pv)[8], int k4, int w, int lane) {
  PW(4 * k4 + w)
  [[maybe_unused]] const int layer = 0;
  const float dt = bfr(__expf(bflo(pv[6])));
  const float al = dt * bflo(pv[0]) * 1.4426950408889634f, bt = dt * bflo(pv[1]) * 0.15915494309189535f;
  float qr[8], qi[8], yr[8], yi[8];
  cmul(qr[0], qi[0], bflo(pv[4]), bflo(pv[5]), dt * bflo(pv[2]), dt * bflo(pv[3]));
  PROFD(2, a_par, __float_as_uint(qr[0] + al + bt));
  float e1r, e1i, eMr, eMi, eLr, eLi;
  cexp_(al, bt, 1.f, e1r, e1i); cexp_(al, -bt, 8.f, yr[1], yi[1]); cexp_(al, -bt, 64.f, eMr, eMi); cexp_(al, bt, 256.f, eLr, eLi);
  const uint32_t ad = SB + k4 * 32768 + (w & 1) * 512 + lane * 16, am = ad + (w >> 1) * KS, an = ad + (8 + 3 * (w >> 1)) * KS;
  yr[0] = 1.f; yi[0] = 0.f;
#pragma unroll
  for (int k = 1; k < 8; ++k) {
    cmul(qr[k], qi[k], qr[k - 1], qi[k - 1], e1r, e1i);
    if (k > 1) cmul(yr[k], yi[k], yr[k - 1], yi[k - 1], yr[1], yi[1]);
  }
  put8(an, qr, qi);
#pragma unroll
  for (int j = 0; j < 4; ++j) {
    put8(am + j * 2 * KS, yr, yi);
#pragma unroll
    for (int k = 0; k < 8; ++k) {
      if (j == 0 && k == 0) { yr[0] = eMr; yi[0] = eMi; } else if (j < 3) cmul(yr[k], yi[k], yr[k], yi[k], eMr, eMi);
    }
    if (j == 0) {
#pragma unroll
      for (int k = 0; k < 8; ++k) { const int o = k < 4 ? 2 * k : k < 6 ? 2 * k - 8 : k - 2; cmul(qr[k], qi[k], qr[o], qi[o], eLr, eLi); }
      put8(an + KS, qr, qi);
    } else if (j == 1) {
#pragma unroll
      for (int k = 0; k < 5; ++k) cmul(qr[k], qi[k], qr[k ? k - 1 : 6], qi[k ? k - 1 : 6], eLr, eLi);
      put8(an + 2 * KS, qr, qi);
    }
  }
  PROF(3, a_tab);
}

DEV void sts16_if(uint32_t a, uint32_t v, bool c) { asm volatile("{.reg .pred q; .reg .b16 h; setp.ne.u32 q,%2,0; cvt.u16.u32 h,%1; @q st.shared.u16 [%0],h;}" :: "r"(a), "r"(v), "r"((uint32_t)c) : "memory"); }
DEV void sts1_if(uint32_t a, uint32_t v, bool c) { asm volatile("{.reg .pred q; setp.ne.u32 q,%2,0; @q st.shared.u32 [%0],%1;}" :: "r"(a), "r"(v), "r"((uint32_t)c) : "memory"); }
DEV void taps(uint32_t dskip, int k4, int w, int lane) {
  PW(4 * k4 + w)
  [[maybe_unused]] const int layer = 0;
  fence_async_smem();
  bar_sync((k4 & 1) ? NB_WG + k4 : NB_Q, (k4 & 1) ? 128 : 448);
  float d[24];
  undef(d);
  const uint64_t da = mkdesc(SB + k4 * 32768, 1024, KS, 0);
  wg_fence();
#pragma unroll
  for (int j = 0; j < 8; ++j) wg_ss48(d, da + j * 8, da + KS / 2 + j * 8, j);
  wg_commit();
  const int b = 8 * w + (lane >> 2), t = lane & 3, id = 32 * w + lane;
  constexpr int DO = T_O - T_E;
  const uint32_t te = SM_TAP + k4 * TAP_SZ + T_E, a0 = te - 16 * b - 4 * t;
  const uint32_t a1 = a0 - 512 - 4 * t, a2 = te - 2 * (511 + b) - 64 * t, a3 = te + (T_C - T_E) - 2 * (127 + b) - 128 * t;
  wg_wait<0>();
  PROF(4, a_mma);
  {
    const uint32_t v = pack2(d[1] + d[15], d[0] + d[14] + (id ? 0.f : bflo(dskip)));
    sts1(a0 + DO - 2, v); sts16(a0 - 2, v); sts16(a0, v >> 16);
  }
  {
    const uint32_t v = pack2(d[5] + d[19], d[4] + d[18]), u = prmt(v, v, 0x3232);
    const bool lo = t < 2, k512 = id == 2;
    sts1_if(k512 ? te - 2 * 512 : a1, u, (lo && id) || k512);
    sts1_if(k512 ? te - 2 * 514 : a1 - 4, k512 ? u : v, lo || k512);
    sts1_if(k512 ? te + DO - 2 * 513 : a1 + DO - 2, u, lo || k512);
    sts16(lo ? a1 + DO - 4 : a2 + DO - 194, v);
    sts16(lo ? (id ? a1 + DO + 2 : a1) : k512 ? te + DO - 2 * 511 : a2 + DO, u);
    sts16_if(a2 - 194, v, !lo);
    sts16_if(k512 ? te + DO - 2 * 514 : a2, u, !lo);
  }
  {
    const uint32_t v = pack2(d[8] + d[22], d[9] + d[23]);
    sts16_if(id ? a3 : te - 2 * 639, v, t < 2 || id == 2);
    sts16_if(a3 - 64, v >> 16, t < 2);
    sts16_if(te + DO - 2 * 639, v, id == 0);
  }
  bar_sync(NB_WG + k4, 128);
  mbar_arrive1_if(B_K, w == 0);
}

DEV uint32_t cpy(uint32_t v, uint32_t id) {
  uint32_t d; asm volatile("prmt.b32 %0,%1,%1,%2;" : "=r"(d) : "r"(v), "r"(id)); return d;
}
DEV uint32_t uoff(int s) { return (s ^ ((s >> 3) & 3)) * 16; }
template <bool FULL> DEV void boxes(const uint32_t (&u)[10], uint32_t a, uint32_t a9, uint32_t a7, uint32_t (&pv)[4]) {
  uint32_t v[8], p[8], x[4], y[4];
#pragma unroll
  for (int j = 0; j < 8; ++j) { v[j] = prmt(u[j], u[j + 1], 0x5432); p[j] = hadd2(u[j], v[j]); }
#pragma unroll
  for (int j = 0; j < 4; ++j) { x[j] = hadd2(hadd2(p[j + 1], p[j + 2]), u[j + 3]); y[j] = hadd2(v[j + 3], p[j + 4]); }
  sts4(a + R_A5, x[0], x[1], x[2], x[3]);
  sts4(a + R_A3, y[0], y[1], y[2], y[3]);
  if (FULL) {
#pragma unroll
    for (int j = 0; j < 4; ++j) { x[j] = hadd2(x[j], hadd2(v[j], v[j + 3])); y[j] = hadd2(x[j], hadd2(u[j], u[j + 4])); pv[j] = p[j + 4]; }
    sts4(a7, x[0], x[1], x[2], x[3]);
    sts4(a9, y[0], y[1], y[2], y[3]);
  }
}
DEV uint32_t shfl_up(uint32_t v, int d) { uint32_t r; asm volatile("shfl.sync.up.b32 %0,%1,%2,0,0xffffffff;" : "=r"(r) : "r"(v), "r"(d) : "memory"); return r; }
DEV void halo(uint32_t (&u)[10], uint32_t a, uint32_t b, int lane) {
  asm volatile("{.reg .pred p,q; setp.eq.s32 p,%8,0; setp.lt.s32 q,%8,2;\n@p ld.shared.v4.u32 {%2,%3,%4,%5},[%6];\n@q ld.shared.v2.u32 {%0,%1},[%7];}"
    : "+r"(u[0]), "+r"(u[1]), "+r"(u[2]), "+r"(u[3]), "+r"(u[4]), "+r"(u[5]) : "r"(a), "r"(b), "r"(lane));
}
#define W1 4
#define ROT 2
#define G1 -1
#define G2 1
#define G3 8
#define TPS 0x7134
#define GMASK ((G1 >= 0 ? 2 : 0) | (G2 >= 0 ? 4 : 0) | (G3 >= 0 ? 8 : 0))
#define GATE1(g, n, p) if (g >= 0 && (g & 3) == p) mbar_arrive1_if(B_G + 8 * n, k4 == (g >> 2));
#define GATE(p) GATE1(G1, 0, p) GATE1(G2, 1, p) GATE1(G3, 2, p)
#define TMASK(p) (((TPS & 15) == p) | ((((TPS >> 4) & 15) == p) << 1) | ((((TPS >> 8) & 15) == p) << 2) | ((((TPS >> 12) & 15) == p) << 3))
#define TURN(p) if (TMASK(p) == 15) bar_arrive(NB_T + 1 + k4, 256); else if (TMASK(p)) { if ((TMASK(p) >> k4) & 1) bar_arrive(NB_T + 1 + k4, 256); }
DEV void w_load(const CUtensorMap* mW, int cg, int h) {
  mbar_expect1(B_W + 8 * h, 24576);
  tma3(SM_S0 + (h & 3) * 24576, mW, 64 * cg, 64 * h, B_W + 8 * h);
}

DEV void conv(const Params& P, const CUtensorMap* mW, int c, int k4, int w, int layer) {
  const uint32_t zero = P.zero;
  PW(4 * k4 + w)
  int lane = lane_here(zero);
  const int g = lane >> 2, t = lane & 3, v = w ^ (ROT * (k4 & 1)), tid = 32 * v + lane;
  const uint32_t reg = SM_R + k4 * 16384, tp = SM_TAP + k4 * TAP_SZ;
  const uint32_t g0 = tp + ((g & 1) ? T_O : T_E) + 2 * (2 * t - g);
  uint32_t F[18][4], U[20], qc[4][4];
#define LO(q, a) q[0] = lds1(a); q[2] = lds1(a + 16);
#define HI(q, a) q[1] = lds1(a - 128); q[3] = lds1(a - 112);
  {
    const uint32_t ga = g0 - 32 * (w & 1) - 576 * (w >> 1), g2 = tp + T_C - 258 - 32 * w + 4 * (t - g);
    F[0][2] = lds1(ga + 48);
#pragma unroll
    for (int j = 0; j < 8; ++j) { F[j][0] = lds1(ga + 32 - 32 * j); F[j][1] = lds1(ga + 16 - 32 * j); }
#pragma unroll
    for (int j = 0; j < 20; ++j) U[j] = lds1(ga - 224 - 16 * j);
#pragma unroll
    for (int j = 0; j < 4; ++j) { LO(qc[j], g2 + 32 * j) HI(qc[j], g2 + 32 * j) }
  }
  if (layer) { mbar_wait(B_ED, 0); mbar_wait(B_ED + 8, 0); }
  sts4z_if(reg + lane * 16 + (w ? w * 3584 + 1024 : 0), w < 3);
  PROF(5, a_pre);
  if (k4 == 3 && w == 3) {
    mbar_wait(B_E, layer);
    mbar_wait(B_K, 0);
#pragma unroll
    for (int h = 0; h < 4; ++h) w_load(mW, c & 7, h);
  }
  const uint32_t bo = reg + R_B + tid * 16 + (v >> 1) * 1056, be = tid == 127 ? reg + R_B + 1024 : bo + (tid == 63 ? 2112 : 1056);
  const uint32_t a9 = (lane & 1) ? be : bo, a7 = (lane & 1) ? bo : be, ua = reg + R_U + uoff(tid);
  const uint32_t h1 = reg + R_U + v * 512 - 64, h2 = h1 + 24 - 16 * lane;
  keep(a9 & a7 & ua & h2, zero);
  mbar_wait(k4 && ((GMASK >> k4) & 1) ? B_G - 8 + 8 * k4 : B_E, layer);
  PROF(6, a_x);
  uint4 x[2];
  uint32_t pv[4];
  {
    uint4 s[4];
    uint32_t u[2][10];
#pragma unroll
    for (int z = 0; z < 2; ++z) { x[z] = lds4(reg + R_B + tid * 16 + z * 2048); s[2 * z] = lds4(SM_RES + tid * 16 + z * 2048); s[2 * z + 1] = lds4(SM_RES + tid * 16 + z * 2048 + 4096); }
    for (int it = 0;; ++it) {
      const uint32_t m = min(min(min((both(x[0].x, x[1].x, layer) | lane) & 1, min(s[0].x, s[0].z)), min(s[1].x, s[1].z)), min(min(s[2].x, s[2].z), min(s[3].x, s[3].z)));
      if (__builtin_expect(__all_sync(0xffffffffu, m != 0u), 1)) break;
      EVENT(16 + layer * 4 + k4);
      const int o = tid | here(zero);
#pragma unroll
      for (int z = 0; z < 2; ++z) x[z] = ldr4(&P.S->XG[(128 * k4 + c) * 256 + o] + z * 128);
#pragma unroll
      for (int z = 0; z < 4; ++z) {
        s[z] = ldr4(&P.S->SR[layer][c >> 4][o] + ((z >> 1) * 128 + (z & 1) * 256));
        sts4(SM_RES + tid * 16 + (z >> 1) * 2048 + (z & 1) * 4096, s[z].x, s[z].y, s[z].z, s[z].w);
      }
      spin_guard(it);
    }
#pragma unroll
    for (int z = 0; z < 2; ++z) {
      u[z][6] = hmul2(hsub2(x[z].x, s[2 * z].y), s[2 * z].x); u[z][7] = hmul2(hsub2(x[z].y, s[2 * z].w), s[2 * z].z);
      u[z][8] = hmul2(hsub2(x[z].z, s[2 * z + 1].y), s[2 * z + 1].x); u[z][9] = hmul2(hsub2(x[z].w, s[2 * z + 1].w), s[2 * z + 1].z);
      sts4(ua + z * 2048, u[z][6], u[z][7], u[z][8], u[z][9]);
    }
    u[1][0] = 0; u[1][1] = s[3].x; u[1][2] = s[2].x; u[1][3] = s[2].y; u[1][4] = s[2].z; u[1][5] = s[2].w;
    if (v < 2) {
#pragma unroll
      for (int j = 1; j < 6; ++j) u[1][j] = shfl_up(u[1][j < 2 ? 8 + j : 4 + j], j < 2 ? 2 : 1);
    }
#pragma unroll
    for (int j = 0; j < 6; ++j) u[0][j] = shfl_up(u[0][j < 2 ? 8 + j : 4 + j], j < 2 ? 2 : 1);
    bar_sync(NB_WG + k4, 128);
    GATE(0)
    PROF(7, a_u);
    halo(u[0], h1, h2, lane);
    halo(u[1], h1 + 2048, h2 + 2048, lane + 16 * (v & 2));
    sts4z_if(reg + R_B + 1040, tid == 0);
    boxes<true>(u[0], reg + tid * 16, a9, a7, pv);
    if (v < 2) boxes<false>(u[1], reg + tid * 16 + 2048, 0, 0, pv);
  }
  GATE(1)
  fence_async_smem();
  if (k4 == 3 && w == 0) {
    const uint32_t src = SM_RES + 8192;
#pragma unroll
    for (int z = 0; z < 4; ++z) sts4(src + lane * 16 + z * 512, 0, 0, 0, 0);
    fence_async_smem();
    __syncwarp();
#pragma unroll
    for (int z = 0; z < 2; ++z) {
      bulk_store(&P.S->H[(c + 8) * 256] + z * 128, src, 2048);
      bulk_store(P.S->F + ((c >> 3) * 64 + 4 * (c & 7)) + z * 32, src, 16);
    }
    bulk_store(&P.S->PS[c * 64], src, 1024);
    bulk_store(&P.S->ST[c * 4], src, 64);
    if (c < 5) bulk_store(P.S->C + (c + 5 - 5 * layer) * 1024, src, 128 * NCOPY * NSUB);
    asm volatile("cp.async.bulk.commit_group;" ::: "memory");
  }
  const uint32_t id = opq(0x3210u);
#pragma unroll
  for (int j = 0; j < 8; ++j) { F[j][3] = cpy(F[j][0], id); if (j) F[j][2] = cpy(F[j - 1][1], id); }
  PROF(8, a_box);
  bar_sync(NB_T + k4, k4 ? 256 : 128);
  PROF(9, a_turn);
  float acc[32], f1[24], f3[16];
  uint32_t qa[4][4], qb[4][4], fp[4];
  const uint64_t db = mkdesc(reg + R_U, 16, 512, 2) + 2;
#define STEP(mm, n) wg_fence(); mm; wg_commit(); wg_wait<n>();
#define D(j, n) STEP(wg_rs64k(acc, F[j], db - 2 * j, j), n)
#define C(j, n) STEP(wg_rs32t(f3, qc[j], mkdesc(reg + R_B, 128, 1040, 0) + 16 * j, j), n)
#define NIL(q, y) { const uint32_t z = y & zero; q[2][1] = cpy(z, 0); q[2][3] = cpy(z, 1); q[3][1] = cpy(z, 2); q[3][3] = cpy(z, 3); }
#define X(j) F[j][0] = cpy(U[2 * j - 16], ix); F[j][1] = cpy(U[2 * j - 15], ix); F[j][3] = cpy(F[j][0], ix); F[j][2] = cpy(F[j - 1][1], ix);
  const uint32_t g1 = g0 - 2 * 576 - 16 * w;
  const uint64_t d1 = mkdesc(reg + R_A5, 128, 512, 0);
  constexpr int O3 = (R_A3 - R_A5) / 16;
  uint32_t ix = id;
  undef(acc);
  D(0, 4) TURN(0) D(1, 4) D(2, 4) D(3, 4) D(4, 4) D(5, 2)
  undef(f3);
  C(0, 3) C(1, 3) TURN(1) C(2, 3) X(8) C(3, W1) X(9) LO(qa[0], g1)
  D(6, W1) HI(qa[0], g1) X(10) D(7, W1) LO(qa[1], g1 + 32) X(11) D(8, W1) HI(qa[1], g1 + 32) D(9, 4) LO(qa[2], g1 - 64)
  fp[0] = pack2(f3[0], f3[1]); fp[1] = pack2(f3[4], f3[5]); fp[2] = pack2(f3[8] + f3[2], f3[9] + f3[3]); fp[3] = pack2(f3[12] + f3[6], f3[13] + f3[7]);
  ix |= fp[0] & fp[1] & fp[2] & fp[3] & zero;
  X(12) D(10, 4) TURN(2) LO(qa[3], g1 - 32) X(13) X(14) D(11, 4) LO(qb[0], g1 - 192) X(15) D(12, 4) HI(qb[0], g1 - 192) X(16)
  D(13, 4) LO(qb[1], g1 - 160) X(17) D(14, 4) TURN(3) HI(qb[1], g1 - 160) NIL(qa, qa[1][0])
  D(15, 4) LO(qb[2], g1 - 256) D(16, 3) LO(qb[3], g1 - 224) NIL(qb, qa[1][1]) D(17, 2) TURN(4)
  PROF(10, a_den);
  undef(f1);
  wg_fence();
#pragma unroll
  for (int j = 0; j < 4; ++j) wg_rs48t(f1, qa[j], d1 + 16 * (j & 1) - 32 * (j >> 1), j);
  wg_commit();
  wg_wait<1>();
  TURN(5)
  wg_fence();
#pragma unroll
  for (int j = 0; j < 4; ++j) wg_rs48t(f1, qb[j], d1 + O3 + 16 * (j & 1) - 32 * (j >> 1), 1);
  wg_commit();
  TURN(6)
  lane = lane_here(zero);
  bar_sync(NB_WG + k4, 128);
  {
    const int p = (lane + 9 * (w >> 1)) & 31;
    const uint32_t ya = reg + ((w >> 1) ? R_B : R_U) + p * 64 + (((2 * (w & 1)) ^ ((p >> 1) & 3)) * 16), up = p < lane ? 2048 : 0;
#pragma unroll
    for (int z = 0; z < 4; ++z) {
      const float* a = acc + 16 * (z >> 1) + 2 * (z & 1);
      stsm4t((ya + (up ^ ((z >> 1) * 2048))) ^ ((z & 1) * 16), pack2(a[0], a[1]), pack2(a[4], a[5]), pack2(a[8], a[9]), pack2(a[12], a[13]));
    }
  }
  asm volatile("cp.async.bulk.wait_group 0;" ::: "memory");
  const uint32_t fa = reg + R_A5 + (lane >> 3) * 512 + w * 128 + (lane & 7) * 16;
  const uint32_t fc = reg + R_A3 + uoff(64 * (lane >> 4) + 16 * w + 2 * (lane & 7) + 1 - ((lane >> 3) & 1));
  uint32_t k1024 = lds16(tp + T_E - 2 * 639 + (fa & fc & zero));
  wg_wait<0>();
  GATE(2)
  PROF(11, a_far);
  bar_sync(NB_WG + k4, 128);
  stsm4(fc, fp[0], fp[1], fp[2], fp[3]);
  stsm4(fa, pack2(f1[0], f1[1]), pack2(f1[4], f1[5]), pack2(f1[8] + f1[2], f1[9] + f1[3]), pack2(f1[12] + f1[6], f1[13] + f1[7]));
  stsm2(fa + 2048, pack2(f1[16] + f1[10], f1[17] + f1[11]), pack2(f1[20] + f1[14], f1[21] + f1[15]));
  {
    const int o = 32 * v + lane;
    const uint32_t a = reg + uoff(o), b = reg + R_A5 + o * 16;
    uint4 y[2] = {hadd8(lds4(a + R_U), lds4(o >= 36 ? a + R_B : reg)), hadd8(lds4(a + R_U + 2048), lds4(a + R_B + 2048))};
    bar_sync(NB_WG + k4, 128);
    TURN(7)
    PROF(12, a_sts);
    const uint4 f = lds4(v >= 2 ? b - 1024 : reg), f2 = lds4(b + 1024);
    uint4 h = lds4(a + R_A3);
    const int e0 = (o >> 3) * 8192 + (128 * k4 + c) * 16 + (((o & 4) + ((o >> 1) & 1)) ^ (c & 7)) * 2 + (o & 1);
    const uint32_t me = (e0 & 3) == ((c >> 1) & 3), m0 = me & ~c, m1 = me & c, tag = 1 - layer;
    uint32_t* cp = cnt_at(P, 1 + 5 * layer + k4, c, lane);
    keep(cp, zero);
    k1024 = prmt(k1024, k1024, 0x1010);
    h = make_uint4(hfma2(pv[0], k1024, h.x), hfma2(pv[1], k1024, h.y), hfma2(pv[2], k1024, h.z), hfma2(pv[3], k1024, h.w));
    y[0] = hadd8(y[0], f); y[1] = hadd8(y[1], hadd8(f2, h));
    cnt_add(cp, 1 | (y[0].x & y[1].x & zero), (o ^ 96) < NCOPY);
#pragma unroll
    for (int z = 0; z < 2; ++z) {
      const uint4 r = hadd8(x[z], y[z]);
      str2((uint2*)P.S->XF + e0 + z * 131072, tagged(prmt(r.x, r.y, 0x5410), m0, tag), tagged(prmt(r.z, r.w, 0x5410), m1, tag));
      str2((uint2*)P.S->XF + (e0 ^ 4) + z * 131072, tagged(prmt(r.x, r.y, 0x7632), m0, tag), tagged(prmt(r.z, r.w, 0x7632), m1, tag));
    }
  }
  TURN(9)
  GATE(3)
  PROF(13, a_out);
}

#define WGATE 1
#define FH 1
#define QPIN 1
#define XORD 1
DEV void x_load(const Params& P, int c, int q, int layer) {
#pragma unroll
  for (int z = 0; z < 2; ++z) {
    const int e = z ^ (XORD && q == 3 && !(c & 4));
    mbar_expect1(B_X + 16 * q + 8 * e, 16384);
    bulk(xstage(q, e), P.S->XF + ((2 * (c >> 3) + 1 - e) * 4096 + q * 1024), 16384, B_X + 16 * q + 8 * e);
  }
}

DEV void means(uint32_t (&m)[4], int row, int lane, int layer, uint32_t zero) {
  mbar_wait(B_CS, 0);
  mbar_wait(B_ST, layer);
  const uint32_t a = SM_MISC + row * 4 + (lane & 28), k = (lane & 3) ? 0u : ~0u;
  m[0] = lds1(a) & k; m[1] = lds1(a + 32) & k; m[2] = m[0] & zero; m[3] = m[1] & zero;
}

DEV void attn_phase(const Params& P, int c, int e, int w, int lane, int layer) {
  PW(4 * e + w)
  const int cg = c & 7, J = 2 * (c >> 3) + 1 - e;
  float acc[96];
  zerov(acc);
  uint32_t m[4] = {0, 0, 0, 0};
#pragma unroll 1
  for (int q = 0;; ++q) {
    const uint64_t da = mkdesc(xstage(q, e), 16, 1024, 1), db = mkdesc(SM_S0 + (q & 1) * 49152, 8192, 1024, 1);
    const uint32_t wr = mbar_test2(B_W + 16 * q, layer), xa = xstage(q, e) + w * 4096 + lane * 132;
    mbar_wait(B_X + 16 * q + 8 * e, layer);
    for (int it = 0;; ++it) {
      const uint32_t ok = both(lds1(xa), lds1(xa ^ 32), layer) & both(lds1(xa ^ 64), lds1(xa ^ 96), layer);
      if (__all_sync(0xffffffffu, ok & 1)) break;
      EVENT(8 * layer + 2 * q + e);
#pragma unroll 1
      for (int j = 0; j < 8; ++j) cp16(xstage(q, e) + w * 4096 + j * 512 + lane * 16, P.S->XF + (J * 4096 + q * 1024 + w * 256 + j * 32 + lane));
      asm volatile("cp.async.wait_all;" ::: "memory");
      fence_async_smem();
      __syncwarp();
      spin_guard(it);
    }
    bool all = __all_sync(0xffffffffu, wr);
    if (q == 0 && e && w == 0) {
      bar_sync(NB_H, 256);
      cnt_wait(P, 2 + 5 * layer, c, lane);
      x_load(P, c, 1, layer);
      PROF(27, m_xi);
    }
    if (q == 3 && e) means(m, 16 * w, lane, layer, P.zero);
    if (!all) { mbar_wait(B_W + 16 * q, layer); all = mbar_test(B_W + 16 * q + 8, layer); }
    bar_sync(e ? NB_Q : q ? NB_T : NB_T + 4, 256);
    PROF(14 + q, m_q);
    wg_fence();
#pragma unroll
    for (int k = 0; k < 8; ++k) {
      if (k == 4) { wg_commit(); if (!all) mbar_wait(B_W + 16 * q + 8, layer); wg_fence(); }
      wg_ss192(acc, da + k * 128, db + (k >> 2) * 1536 + (k & 3) * 128, 1);
    }
    wg_commit();
    if (q == 3) break;
    bar_arrive(e ? NB_T : NB_Q, 256);
    if (FH) { wg_wait<1>(); mbar_arrive1_if(B_FH + 8 * q, e && q < 2); }
    wg_wait<0>();
    mbar_arrive1(B_F + 8 * q);
  }
  const int pos = 2 - 2 * e + (w >> 1);
  uint4* h = P.S->H + ((c + 8) * 256 + (w & 1) * 128 + lane);
  const uint32_t kw = kvslot(cg, pos + 1) + (w & 1) * 2048 + lane * 16;
  {
    if (!e) means(m, 64 + 16 * w, lane, layer, P.zero);
    PROF(28, m_sub);
    wg_fence();
    wg_rs192t(acc, m, mkdesc(SM_CS, 0, 32, 0));
    wg_commit();
    bar_arrive_if(NB_Q, 256, !e);
    keep(h, kw & P.zero);
    mbar_wait(B_F + 16, layer);
    wg_wait<0>();
    mbar_arrive1(B_F + 24);
  }
  PROF(18, m_qkv);
  uint32_t Q[4][4], K[4][3][2], V[4][3][2];
  uint32_t pin = P.zero;
#pragma unroll
  for (int z = 0; z < 4; ++z) {
    V[z][1][0] = pack2(acc[64 + 8 * z], acc[65 + 8 * z]); V[z][1][1] = pack2(acc[68 + 8 * z], acc[69 + 8 * z]);
    K[z][1][0] = pack2(acc[32 + 8 * z], acc[33 + 8 * z]); K[z][1][1] = pack2(acc[36 + 8 * z], acc[37 + 8 * z]);
    pin &= V[z][1][0] & V[z][1][1];
    K[z][2][0] = nz(pack2(acc[34 + 8 * z], acc[35 + 8 * z])); K[z][2][1] = pack2(acc[38 + 8 * z], acc[39 + 8 * z]);
    V[z][2][0] = pack2(acc[66 + 8 * z], acc[67 + 8 * z]); V[z][2][1] = pack2(acc[70 + 8 * z], acc[71 + 8 * z]);
    str4_if(h + z * 32, K[z][2][0], K[z][2][1], V[z][2][0], V[z][2][1], pos == 3);
  }
#pragma unroll
  for (int z = 0; z < 8; ++z) V[z >> 1][2][z & 1] = movm(z < 7 ? V[z >> 1][2][z & 1] : V[3][2][1] | pin);
  if (pos == 0) mbar_wait(B_F + 24, layer);
#pragma unroll
  for (int z = 0; z < 4; ++z) sts4_if(kw + z * 512, K[z][2][0], K[z][2][1], V[z][2][0], V[z][2][1], pos < 3);
  bar_arrive(NB_H + pos + 1, 128);
  PROF(19, m_kv);
  lane |= here(P.zero);
  int g = lane >> 2, t = lane & 3;
  const uint32_t ra = SM_STAT + 256 + (32 - 32 * e + 8 * w) * 16, ob = e ? SM_S1 : SM_XA;
  const float r0 = lds1f(ra + (g >> 1) * 16 + (g & 1) * 4), r1 = lds1f(ra + 64 + (g >> 1) * 16 + (g & 1) * 4);
  const uint4 k1 = lds4(ra + 16 * t), k2 = lds4(ra + 64 + 16 * t);
#pragma unroll
  for (int z = 0; z < 8; ++z) {
    V[z >> 1][1][z & 1] = movm(V[z >> 1][1][z & 1]);
    Q[z >> 1][2 * (z & 1)] = pack2(acc[4 * z], acc[4 * z + 1]);
    Q[z >> 1][2 * (z & 1) + 1] = pack2(acc[4 * z + 2], acc[4 * z + 3]);
    pin &= Q[z >> 1][2 * (z & 1)] & Q[z >> 1][2 * (z & 1) + 1];
  }
  {
    const bool p0 = 2 * t > g, p1 = 2 * t + 1 > g, first = c < 8 && pos == 0;
    const uint32_t M = (p0 ? 0xFFFFu : 0u) | (p1 ? 0xFFFF0000u : 0u);
    const float sc0 = r0 * (0.25f * 1.4426950408889634f), sc1 = r1 * (0.25f * 1.4426950408889634f);
    const float sk2 = __uint_as_float(p0 ? k1.x : k2.x) * sc1, sk3 = __uint_as_float(p1 ? k1.y : k2.y) * sc1;
    const int oo = cg * 512 + (2 * (w & 2) + (w & 1)) * 64 + (lane ^ (g >> 1));
    uint4* O = P.S->O + (J * 4096 + oo);
    keep(oo, pin & M & __float_as_uint(sk2) & __float_as_uint(sk3) & __float_as_uint(sc0));
    mbar_wait(B_F + 24, layer);
    float L[4][4];
#pragma unroll
    for (int z = 0; z < 4; ++z) {
      float S[4];
      mma16z(L[z], Q[z][0], Q[z][1], Q[z][2], Q[z][3], K[z][1][0], K[z][1][1]);
      mma16z(S, Q[z][0], Q[z][1], Q[z][2], Q[z][3], K[z][2][0], K[z][2][1]);
      L[z][2] = (p0 ? L[z][2] : S[2]) * sk2; L[z][3] = (p1 ? L[z][3] : S[3]) * sk3;
      if (QPIN) pin &= __float_as_uint(L[z][2]) & __float_as_uint(L[z][3]);
    }
    bar_sync(NB_H + pos + pin, pos ? 128 : 160);
    const uint4 k0 = lds4(ra - 192 + 16 * t);
#pragma unroll
    for (int z = 0; z < 4; ++z) {
      const uint4 hv = lds4(kvslot(cg, pos) + (w & 1) * 2048 + lane * 16 + z * 512);
      K[z][0][0] = hv.x; K[z][0][1] = hv.y; V[z][0][0] = hv.z; V[z][0][1] = hv.w;
    }
    PROF(20, m_halo);
    const float sk0 = __uint_as_float(p0 ? k0.x : k1.x) * sc0, sk1 = __uint_as_float(p1 ? k0.y : k1.y) * sc0;
    const uint32_t rm[4] = {k0.z & M, k1.z & ~M, k1.z & M, k2.z & ~M}, s0 = k0.w | P.zero, s1 = k1.w | P.zero;
#pragma unroll
    for (int h2 = 0; h2 < 2; ++h2) {
      uint32_t A[2], B[2], mx[2];
#pragma unroll
      for (int z = 0; z < 2; ++z) {
        const int h = 2 * h2 + z;
        float S[4];
        mma16z(S, Q[h][0], Q[h][1], Q[h][2], Q[h][3], K[h][0][0], K[h][0][1]);
        if (first) { S[0] = __uint_as_float(0xFF800000u); S[1] = S[0]; }
        A[z] = pack2((p0 ? S[0] : L[h][0]) * sk0, L[h][2]);
        B[z] = pack2((p1 ? S[1] : L[h][1]) * sk1, L[h][3]);
      }
#pragma unroll
      for (int z = 0; z < 2; ++z) mx[z] = hmax2(A[z], B[z]);
#pragma unroll
      for (int z = 0; z < 2; ++z) mx[z] = hmax2(mx[z], __shfl_xor_sync(0xffffffffu, mx[z], 1));
#pragma unroll
      for (int z = 0; z < 2; ++z) mx[z] = hmax2(mx[z], __shfl_xor_sync(0xffffffffu, mx[z], 2));
      float Oa[2][3][4];
#pragma unroll
      for (int z = 0; z < 2; ++z) {
        const int h = 2 * h2 + z;
        const uint32_t a = hsub2(A[z], mx[z]), b = hsub2(B[z], mx[z]);
        const uint32_t w0 = pack2(ex2(bflo(a)), ex2(bflo(b))), w1 = pack2(ex2(bfhi(a)), ex2(bfhi(b)));
        const uint32_t u0 = hmul2(w0, rm[0]), u1 = hmul2(w0, rm[1]), u2 = hmul2(w1, rm[2]), u3 = hmul2(w1, rm[3]);
        const uint32_t z0 = w0 & P.zero, z1 = w1 & P.zero;
        mma16z(Oa[z][2], u0, z0, u1, u2, s0, s1);
#pragma unroll
        for (int d = 0; d < 2; ++d) mma16z(Oa[z][d], u0, z0, u1, u2, V[h][0][d], V[h][1][d]);
        mma8(Oa[z][2], z1, u3, k2.w);
#pragma unroll
        for (int d = 0; d < 2; ++d) mma8(Oa[z][d], z1, u3, V[h][2][d]);
      }
#pragma unroll
      for (int r = 0; r < 4; r += 2) {
        const float i0 = rcp(Oa[0][2][r]), i1 = rcp(Oa[1][2][r]);
        const uint32_t o0 = pack2(Oa[0][0][r] * i0, Oa[0][0][r + 1] * i0), o1 = pack2(Oa[0][1][r] * i0, Oa[0][1][r + 1] * i0);
        const uint32_t o2 = pack2(Oa[1][0][r] * i1, Oa[1][0][r + 1] * i1), o3 = pack2(Oa[1][1][r] * i1, Oa[1][1][r + 1] * i1);
        str4(O + h2 * 32 + r * 64, o0, o1, o2, o3);
        sts4(ob + oo * 16 + h2 * 512 + r * 1024, o0, o1, o2, o3);
      }
    }
  }
  bar_arrive(NB_T + 1 + e, 160);
  fence_async_smem();
  PROF(21, m_att);
  lane = lane_here(P.zero); g = lane >> 2; t = lane & 3;
  uint32_t res[8][2];
  mbar_wait(B_RES, layer);
  {
    const uint32_t a = SM_RES + e * 8192 + (lane >> 4) * 1024 + (lane & 7) * 128 + (((2 * (w & 2) + ((lane >> 2) & 2) + (w & 1)) ^ (lane & 7)) * 16);
#pragma unroll
    for (int j = 0; j < 8; j += 2) ldsm4t(res[j][0], res[j][1], res[j + 1][0], res[j + 1][1], a + j * 1024);
  }
  PROF(26, m_res);
  if (WGATE) bar_sync(NB_T, 256); else bar_sync(NB_WG + e, 128);
  XgAddr xa = xg_addr<true>(P.S->XG + (64 * cg * 256 + 8 * J), ob, w, lane, P.zero);
  uint4* ps = &P.S->PS[((4 * J + w) * 8 + cg) * 8 + g];
  keep(ps, P.zero);
  if (layer) {
    xa.a = ob + w * 2048 + (lane & 15) * 128 + (((lane >> 4) ^ (lane & 7)) * 16);
    xa.b = ob + w * 2048 + (lane >> 3) * 128 + (((lane & 7) ^ (lane >> 3)) * 16);
    xa.dst = (uint4*)P.out + ((64 * J + 16 * w + 2 * (lane >> 3)) * 64 + 8 * cg + (lane & 7));
  }
  uint32_t y[8][2];
#pragma unroll 1
  for (int it = 0;; ++it) {
    float ac[32];
#pragma unroll
    for (int j = 0; j < 16; ++j) {
      asm volatile("shl.b32 %0,%1,16;" : "=f"(ac[2 * j]) : "r"(res[j >> 1][j & 1]));
      asm volatile("and.b32 %0,%1,0xFFFF0000;" : "=f"(ac[2 * j + 1]) : "r"(res[j >> 1][j & 1]));
    }
#pragma unroll 1
    for (int n = 0; n < 8; ++n) {
      const int s = n == 0 ? cg : n - (n <= cg);
      mbar_wait(n ? B_O + 64 * e + 8 * s : B_WO, layer);
      if (n == 1) PROF(22, m_o1);
      if (n == 7) PROF(23, m_o7);
      const uint64_t da = mkdesc(ob + s * 8192, 16, 1024, 2), db = mkdesc(SM_R + s * 8192, 16, 1024, 1);
      wg_fence();
#pragma unroll
      for (int k = 0; k < 4; ++k) wg_ss64(ac, da + (k >> 1) * 32 + (k & 1) * 2, db + k * 128, 1);
      wg_commit();
    }
    wg_wait<0>();
    const bool bad = ac[0] != ac[0] || ac[2] != ac[2];
#pragma unroll
    for (int j = 0; j < 8; ++j) {
      y[j][0] = pack2(ac[4 * j], ac[4 * j + 1]); y[j][1] = pack2(ac[4 * j + 2], ac[4 * j + 3]);
    }
    if (!bar_any(NB_WG + e, 128, bad) || it == 16) break;
    EVENT(24 + 2 * layer + e);
    refetch(ob, P.S->O + J * 4096, 32768, e, w);
  }
  PROF(24, m_wo);
  if (layer == 0) {
    const float4 s = gram(y, g, P.zero);
    xg_put<true>(xa, y);
    str4_if(ps, nz(__float_as_uint(s.x)), __float_as_uint(s.y), __float_as_uint(s.z), __float_as_uint(s.w), t == (g >> 1));
    mbar_arrive1(B_ED + 8 * e);
    bar_sync(NB_WG + e, 128);
    xg_store(xa, 0);
    bar_arrive(NB_T + 3, 288);
  } else {
#pragma unroll
    for (int j = 0; j < 8; j += 2) stsm4(xa.a ^ (j * 16), y[j][0], y[j][1], y[j + 1][0], y[j + 1][1]);
    __syncwarp();
#pragma unroll
    for (int k = 0; k < 4; ++k) {
      const uint4 v = lds4((xa.b ^ ((k & 1) * 64)) + k * 512);
      stw4(xa.dst + ((k & 1) * 8 + (k >> 1)) * 64, v.x, v.y, v.z, v.w);
    }
  }
  PROF(25, m_epi);
}

#define HDELAY 300
#define ODELAY 200
#define FDELAY 300
#define CSP 0
#define CSU 8
#define SYNC0 1
#define PAR3 0
#define PZB B_X + 48
#define WOQ 2
#define H5 1
#define SRDELAY 350

DEV void o_load(const Params& P, int c, int e, int lane, int layer) {
  PW(8 + e)
  const int J = 2 * (c >> 3) + 1 - e;
#pragma unroll 1
  for (int s = 0; s < 8; ++s) mbar_expect1(B_O + 64 * e + 8 * s, s == (c & 7) ? 0 : 8192);
  const uint4* src = P.S->O + J * 4096;
  const uint32_t* fp = P.S->F + (J * 32 + (lane & 28));
  keep(fp, P.zero);
  bar_sync(NB_T + 1 + e, 160);
  flag_set1(P.S->F + (J * 32 + 4 * (c & 7)));
  if (ODELAY) delay(ODELAY);
  PROF(26, a_go);
  poll(fp, 1);
  PROF(25, h_seen);
  bar_sync_if(NB_Q, 64, e);
#pragma unroll 1
  for (int n = 0; n < 7; ++n) {
    const int s = n + (n >= (c & 7));
    bulk((e ? SM_S1 : SM_XA) + s * 8192, src + s * 512, 8192, B_O + 64 * e + 8 * s);
  }
  bar_arrive_if(NB_Q, 64, !e);
  PROF(28, a_o);
}

DEV void stats(const Params& P, int c, int w, int lane, int layer) {
  PW(12 + w)
  lane = opq(lane);
  const int r = 2 * (lane >> 3), k = (2 * (c & 3) + ((lane >> 2) & 1)) ^ r, e = 1 - ((c >> 2) & 1);
  const uint32_t o = (32 * w + r) * 128 + k * 16 + (lane & 3) * 4;
  const uint32_t no0 = (lane & 7) != r, no1 = ((lane & 7) ^ 4) != r + 1;
  uint32_t* st = (uint32_t*)P.S->ST + (16 * c + 2 * (lane & 7) + (lane >> 4));
  keep(st, P.zero);
  float v[4] = {0.f, 0.f, 0.f, 0.f};
#pragma unroll 1
  for (int q = 0; q < 4; ++q) {
    mbar_wait(B_X + 16 * q + 8 * e, layer);
    PROF(19 + q, s_l);
    uint32_t x[8];
    for (int it = 0;; ++it) {
#pragma unroll
      for (int z = 0; z < 8; ++z) x[z] = lds1v(xstage(q, e) + (o ^ ((z & 1) * 144)) + (z >> 1) * 1024);
      const uint32_t ok = (both(x[0], x[2], layer) & both(x[4], x[6], layer) | no0) & (both(x[1], x[3], layer) & both(x[5], x[7], layer) | no1);
      if (__all_sync(0xffffffffu, ok & 1)) break;
      spin_guard(it);
    }
    mbar_arrive1(B_F + 8 * q);
#pragma unroll
    for (int z = 0; z < 8; ++z) {
      const float lo = bflo(x[z]), hi = bfhi(x[z]);
      v[0] += lo; v[1] += lo * lo; v[2] += hi; v[3] += hi * hi;
    }
  }
  PROFD(14, s_part, __float_as_uint(v[0]));
  fold<2>(v, lane, 16); fold<1>(v, lane, 8);
  PROFD(16, s_fold, __float_as_uint(v[0]));
  if (w) {
    sts1(SM_MISC - 128 + w * 128 + lane * 4, __float_as_uint(v[0]));
    bar_arrive(NB_P, 128);
  } else {
    mbar_wait(B_ST + 8, layer);
    bar_sync(NB_P, 128);
    v[0] += lds1f(SM_MISC + lane * 4) + lds1f(SM_MISC + 128 + lane * 4) + lds1f(SM_MISC + 256 + lane * 4);
    float m;
    const float sd = ln_sd(v[0], __shfl_xor_sync(0xffffffffu, v[0], 8), m);
    if (!(lane & 8)) str1(st, pack2(m, sd));
    PROF(17, s_pub);
    uint4 s;
    for (int it = 0;; ++it) {
      s = ldr4(P.S->ST + ((c >> 3) * 32 + lane));
      if (__all_sync(0xffffffffu, min4(s) != 0u)) break;
      spin_guard(it);
    }
    PROF(18, s_seen);
    const float r0 = rcp(bfhi(s.x)), r1 = rcp(bfhi(s.y)), r2 = rcp(bfhi(s.z)), r3 = rcp(bfhi(s.w));
    const uint32_t sg = 0x80008000u;
    sts4(SM_MISC + lane * 16, prmt(s.x, s.x, 0x1010) ^ sg, prmt(s.y, s.y, 0x1010) ^ sg, prmt(s.z, s.z, 0x1010) ^ sg, prmt(s.w, s.w, 0x1010) ^ sg);
    sts4(SM_STAT + 256 + lane * 32, __float_as_uint(r0), __float_as_uint(r1), pack2(r0, r1), prmt(s.x, s.y, 0x7632));
    sts4(SM_STAT + 272 + lane * 32, __float_as_uint(r2), __float_as_uint(r3), pack2(r2, r3), prmt(s.z, s.w, 0x7632));
    __syncwarp();
    mbar_arrive1(B_ST);
  }
  PROF(15, s_stat);
  if (w == 1) {
    mbar_wait(B_ST, layer);
    if (c >= 8) {
      uint2 s;
      for (int it = 0;; ++it) {
        s = ldr2((const uint2*)P.S->ST + ((c >> 3) * 64 - 12 + (lane & 11)));
        if (__all_sync(0xffffffffu, min(s.x, s.y) != 0u)) break;
        spin_guard(it);
      }
      const float r0 = rcp(bfhi(s.x)), r1 = rcp(bfhi(s.y));
      sts4(SM_STAT + 64 + (lane & 11) * 16, __float_as_uint(r0), __float_as_uint(r1), pack2(r0, r1), prmt(s.x, s.y, 0x7632));
    }
    bar_arrive(NB_H, 160);
  }
  if (w >= 2) {
    const uint4* h = P.S->H + (c * 256 + (w & 1) * 128 + lane);
    uint4 hv[4];
#pragma unroll
    for (int z = 0; z < 4; ++z) hv[z] = make_uint4(0, 0, 0, 0);
    bar_sync(NB_RL, 128);
    PROFD(26, s_hb, lds1v(SM_MISC));
    delay(HDELAY);
    for (int it = 0; c >= 8; ++it) {
#pragma unroll
      for (int z = 0; z < 4; ++z) hv[z] = ldr4(h + z * 32);
      if (__all_sync(0xffffffffu, min(min(hv[0].x, hv[1].x), min(hv[2].x, hv[3].x)) != 0u)) break;
      spin_guard(it);
    }
    mbar_wait(B_F + 24, layer);
#pragma unroll
    for (int z = 0; z < 4; ++z) sts4(kvslot(c & 7, 0) + (w & 1) * 2048 + lane * 16 + z * 512, hv[z].x, hv[z].y, movm(hv[z].z), movm(hv[z].w));
    bar_arrive(NB_H, 160);
    PROF(25, s_halo);
  }
}

DEV void finalize(const Params& P, int c, int lane, int layer) {
  PW(12)
  uint2* so = (uint2*)P.S->SR[layer] + ((lane >> 3) * 1024 + (lane & 2) * 256 + 4 * c + ((lane >> 1) & 2) + (lane & 1));
  const uint4* ps = &P.S->PS[c * 64 + lane];
  keep(so, P.zero); keep(ps, P.zero);
  uint4 a, b;
  if (layer == 0) {
    bar_sync(NB_P, 256);
    a = lds4(SM_RES + 8192 + lane * 16); b = lds4(SM_RES + 8704 + lane * 16);
  } else {
    mbar_wait(B_ED + 8 - 2 * (c & 4), 0);
    delay(FDELAY);
    for (int it = 0;; ++it) {
      a = ldr4(ps); b = ldr4(ps + 32);
      if (__all_sync(0xffffffffu, min(a.x, b.x) != 0u)) break;
      spin_guard(it);
    }
  }
  float z[4] = {__uint_as_float(a.x) + __uint_as_float(b.x), __uint_as_float(a.y) + __uint_as_float(b.y),
                __uint_as_float(a.z) + __uint_as_float(b.z), __uint_as_float(a.w) + __uint_as_float(b.w)};
#pragma unroll
  for (int o = 8; o < 32; o <<= 1)
#pragma unroll
    for (int k = 0; k < 4; ++k) z[k] += __shfl_xor_sync(0xffffffffu, z[k], o);
  const float m0 = z[0] * (1.f / 512.f), m1 = z[2] * (1.f / 512.f);
  const float r0 = rsq(fmaxf(z[1] * (1.f / 512.f) - m0 * m0, 0.f) + 1e-5f), r1 = rsq(fmaxf(z[3] * (1.f / 512.f) - m1 * m1, 0.f) + 1e-5f);
  const uint32_t wr = nz(pack2(r0, r1)), wm = pack2(m0, m1);
  str2(so, wr, wm); str2(so + 4096, wr, wm);
  bar_arrive_if(NB_Q, 448, !layer);
  PROF(23, s_sr);
}

DEV void announce(const Params& P, int c, int lane, int layer) {
  PW(13)
  uint32_t* cp = cnt_at(P, 5 * layer, c, lane);
  keep(cp, P.zero);
  bar_sync(NB_T + 3, 288);
  cnt_add(cp, 1, lane < NCOPY);
  if (!layer) { bar_sync(NB_Q, 448); fence_async_smem(); }
  PROF(24, s_own);
}

DEV void fetch(const Params& P, int c, int lane, int layer) {
  PW(13)
  mbar_expect1(B_E, 24576);
  cnt_wait(P, 5 * layer, c, lane);
#pragma unroll
  for (int k = 0; k < 4; ++k) bulk(SM_R + k * 16384 + R_B, P.S->XG + (128 * k + c) * 256, 4096, B_E);
  if (layer) delay(SRDELAY);
  bulk(SM_RES, P.S->SR[layer][c >> 4], 8192, B_E);
  if (!layer) { if (!CSP) l2_prefetch(P.wqkv + c * 6144, 12288); l2_prefetch(P.wo + c * 2048, 4096); }
  PROF(25, s_all);
}

DEV void cs_part(const Params& P, int c, int w, int lane, int layer) {
  float cs[8];
#pragma unroll
  for (int k = 0; k < 8; ++k) cs[k] = 0.f;
  const int col = w * 512 + 64 * (c & 7) + 8 * (lane & 7);
#pragma unroll 1
  for (int r = 8 * layer; r < 8; r += CSU) {
    uint4 v[CSU];
#pragma unroll
    for (int k = 0; k < CSU; ++k) v[k] = ldnc4(P.wqkv + ((32 * (c >> 3) + 4 * r + (lane >> 3)) * 1536 + col) + 4 * k * 1536);
#pragma unroll
    for (int k = 0; k < CSU; ++k) {
      cs[0] += bflo(v[k].x); cs[1] += bfhi(v[k].x); cs[2] += bflo(v[k].y); cs[3] += bfhi(v[k].y);
      cs[4] += bflo(v[k].z); cs[5] += bfhi(v[k].z); cs[6] += bflo(v[k].w); cs[7] += bfhi(v[k].w);
    }
  }
  fold<4>(cs, lane, 16); fold<2>(cs, lane, 8);
  str2((float*)P.S->CS + ((c >> 3) * 1536 + col + 2 * (lane >> 3)), max(__float_as_uint(cs[0]), 1u - layer), __float_as_uint(cs[1]));
}

DEV void cs_sum(const Params& P, int c, int w, int lane) {
  float a, b;
  for (int it = 0;; ++it) {
    uint32_t m = ~0u;
    a = b = 0.f;
#pragma unroll
    for (int k = 0; k < 16; ++k) {
      const uint2 u = ldr2((const float*)P.S->CS + (w * 512 + 64 * (c & 7) + 2 * lane) + k * 1536);
      a += __uint_as_float(u.x); b += __uint_as_float(u.y); m = min(m, u.x);
    }
    if (__all_sync(0xffffffffu, m != 0u)) break;
    spin_guard(it);
  }
  const uint32_t hi = pack2(a, b), ad = SM_CS + w * 256 + (lane >> 2) * 32 + (lane & 3) * 4;
  sts1(ad, hi); sts1(ad + 16, pack2(a - bflo(hi), b - bfhi(hi)));
  fence_async_smem();
  __syncwarp();
  mbar_arrive1(B_CS);
}

DEV void x0_get(uint32_t (&x)[8][2], uint32_t a) {
  asm volatile("cp.async.wait_group 0;" ::: "memory");
#pragma unroll
  for (int z = 0; z < 4; ++z) {
    const uint4 v = lds4(a + z * 512);
    x[2 * (z & 2)][z & 1] = v.x; x[2 * (z & 2) + 1][z & 1] = v.y; x[2 * (z & 2) + 2][z & 1] = v.z; x[2 * (z & 2) + 3][z & 1] = v.w;
  }
}

DEV void par_load(const Params& P, int ch, int m, uint32_t (&pv)[8], bool c) {
  const int mo = ch * 128 + m;
  pv[0] = ld16_if(P.Are + mo, c); pv[1] = ld16_if(P.Aim + mo, c); pv[2] = ld16_if(P.Bre + mo, c); pv[3] = ld16_if(P.Bim + mo, c);
  pv[4] = ld16_if(P.Cre + mo, c); pv[5] = ld16_if(P.Cim + mo, c); pv[6] = ld16_if(P.logdt + ch, c); pv[7] = ld16_if(P.dskip + ch, c);
}

template <bool BY_SM> __global__ void __launch_bounds__(NTHR, 1)
fused_kernel(const __grid_constant__ Params P, const __grid_constant__ CUtensorMap mapW,
             const __grid_constant__ CUtensorMap mapWo) {
  extern __shared__ __align__(1024) uint8_t smem_raw[];
  uint32_t smid; asm("mov.u32 %0,%%smid;" : "=r"(smid));
  const int role = P.role[(BY_SM ? smid : blockIdx.x) + (threadIdx.x >> 10)];
  uint32_t pv[8];
  par_load(P, (threadIdx.x & 384) + (role & 127), threadIdx.x & 127, pv, (PAR3 || threadIdx.x < 384) && role < 128);
  const int warp0 = __shfl_sync(0xffffffffu, threadIdx.x >> 5, 0), lane0 = threadIdx.x & 31, c = __shfl_sync(0xffffffffu, role, 0);
  if (c == 255) {
    if (threadIdx.x < NCOPY * NSUB)
#pragma unroll 1
      for (int it = 0; it < 256 && ldr1(P.S->C + 32 * threadIdx.x) < 128 / NSUB; ++it) __nanosleep(200);
    return;
  }
  const int cg = c & 7;
  PW(warp0)
  uint32_t dskip;
  {
    [[maybe_unused]] const int layer = 0;
    const int lane = lane0, g = lane >> 2, t = lane & 3, warp = warp0, k4 = warp >> 2, w = warp & 3;
    if (SYNC0) __syncthreads();
    const uint16_t* r = P.x0 + ((k4 < 2 ? 8192 * c + 64 * warp : (128 * (c >> 3) + 16 * (warp - 8)) * 512 + 64 * cg) + 1024 * g + 8 * t);
    const uint32_t xa = SM_R + k4 * 16384 + w * 2048 + lane * 16;
#pragma unroll
    for (int z = 0; z < 4; ++z) cp16(xa + z * 512, r + (z & 1) * 512 + (z & 2) * 16);
    asm volatile("cp.async.commit_group;" ::: "memory");
    sts4(SM_TAP + k4 * TAP_SZ + (32 * w + lane) * 16, 0, 0, 0, 0);
    sts4z_if(SM_TAP + k4 * TAP_SZ + 2048 + (32 * w + lane) * 16, w < 3);
    const XgAddr xd = xg_addr<false>(P.S->XG + (64 * cg * 256 + 16 * (c >> 3) + 8 * (k4 & 1)), SM_R + k4 * 16384 + 8192, w, lane, P.zero);
    uint32_t x[8][2];
    if (k4 == 3) {
      if (threadIdx.x == 448) {
        asm volatile("prefetch.tensormap [%0];" :: "l"(&mapW) : "memory");
        asm volatile("prefetch.tensormap [%0];" :: "l"(&mapWo) : "memory");
      }
      __syncwarp();
      if (!PAR3) par_load(P, 128 * k4 + c, 32 * w + lane, pv, true);
      if (s2u(smem_raw) != SB) __trap();
      sts4(SM_STAT - 32 + min(lane, 17) * 16, 0x3F800000u, 0x3F800000u, 0x3F803F80u, 0x3F803F80u);
      x0_get(x, xa);
      PROF(27, a_ld);
      xg_put<false>(xd, x);
      bar_sync(NB_WG + 3, 128);
      xg_store(xd, 1);
      bar_arrive(NB_T + 3, 288);
#pragma unroll
      for (int n = 0; n < 14; ++n) mbar_init1(SM_BAR + (n < 10 ? w * 80 : 240 + w * 32) + n * 8, n < 10 ? 1 : (CNT >> (8 * w + 2 * (n - 10 & 2))) & 15);
      bar_sync(NB_Q, 448);
    }
    tables(pv, k4, w, lane);
    if (k4 < 3) {
      x0_get(x, xa);
      if (k4 < 2) {
        const float4 s = gram(x, g, P.zero);
        if (t == (g >> 1)) sts4f(SM_RES + 8192 + (warp * 8 + g) * 16, s.x, s.y, s.z, s.w);
        __syncwarp();
        bar_arrive_if(NB_P, 256, warp != 7);
      } else {
        xg_put<false>(xd, x);
        bar_sync(NB_WG + 2, 128);
        xg_store(xd, 1);
        bar_arrive(NB_T + 3, 288);
      }
    }
    dskip = pv[7];
    PROF(1, a_x0);
  }
#pragma unroll 1
  for (int layer = 0; layer < 2; ++layer) {
    int lane = lane_here(P.zero);
    const int warp = warp0 | (layer & P.zero), k4 = warp >> 2, w = warp & 3;
    if (warp == (layer ? 12 : 7)) finalize(P, c, lane, layer);
    if (warp == (layer ? 13 : 6)) { announce(P, c, lane, layer); fetch(P, c, lane, layer); }
    if (layer == 0) {
      if (CSP && k4 == 1 && w != 2) { if (CSP > 1) delay(CSP); cs_part(P, c, w - (w >> 1), lane, 0); }
      taps(dskip, k4, w, lane);
    }
    conv(P, &mapW, c, k4, w, layer);
    lane = lane_here(P.zero);
    if (k4 < 2) {
      bar_arrive_if(NB_H, 256, warp != 4);
      if (warp == 0) {
        mbar_wait(B_K, 0);
        cnt_wait(P, 1 + 5 * layer, c, lane);
        x_load(P, c, 0, layer);
        PROF(27, m_xi);
      } else if (k4 == 0 && (CSP == 0 || layer)) cs_part(P, c, w - 1, lane, CSP ? 1 : layer);
      attn_phase(P, c, k4, w, lane, layer);
    } else {
      bar_arrive_if(NB_RL, 256, warp >= 10);
      if (k4 == 3) {
        stats(P, c, w, lane, layer);
      } else if (w < 2) {
        bar_sync_if(NB_RL, 256, w);
        cnt_wait(P, 3 + 5 * layer + w, c, lane);
        bar_sync_if(NB_RL, 256, !w);
        if (w) mbar_wait(B_F, layer);
        x_load(P, c, 2 + w, layer);
        if (H5 && w) w_load(&mapW, cg, 5);
        PROF(14, h_xi);
        if (w == 1) str4(&P.S->SR[layer][lane >> 2][4 * c + (lane & 3)], 0, 0, 0, 0);
      } else if (w == 2) {
        mbar_expect1(B_WO, 65536);
        mbar_expect1(B_RES, 16384);
#pragma unroll 1
        for (int q = 0; q < 4; ++q) {
          if (FH && q < 2) { mbar_wait(B_FH + 8 * q, layer); w_load(&mapW, cg, 4 + 2 * q); }
          mbar_wait(B_F + 8 * q, layer);
          if (!FH && q < 2) w_load(&mapW, cg, 4 + 2 * q);
          if (q == 1 || (q == 0 && !H5)) w_load(&mapW, cg, 5 + 2 * q);
          if (WOQ == 0 && ((q + 1) & 2)) tma5(SM_R + (q & 2) * 16384, &mapWo, 64 * cg, 4 * (q & 2), B_WO);
          if (WOQ && q == 2) {
            if (WOQ >= 2) mbar_wait(B_ST, layer);
            tma5(SM_R, &mapWo, 64 * cg, 0, B_WO);
            if (WOQ < 3) tma5(SM_R + 32768, &mapWo, 64 * cg, 8, B_WO);
          }
          if (q == 3) {
#pragma unroll
            for (int e = 0; e < 2; ++e) bulk(SM_RES + e * 8192, P.S->XF + ((2 * (c >> 3) + 1 - e) * 4096 + cg * 512), 8192, B_RES);
          }
          PROF(15 + q, h_w);
        }
      }
      if (k4 == 2 && w != 2 && layer == 0) cs_sum(P, c, w - (w >> 1), lane);
      if (warp == 11) {
#pragma unroll
        for (int z = 0; z < 8; ++z) sts4(SM_RES + 10240 + lane * 16 + z * 512, ~0u, ~0u, ~0u, ~0u);
        fence_async_smem();
        mbar_wait(PZB, layer);
#pragma unroll
        for (int z = 0; z < 4; ++z) bulk_store(&P.S->O[((c >> 3) * 16 + cg) * 512] + ((z >> 1) * 4096 + (z & 1) * 256), SM_RES + 10240, 4096);
        asm volatile("cp.async.bulk.commit_group;\ncp.async.bulk.wait_group 0;" ::: "memory");
        mbar_arrive1(B_ST + 8);
        PROF(18, h_pz);
      }
      if (warp < 10) o_load(P, c, w, lane, layer);
    }
    asm volatile("mov.b32 %0,0;" : "=r"(dskip));
  }
}

typedef CUresult (*EncodeFn)(CUtensorMap*, CUtensorMapDataType, cuuint32_t, void*, const cuuint64_t*, const cuuint64_t*,
                             const cuuint32_t*, const cuuint32_t*, CUtensorMapInterleave, CUtensorMapSwizzle,
                             CUtensorMapL2promotion, CUtensorMapFloatOOBfill);

#define PLAIN false
#define POOL 0
#define GOFF 0
static int place_roles(uint8_t* role) {
  int dev = 0, nsm = 0;
  cudaGetDevice(&dev);
  cudaDeviceGetAttribute(&nsm, cudaDevAttrMultiProcessorCount, dev);
  if (nsm < 128 || nsm > 144 || (nsm & 1)) return 0;
  cudaFuncSetAttribute(fused_kernel<true>, cudaFuncAttributeNonPortableClusterSizeAllowed, 1);
  int occ[9] = {0};
  for (int k = 2; k <= 8; ++k) {
    cudaLaunchConfig_t cfg = {};
    cudaLaunchAttribute at[1];
    at[0].id = cudaLaunchAttributeClusterDimension;
    at[0].val.clusterDim.x = 2 * k; at[0].val.clusterDim.y = 1; at[0].val.clusterDim.z = 1;
    cfg.gridDim = dim3(2 * k); cfg.blockDim = dim3(NTHR); cfg.dynamicSmemBytes = SM_TOTAL; cfg.attrs = at; cfg.numAttrs = 1;
    if (cudaOccupancyMaxActiveClusters(&occ[k], fused_kernel<true>, &cfg) != cudaSuccess) { cudaGetLastError(); occ[k] = 0; }
  }
  int n[10];
  n[7] = occ[8]; n[6] = occ[7]; n[5] = occ[6] - 0; n[4] = occ[5];
  n[3] = occ[4] - n[7]; n[1] = occ[2] - n[3] - n[5] - n[7]; n[0] = n[2] = n[1];
  n[8] = occ[3] - n[2] - n[5];
  const int ntpc = nsm / 2;
  int sum = 0;
  bool ok = n[0] > 0 && n[0] <= 8;
  for (int r = 0; r < 9; ++r) { ok = ok && n[r] >= 0 && (r == 0 || n[r] <= n[r - 1]); sum += n[r]; }
  if (!ok || sum > ntpc) { for (int r = 0; r < 9; ++r) n[r] = r < 8 ? 8 : 0; sum = 64; }
  int tp[8][9], cnt[8] = {0}, pool[72], np = 0, id = 0;
  for (int r = 0; r < 9; ++r)
    for (int g = n[0] - n[r]; g < n[0]; ++g) tp[g][cnt[g]++] = id++;
  for (; id < ntpc; ++id) pool[np++] = id;
  int order[72], no = 0;
  for (int g = 0; g < n[0]; ++g) {
    const int full = cnt[g] / 4 * 4;
    for (int k = 0; k < cnt[g]; ++k) { if (k < full) order[no++] = tp[g][k]; else pool[np++] = tp[g][k]; }
  }
  for (int k = 0; k < np; ++k) order[no++] = pool[POOL == 1 ? np - 1 - k : POOL == 2 ? (k + np - 2) % np : k];
  for (int k = 0; k < 144; ++k) role[k] = 255;
  for (int k = 0; k < 64; ++k) { role[2 * order[k]] = (2 * k + GOFF) & 127; role[2 * order[k] + 1] = (2 * k + 1 + GOFF) & 127; }
  return nsm;
}

extern "C" void kernel_launch(void* const* d_in, const int* in_sizes, int n_in, void* d_out, int out_size) {
  (void)in_sizes; (void)n_in; (void)out_size;
  static EncodeFn enc = nullptr;
  static uint8_t role[144];
  static int nsm = 0;
  static void* scratch = nullptr;
  if (!enc) {
    void* fn = nullptr;
    cudaDriverEntryPointQueryResult qr;
    cudaGetDriverEntryPoint("cuTensorMapEncodeTiled", &fn, cudaEnableDefault, &qr);
    enc = (EncodeFn)fn;
    cudaFuncSetAttribute(fused_kernel<true>, cudaFuncAttributeMaxDynamicSharedMemorySize, SM_TOTAL);
    cudaFuncSetAttribute(fused_kernel<PLAIN>, cudaFuncAttributeMaxDynamicSharedMemorySize, SM_TOTAL);
    nsm = place_roles(role);
    cudaGetSymbolAddress(&scratch, g_S);
  }
  CUtensorMap mW, mWo;
  {
    cuuint64_t dim[3] = {512, 512, 3}, str[2] = {3072, 1024};
    cuuint32_t box[3] = {64, 64, 3}, es[3] = {1, 1, 1};
    enc(&mW, CU_TENSOR_MAP_DATA_TYPE_BFLOAT16, 3, d_in[10], dim, str, box, es, CU_TENSOR_MAP_INTERLEAVE_NONE,
        CU_TENSOR_MAP_SWIZZLE_128B, CU_TENSOR_MAP_L2_PROMOTION_NONE, CU_TENSOR_MAP_FLOAT_OOB_FILL_NONE);
  }
  {
    cuuint64_t dim[5] = {512, 2, 4, 4, 16}, str[4] = {1024, 8192, 2048, 32768};
    cuuint32_t box[5] = {64, 2, 4, 4, 8}, es[5] = {1, 1, 1, 1, 1};
    enc(&mWo, CU_TENSOR_MAP_DATA_TYPE_BFLOAT16, 5, d_in[11], dim, str, box, es, CU_TENSOR_MAP_INTERLEAVE_NONE,
        CU_TENSOR_MAP_SWIZZLE_128B, CU_TENSOR_MAP_L2_PROMOTION_NONE, CU_TENSOR_MAP_FLOAT_OOB_FILL_NONE);
  }
  Params P;
  P.x0 = (const uint16_t*)d_in[0]; P.Are = (const uint16_t*)d_in[1]; P.Aim = (const uint16_t*)d_in[2];
  P.Bre = (const uint16_t*)d_in[3]; P.Bim = (const uint16_t*)d_in[4]; P.Cre = (const uint16_t*)d_in[5];
  P.Cim = (const uint16_t*)d_in[6]; P.logdt = (const uint16_t*)d_in[7]; P.dskip = (const uint16_t*)d_in[8];
  P.wqkv = (const uint16_t*)d_in[10]; P.wo = (const uint16_t*)d_in[11]; P.out = (uint16_t*)d_out;
  for (int k = 0; k < 144; ++k) P.role[k] = nsm > 0 ? role[k] : k;
  P.pad = 0;
  P.zero = 0;
  P.S = (Scratch*)scratch;
  if (nsm > 0) fused_kernel<true><<<nsm, NTHR, SM_TOTAL, cudaStreamPerThread>>>(P, mW, mWo);
  else fused_kernel<PLAIN><<<128, NTHR, SM_TOTAL, cudaStreamPerThread>>>(P, mW, mWo);
}
```

```cpp
#include <cuda_runtime.h>
#include <cuda_bf16.h>
#include <cuda.h>
#include <stdint.h>

#define DEV __device__ __forceinline__

#define NCOPY 4
#define NSUB 1
constexpr int NTHR = 512;
constexpr int SPIN_LIMIT = 1 << 22;

constexpr uint32_t SB = 1024;
constexpr uint32_t SM_XA   = SB;
constexpr uint32_t SM_S0   = SM_XA + 16384;
constexpr uint32_t SM_S1   = SM_S0 + 49152;
constexpr uint32_t SM_XB   = SM_S1 + 49152;
constexpr uint32_t SM_R    = SM_XB + 16384;
constexpr uint32_t SM_RES  = SM_R + 65536;
constexpr uint32_t SM_TAP  = SM_RES + 16384;
constexpr int TAP_SZ = 3584;
constexpr uint32_t SM_CS   = SM_TAP + 4 * TAP_SZ;
constexpr uint32_t SM_STAT = SM_CS + 800;
constexpr uint32_t SM_MISC = SM_STAT + 1280;
constexpr uint32_t SM_BAR  = SM_MISC + 512;
constexpr int SM_TOTAL = SM_BAR + 448 - SB;
constexpr int R_U = 512, R_A5 = 5120, R_A3 = 8704, R_B = 11776;
constexpr int T_E = 1536, T_O = T_E + 1602, T_C = 3714;
constexpr uint32_t B_W = SM_BAR, B_X = SM_BAR + 64, B_O = SM_BAR + 128, B_WO = SM_BAR + 256, B_RES = SM_BAR + 264;
constexpr uint32_t B_ST = SM_BAR + 272, B_R = SM_BAR + 288, B_E = SM_BAR + 304;
constexpr uint32_t B_F = SM_BAR + 320, B_G = SM_BAR + 352, B_K = SM_BAR + 376, B_ED = SM_BAR + 384, B_CS = SM_BAR + 400, B_FH = SM_BAR + 416;
constexpr uint32_t CNT = 0x141444CC;
constexpr int NB_WG = 1, NB_T = 5, NB_Q = 10, NB_H = 11, NB_P = 14, NB_RL = 15;

struct Scratch {
  uint32_t F[32 * 32];
  uint4    H[17 * 8 * 256];
  uint4    SR[2][8][512];
  uint4    ST[32 * 16];
  uint4    PS[128 * 64];
  uint4    CS[8 * 48];
  uint32_t C[10 * 32 * 32];
  uint4    XF[32 * 4096];
  uint4    O[32 * 8 * 512];
  uint4    XG[512 * 256];
};
__device__ __align__(1024) Scratch g_S;

struct Params {
  const uint16_t *logdt, *dskip, *Are, *Aim, *Bre, *Bim, *Cre, *Cim, *x0, *wqkv, *wo;
  uint16_t* out;
  Scratch* S;
  uint32_t zero, pad;
  uint8_t role[144];
};
#define EVENT(n) do {} while (0)
#define PROFD(slot, name, v) do {} while (0)
#define PROF(slot, name) do {} while (0)
#define PW(x)

DEV uint32_t s2u(const void* p) { return (uint32_t)__cvta_generic_to_shared(p); }
template <class T> DEV T opq(T x) { asm volatile("" : "+r"(x)); return x; }
DEV uint32_t pack2(float lo, float hi) { uint32_t d; asm("cvt.rn.bf16x2.f32 %0,%1,%2;" : "=r"(d) : "f"(hi), "f"(lo)); return d; }
DEV float bflo(uint32_t v) { return __uint_as_float(v << 16); }
DEV float bfhi(uint32_t v) { return __uint_as_float(v & 0xFFFF0000u); }
DEV float bfr(float x) { return bflo(pack2(x, 0.f)); }
DEV uint32_t hadd2(uint32_t a, uint32_t b) { uint32_t d; asm("add.rn.bf16x2 %0,%1,%2;" : "=r"(d) : "r"(a), "r"(b)); return d; }
DEV uint32_t hsub2(uint32_t a, uint32_t b) { uint32_t d; asm("sub.rn.bf16x2 %0,%1,%2;" : "=r"(d) : "r"(a), "r"(b)); return d; }
DEV uint32_t hmul2(uint32_t a, uint32_t b) { uint32_t d; asm("mul.rn.bf16x2 %0,%1,%2;" : "=r"(d) : "r"(a), "r"(b)); return d; }
DEV uint32_t hfma2(uint32_t a, uint32_t b, uint32_t c) { uint32_t d; asm("fma.rn.bf16x2 %0,%1,%2,%3;" : "=r"(d) : "r"(a), "r"(b), "r"(c)); return d; }
DEV uint32_t hmax2(uint32_t a, uint32_t b) { uint32_t d; asm("max.bf16x2 %0,%1,%2;" : "=r"(d) : "r"(a), "r"(b)); return d; }
DEV uint32_t prmt(uint32_t a, uint32_t b, uint32_t s) { uint32_t d; asm("prmt.b32 %0,%1,%2,%3;" : "=r"(d) : "r"(a), "r"(b), "r"(s)); return d; }
DEV uint32_t nz(uint32_t v) { uint32_t d; asm("max.u32 %0,%1,1;" : "=r"(d) : "r"(v)); return d; }
DEV uint32_t tagged(uint32_t v, uint32_t m, uint32_t tag) { uint32_t d; asm("lop3.b32 %0,%1,%2,%3,0xB8;" : "=r"(d) : "r"(v), "r"(m), "r"(tag)); return d; }
DEV uint32_t both(uint32_t a, uint32_t b, uint32_t x) { uint32_t d; asm("lop3.b32 %0,%1,%2,%3,0x42;" : "=r"(d) : "r"(a), "r"(b), "r"(x)); return d; }
DEV uint4 hadd8(const uint4& a, const uint4& b) { return make_uint4(hadd2(a.x, b.x), hadd2(a.y, b.y), hadd2(a.z, b.z), hadd2(a.w, b.w)); }
DEV uint32_t min4(const uint4& v) { return min(min(v.x, v.y), min(v.z, v.w)); }
DEV float rcp(float x) { float y; asm("rcp.approx.ftz.f32 %0,%1;" : "=f"(y) : "f"(x)); return y; }
DEV float sqrt_(float x) { float y; asm("sqrt.approx.ftz.f32 %0,%1;" : "=f"(y) : "f"(x)); return y; }
DEV float rsq(float x) { float y; asm("rsqrt.approx.ftz.f32 %0,%1;" : "=f"(y) : "f"(x)); return y; }
DEV float ex2(float x) { float y; asm("ex2.approx.ftz.f32 %0,%1;" : "=f"(y) : "f"(x)); return y; }

DEV uint4 ldr4(const void* p) { uint4 v; asm volatile("ld.relaxed.gpu.global.v4.u32 {%0,%1,%2,%3},[%4];" : "=r"(v.x), "=r"(v.y), "=r"(v.z), "=r"(v.w) : "l"(p) : "memory"); return v; }
DEV void ldr4_if(uint4& v, const void* p, bool c) {
  asm volatile("{.reg .pred q; setp.ne.u32 q,%5,0; @q ld.relaxed.gpu.global.v4.u32 {%0,%1,%2,%3},[%4];}"
    : "+r"(v.x), "+r"(v.y), "+r"(v.z), "+r"(v.w) : "l"(p), "r"((uint32_t)c) : "memory");
}
DEV uint2 ldr2(const void* p) { uint2 v; asm volatile("ld.relaxed.gpu.global.v2.u32 {%0,%1},[%2];" : "=r"(v.x), "=r"(v.y) : "l"(p) : "memory"); return v; }
DEV uint32_t ldr1(const void* p) { uint32_t v; asm volatile("ld.relaxed.gpu.global.u32 %0,[%1];" : "=r"(v) : "l"(p) : "memory"); return v; }
DEV void str4(void* p, uint32_t a, uint32_t b, uint32_t c, uint32_t d) { asm volatile("st.relaxed.gpu.global.v4.u32 [%0],{%1,%2,%3,%4};" :: "l"(p), "r"(a), "r"(b), "r"(c), "r"(d) : "memory"); }
DEV void str4_if(void* p, uint32_t a, uint32_t b, uint32_t c, uint32_t d, bool q) {
  asm volatile("{.reg .pred q; setp.ne.u32 q,%5,0; @q st.relaxed.gpu.global.v4.u32 [%0],{%1,%2,%3,%4};}" :: "l"(p), "r"(a), "r"(b), "r"(c), "r"(d), "r"((uint32_t)q) : "memory");
}
DEV void str2(void* p, uint32_t a, uint32_t b) { asm volatile("st.relaxed.gpu.global.v2.u32 [%0],{%1,%2};" :: "l"(p), "r"(a), "r"(b) : "memory"); }
DEV void str1(void* p, uint32_t a) { asm volatile("st.relaxed.gpu.global.u32 [%0],%1;" :: "l"(p), "r"(a) : "memory"); }
DEV void stw4(void* p, uint32_t a, uint32_t b, uint32_t c, uint32_t d) { asm volatile("st.global.v4.u32 [%0],{%1,%2,%3,%4};" :: "l"(p), "r"(a), "r"(b), "r"(c), "r"(d) : "memory"); }
DEV uint4 ldnc4(const void* p) { uint4 v; asm volatile("ld.global.nc.v4.u32 {%0,%1,%2,%3},[%4];" : "=r"(v.x), "=r"(v.y), "=r"(v.z), "=r"(v.w) : "l"(p)); return v; }
DEV uint4 ldw4(const void* p) { uint4 v; asm volatile("ld.global.v4.u32 {%0,%1,%2,%3},[%4];" : "=r"(v.x), "=r"(v.y), "=r"(v.z), "=r"(v.w) : "l"(p) : "memory"); return v; }
DEV void cp16(uint32_t d, const void* p) { asm volatile("cp.async.cg.shared.global [%0],[%1],16;" :: "r"(d), "l"(p) : "memory"); }
DEV uint32_t ld16_if(const void* p, bool c) { uint32_t v = 0; asm volatile("{.reg .pred q; setp.ne.u32 q,%2,0; @q ld.global.u16 %0,[%1];}" : "+r"(v) : "l"(p), "r"((uint32_t)c) : "memory"); return v; }
DEV uint32_t ldnc16(const void* p) { uint32_t v; asm volatile("ld.global.u16 %0,[%1];" : "=r"(v) : "l"(p) : "memory"); return v; }

DEV uint32_t lds1v(uint32_t a) { uint32_t v; asm volatile("ld.volatile.shared.u32 %0,[%1];" : "=r"(v) : "r"(a) : "memory"); return v; }
DEV uint4 lds4v(uint32_t a) { uint4 v; asm volatile("ld.volatile.shared.v4.u32 {%0,%1,%2,%3},[%4];" : "=r"(v.x), "=r"(v.y), "=r"(v.z), "=r"(v.w) : "r"(a) : "memory"); return v; }
DEV uint32_t lds1(uint32_t a) { uint32_t v; asm volatile("ld.shared.u32 %0,[%1];" : "=r"(v) : "r"(a)); return v; }
DEV uint2 lds2(uint32_t a) { uint2 v; asm volatile("ld.shared.v2.u32 {%0,%1},[%2];" : "=r"(v.x), "=r"(v.y) : "r"(a)); return v; }
DEV uint4 lds4(uint32_t a) { uint4 v; asm volatile("ld.shared.v4.u32 {%0,%1,%2,%3},[%4];" : "=r"(v.x), "=r"(v.y), "=r"(v.z), "=r"(v.w) : "r"(a)); return v; }
DEV uint32_t lds16(uint32_t a) { uint32_t v; asm volatile("ld.shared.u16 %0,[%1];" : "=r"(v) : "r"(a)); return v; }
DEV float lds1f(uint32_t a) { float v; asm volatile("ld.shared.f32 %0,[%1];" : "=f"(v) : "r"(a)); return v; }
DEV float2 lds2f(uint32_t a) { float2 v; asm volatile("ld.shared.v2.f32 {%0,%1},[%2];" : "=f"(v.x), "=f"(v.y) : "r"(a)); return v; }
DEV float4 lds4f(uint32_t a) { float4 v; asm volatile("ld.shared.v4.f32 {%0,%1,%2,%3},[%4];" : "=f"(v.x), "=f"(v.y), "=f"(v.z), "=f"(v.w) : "r"(a)); return v; }
DEV void sts1(uint32_t a, uint32_t v) { asm volatile("st.shared.u32 [%0],%1;" :: "r"(a), "r"(v) : "memory"); }
DEV void sts16(uint32_t a, uint32_t v) { asm volatile("{.reg .b16 h; cvt.u16.u32 h,%1; st.shared.u16 [%0],h;}" :: "r"(a), "r"(v) : "memory"); }
DEV void sts2f(uint32_t a, float x, float y) { asm volatile("st.shared.v2.f32 [%0],{%1,%2};" :: "r"(a), "f"(x), "f"(y) : "memory"); }
DEV void sts4f(uint32_t a, float x, float y, float z, float w) { asm volatile("st.shared.v4.f32 [%0],{%1,%2,%3,%4};" :: "r"(a), "f"(x), "f"(y), "f"(z), "f"(w) : "memory"); }
DEV void sts4(uint32_t a, uint32_t x, uint32_t y, uint32_t z, uint32_t w) { asm volatile("st.shared.v4.u32 [%0],{%1,%2,%3,%4};" :: "r"(a), "r"(x), "r"(y), "r"(z), "r"(w) : "memory"); }
DEV void sts4_if(uint32_t a, uint32_t x, uint32_t y, uint32_t z, uint32_t w, bool c) {
  asm volatile("{.reg .pred q; setp.ne.u32 q,%5,0; @q st.shared.v4.u32 [%0],{%1,%2,%3,%4};}" :: "r"(a), "r"(x), "r"(y), "r"(z), "r"(w), "r"((uint32_t)c) : "memory");
}
DEV void sts4z_if(uint32_t a, bool c) { asm volatile("{.reg .pred q; setp.ne.u32 q,%1,0; @q st.shared.v4.u32 [%0],{%2,%2,%2,%2};}" :: "r"(a), "r"((uint32_t)c), "r"(0) : "memory"); }

DEV void ldsm4t(uint32_t& r0, uint32_t& r1, uint32_t& r2, uint32_t& r3, uint32_t a) { asm volatile("ldmatrix.sync.aligned.m8n8.x4.trans.shared.b16 {%0,%1,%2,%3},[%4];" : "=r"(r0), "=r"(r1), "=r"(r2), "=r"(r3) : "r"(a) : "memory"); }
DEV void stsm4(uint32_t a, uint32_t r0, uint32_t r1, uint32_t r2, uint32_t r3) { asm volatile("stmatrix.sync.aligned.m8n8.x4.shared.b16 [%0],{%1,%2,%3,%4};" :: "r"(a), "r"(r0), "r"(r1), "r"(r2), "r"(r3) : "memory"); }
DEV void stsm2(uint32_t a, uint32_t r0, uint32_t r1) { asm volatile("stmatrix.sync.aligned.m8n8.x2.shared.b16 [%0],{%1,%2};" :: "r"(a), "r"(r0), "r"(r1) : "memory"); }
DEV void stsm4t(uint32_t a, uint32_t r0, uint32_t r1, uint32_t r2, uint32_t r3) { asm volatile("stmatrix.sync.aligned.m8n8.x4.trans.shared.b16 [%0],{%1,%2,%3,%4};" :: "r"(a), "r"(r0), "r"(r1), "r"(r2), "r"(r3) : "memory"); }
DEV uint32_t movm(uint32_t a) { uint32_t d; asm volatile("movmatrix.sync.aligned.m8n8.trans.b16 %0,%1;" : "=r"(d) : "r"(a)); return d; }
DEV void mma16(float (&d)[4], uint32_t a0, uint32_t a1, uint32_t a2, uint32_t a3, uint32_t b0, uint32_t b1) {
  asm volatile("mma.sync.aligned.m16n8k16.row.col.f32.bf16.bf16.f32 {%0,%1,%2,%3},{%4,%5,%6,%7},{%8,%9},{%0,%1,%2,%3};"
    : "+f"(d[0]), "+f"(d[1]), "+f"(d[2]), "+f"(d[3]) : "r"(a0), "r"(a1), "r"(a2), "r"(a3), "r"(b0), "r"(b1));
}
DEV void mma16z(float (&d)[4], uint32_t a0, uint32_t a1, uint32_t a2, uint32_t a3, uint32_t b0, uint32_t b1) {
  asm volatile("mma.sync.aligned.m16n8k16.row.col.f32.bf16.bf16.f32 {%0,%1,%2,%3},{%4,%5,%6,%7},{%8,%9},{%10,%10,%10,%10};"
    : "=f"(d[0]), "=f"(d[1]), "=f"(d[2]), "=f"(d[3]) : "r"(a0), "r"(a1), "r"(a2), "r"(a3), "r"(b0), "r"(b1), "f"(0.f));
}
DEV void mma8z(float (&d)[4], uint32_t a0, uint32_t a1, uint32_t b0) {
  asm volatile("mma.sync.aligned.m16n8k8.row.col.f32.bf16.bf16.f32 {%0,%1,%2,%3},{%4,%5},{%6},{%7,%7,%7,%7};"
    : "=f"(d[0]), "=f"(d[1]), "=f"(d[2]), "=f"(d[3]) : "r"(a0), "r"(a1), "r"(b0), "f"(0.f));
}
DEV void mma8(float (&d)[4], uint32_t a0, uint32_t a1, uint32_t b0) {
  asm volatile("mma.sync.aligned.m16n8k8.row.col.f32.bf16.bf16.f32 {%0,%1,%2,%3},{%4,%5},{%6},{%0,%1,%2,%3};"
    : "+f"(d[0]), "+f"(d[1]), "+f"(d[2]), "+f"(d[3]) : "r"(a0), "r"(a1), "r"(b0));
}

DEV void bar_sync(int id, int n) { asm volatile("bar.sync %0,%1;" :: "r"(id), "r"(n) : "memory"); }
DEV void bar_arrive(int id, int n) { asm volatile("bar.arrive %0,%1;" :: "r"(id), "r"(n) : "memory"); }
DEV void bar_sync_if(int id, int n, int c) { asm volatile("{.reg .pred q; setp.ne.s32 q,%2,0; @q bar.sync %0,%1;}" :: "r"(id), "r"(n), "r"(c) : "memory"); }
DEV void bar_arrive_if(int id, int n, int c) { asm volatile("{.reg .pred q; setp.ne.s32 q,%2,0; @q bar.arrive %0,%1;}" :: "r"(id), "r"(n), "r"(c) : "memory"); }
DEV bool bar_any(int id, int n, bool c) {
  uint32_t r; asm volatile("{.reg .pred p,q; setp.ne.u32 q,%3,0; bar.red.or.pred p,%1,%2,q; selp.u32 %0,1,0,p;}" : "=r"(r) : "r"(id), "r"(n), "r"((uint32_t)c) : "memory");
  return __any_sync(0xffffffffu, r);
}
DEV void fence_async_glob() { asm volatile("fence.proxy.async.global;" ::: "memory"); }
DEV void fence_async_smem() { asm volatile("fence.proxy.async.shared::cta;" ::: "memory"); }
DEV void fence_gpu() { asm volatile("fence.acq_rel.gpu;" ::: "memory"); }
DEV void mbar_wait(uint32_t b, uint32_t ph) {
  asm volatile("{\n.reg .pred p;\nW: mbarrier.try_wait.parity.shared::cta.b64 p,[%0],%1;\n@!p bra W;\n}" :: "r"(b), "r"(ph) : "memory");
}
DEV bool mbar_test(uint32_t b, uint32_t ph) {
  uint32_t r; asm volatile("{.reg .pred p; mbarrier.test_wait.parity.shared::cta.b64 p,[%1],%2; selp.u32 %0,1,0,p;}" : "=r"(r) : "r"(b), "r"(ph) : "memory");
  return __all_sync(0xffffffffu, r);
}
DEV uint32_t mbar_test2(uint32_t b, uint32_t ph) {
  uint32_t r; asm volatile("{.reg .pred p,q; mbarrier.test_wait.parity.shared::cta.b64 p,[%1],%2; mbarrier.test_wait.parity.shared::cta.b64 q,[%1+8],%2;\n"
                           "and.pred p,p,q; selp.u32 %0,1,0,p;}" : "=r"(r) : "r"(b), "r"(ph) : "memory");
  return r;
}
DEV void spin_guard(int it) { asm volatile("{.reg .pred p; setp.gt.s32 p,%0,%1; @p trap;}" :: "r"(it), "n"(SPIN_LIMIT)); }
DEV uint32_t here(uint32_t zero) {
  uint32_t d; asm volatile("mov.u32 %0,%%clock;" : "=r"(d) :: "memory"); return d & zero;
}
DEV int lane_here(uint32_t zero) {
  uint32_t d; asm volatile("mov.u32 %0,%%laneid;" : "=r"(d)); return d | here(zero);
}
DEV void delay(uint32_t n) {
  asm volatile("{\n.reg .pred p;\n.reg .u32 a,b;\nmov.u32 a,%%clock;\nW: mov.u32 b,%%clock;\nsub.u32 b,b,a;\nsetp.lt.u32 p,b,%0;\n@p bra.uni W;\n}" :: "r"(n) : "memory");
}
DEV void poll(const uint32_t* p, uint32_t n) {
  for (int it = 0; !__all_sync(0xffffffffu, ldr1(p) >= n); ++it) spin_guard(it);
}
DEV uint32_t* cnt_at(const Params& P, int n, int c, int lane) { return P.S->C + (32 * (NSUB * lane + c % NSUB) + n * 1024); }
DEV void cnt_add(uint32_t* p, uint32_t one, bool q) { asm volatile("{.reg .pred p; setp.ne.u32 p,%2,0; @p red.relaxed.gpu.global.add.u32 [%0],%1;}" :: "l"(p), "r"(one), "r"((uint32_t)q) : "memory"); }
DEV void cnt_wait(const Params& P, int n, int c, int lane) { poll(P.S->C + (32 * (NSUB * (c / (128 / NCOPY)) + lane % NSUB) + n * 1024), 128 / NSUB); }
DEV void mbar_init1(uint32_t b, int n) { asm volatile("{.reg .pred p; elect.sync _|p,0xffffffff; @p mbarrier.init.shared::cta.b64 [%0],%1;}" :: "r"(b), "r"(n) : "memory"); }
DEV void mbar_arrive1(uint32_t b) { asm volatile("{.reg .pred p; elect.sync _|p,0xffffffff; @p mbarrier.arrive.shared::cta.b64 _,[%0];}" :: "r"(b) : "memory"); }
DEV void mbar_arrive1_if(uint32_t b, int c) {
  asm volatile("{.reg .pred p,q; setp.ne.s32 q,%1,0; elect.sync _|p,0xffffffff; and.pred p,p,q; @p mbarrier.arrive.shared::cta.b64 _,[%0];}" :: "r"(b), "r"(c) : "memory");
}
DEV void mbar_expect1(uint32_t b, int bytes) { asm volatile("{.reg .pred p; elect.sync _|p,0xffffffff; @p mbarrier.arrive.expect_tx.shared::cta.b64 _,[%0],%1;}" :: "r"(b), "r"(bytes) : "memory"); }
DEV void flag_set1(uint32_t* q) { asm volatile("{.reg .pred p; elect.sync _|p,0xffffffff; @p st.relaxed.gpu.global.u32 [%0],1;}" :: "l"(q) : "memory"); }
DEV void tma3(uint32_t dst, const CUtensorMap* m, int c0, int c1, uint32_t bar) {
  asm volatile("{.reg .pred p; elect.sync _|p,0xffffffff;\n"
    "@p cp.async.bulk.tensor.3d.shared::cluster.global.mbarrier::complete_tx::bytes [%0],[%1,{%2,%3,%5}],[%4];}"
    :: "r"(dst), "l"(m), "r"(c0), "r"(c1), "r"(bar), "r"(0) : "memory");
}
DEV void tma5(uint32_t dst, const CUtensorMap* m, int c0, int c4, uint32_t bar) {
  asm volatile("{.reg .pred p; elect.sync _|p,0xffffffff;\n"
    "@p cp.async.bulk.tensor.5d.shared::cluster.global.mbarrier::complete_tx::bytes [%0],[%1,{%2,%5,%5,%5,%3}],[%4];}"
    :: "r"(dst), "l"(m), "r"(c0), "r"(c4), "r"(bar), "r"(0) : "memory");
}
DEV void bulk(uint32_t dst, const void* src, int bytes, uint32_t bar) {
  asm volatile("{.reg .pred p; elect.sync _|p,0xffffffff;\n@p cp.async.bulk.shared::cluster.global.mbarrier::complete_tx::bytes [%0],[%1],%2,[%3];}" :: "r"(dst), "l"(src), "r"(bytes), "r"(bar) : "memory");
}
DEV void bulk_store(void* dst, uint32_t src, int bytes) {
  asm volatile("{.reg .pred p; elect.sync _|p,0xffffffff;\n@p cp.async.bulk.global.shared::cta.bulk_group [%0],[%1],%2;}" :: "l"(dst), "r"(src), "r"(bytes) : "memory");
}
DEV void l2_prefetch(const void* src, int bytes) {
  asm volatile("{.reg .pred p; elect.sync _|p,0xffffffff;\n@p cp.async.bulk.prefetch.L2.global [%0],%1;}" :: "l"(src), "r"(bytes) : "memory");
}

DEV uint64_t mkdesc(uint32_t addr, uint32_t lbo, uint32_t sbo, uint32_t swz) {
  return (uint64_t)((addr >> 4) | ((lbo >> 4) << 16)) | ((uint64_t)((sbo >> 4) | (swz << 30)) << 32);
}
DEV void wg_fence() { asm volatile("wgmma.fence.sync.aligned;" ::: "memory"); }
DEV void wg_commit() { asm volatile("wgmma.commit_group.sync.aligned;" ::: "memory"); }
template <int N> DEV void wg_wait() { asm volatile("wgmma.wait_group.sync.aligned %0;" :: "n"(N) : "memory"); }
template <int N> DEV void zerov(float (&d)[N]) {
#pragma unroll
  for (int i = 0; i < N; ++i) asm volatile("mov.b32 %0,0;" : "=f"(d[i]));
}
template <int N> DEV void undef(float (&d)[N]) {
#pragma unroll
  for (int i = 0; i < N; ++i) asm volatile("" : "=f"(d[i]));
}
#define R4(d, o) "+f"(d[o]), "+f"(d[o + 1]), "+f"(d[o + 2]), "+f"(d[o + 3])
#define R8(d, o) R4(d, o), R4(d, o + 4)
#define R16(d, o) R8(d, o), R8(d, o + 8)
#define R32(d, o) R16(d, o), R16(d, o + 16)
#define L0 "%0,%1,%2,%3,%4,%5,%6,%7,%8,%9,"
#define L10(a) "%" #a "0,%" #a "1,%" #a "2,%" #a "3,%" #a "4,%" #a "5,%" #a "6,%" #a "7,%" #a "8,%" #a "9,"
#define WG_HEAD(pr, n) "{.reg .pred p; setp.ne.s32 p,%" #pr ",0;\nwgmma.mma_async.sync.aligned.m64n" #n "k16.f32.bf16.bf16 {"
DEV void wg_rs64k(float (&d)[32], const uint32_t (&a)[4], uint64_t db, int acc) {
  asm volatile(WG_HEAD(37, 64) L0 L10(1) L10(2) "%30,%31},{%32,%33,%34,%35},%36,p,1,1,0;}"
    : R32(d, 0) : "r"(a[0]), "r"(a[1]), "r"(a[2]), "r"(a[3]), "l"(db), "r"(acc));
}
DEV void wg_rs48t(float (&d)[24], const uint32_t (&a)[4], uint64_t db, int acc) {
  asm volatile(WG_HEAD(29, 48) L0 L10(1) "%20,%21,%22,%23},{%24,%25,%26,%27},%28,p,1,1,1;}"
    : R16(d, 0), R8(d, 16) : "r"(a[0]), "r"(a[1]), "r"(a[2]), "r"(a[3]), "l"(db), "r"(acc));
}
DEV void wg_rs32t(float (&d)[16], const uint32_t (&a)[4], uint64_t db, int acc) {
  asm volatile(WG_HEAD(21, 32) L0 "%10,%11,%12,%13,%14,%15},{%16,%17,%18,%19},%20,p,1,1,1;}"
    : R16(d, 0) : "r"(a[0]), "r"(a[1]), "r"(a[2]), "r"(a[3]), "l"(db), "r"(acc));
}
DEV void wg_ss8(float (&d)[4], uint64_t da, uint64_t db) {
  asm volatile("wgmma.mma_async.sync.aligned.m64n8k16.f32.bf16.bf16 {%0,%1,%2,%3},%4,%5,1,1,1,1,0;" : R4(d, 0) : "l"(da), "l"(db));
}
DEV void wg_ss48(float (&d)[24], uint64_t da, uint64_t db, int acc) {
  asm volatile(WG_HEAD(26, 48) L0 L10(1) "%20,%21,%22,%23},%24,%25,p,1,1,1,1;}" : R16(d, 0), R8(d, 16) : "l"(da), "l"(db), "r"(acc));
}
DEV void wg_ss64(float (&d)[32], uint64_t da, uint64_t db, int acc) {
  asm volatile(WG_HEAD(34, 64) L0 L10(1) L10(2) "%30,%31},%32,%33,p,1,1,0,1;}" : R32(d, 0) : "l"(da), "l"(db), "r"(acc));
}
DEV void wg_ss192(float (&d)[96], uint64_t da, uint64_t db, int acc) {
  asm volatile(WG_HEAD(98, 192) L0 L10(1) L10(2) L10(3) L10(4) L10(5) L10(6) L10(7) L10(8) "%90,%91,%92,%93,%94,%95},%96,%97,p,1,1,1,1;}"
    : R32(d, 0), R32(d, 32), R32(d, 64) : "l"(da), "l"(db), "r"(acc));
}

DEV void wg_rs192t(float (&d)[96], const uint32_t (&a)[4], uint64_t db) {
  asm volatile("wgmma.mma_async.sync.aligned.m64n192k16.f32.bf16.bf16 {" L0 L10(1) L10(2) L10(3) L10(4) L10(5) L10(6) L10(7) L10(8) "%90,%91,%92,%93,%94,%95},{%96,%97,%98,%99},%100,1,1,1,1;"
    : R32(d, 0), R32(d, 32), R32(d, 64) : "r"(a[0]), "r"(a[1]), "r"(a[2]), "r"(a[3]), "l"(db));
}

DEV float ln_sd(float s, float q, float& m) {
  m = s * (1.f / 512.f);
  return bfr(sqrt_(bfr(bfr(fmaxf(q * (1.f / 512.f) - m * m, 0.f)) + 1e-5f)));
}
DEV float4 gram(const uint32_t (&w)[8][2], int g, uint32_t zero) {
  float s[4], q[4][4];
  const uint32_t o0 = 0x3F803F80u | zero, o1 = 0x3F803F80u ^ zero;
#pragma unroll
  for (int j = 0; j < 8; ++j) {
#pragma unroll
    for (int h = 0; h < 2; ++h) { if (j < 2) mma8z(q[2 * j + h], w[j][0], w[j][1], w[j][h]); else mma8(q[2 * (j & 1) + h], w[j][0], w[j][1], w[j][h]); }
    if (j == 1) mma16z(s, w[0][0], w[0][1], w[1][0], w[1][1], o0, o1);
    else if (j & 1) mma16(s, w[j - 1][0], w[j - 1][1], w[j][0], w[j][1], o0, o1);
  }
  const bool od = g & 1;
  return make_float4(s[0], od ? q[0][1] + q[2][1] : q[0][0] + q[2][0], s[2], od ? q[1][3] + q[3][3] : q[1][2] + q[3][2]);
}
DEV void keep(uint32_t v, uint32_t zero) {
  asm volatile("{.reg .pred p; setp.ne.u32 p,%1,0; @p st.shared.u32 [%0],%0;}" :: "r"(v), "r"(zero) : "memory");
}
DEV void keep(const void* v, uint32_t zero) { asm volatile("{.reg .pred p; setp.ne.u32 p,%1,0; @p st.global.u32 [%0],%1;}" :: "l"(v), "r"(zero) : "memory"); }
struct XgAddr { uint32_t a, b; uint4* dst; };
template <bool FRAG> DEV XgAddr xg_addr(uint4* dst, uint32_t stg, int wp, int lane, uint32_t zero) {
  const int t = lane & 3, r = 4 * wp + (lane >> 3);
  XgAddr x = {stg + t * (FRAG ? 256 : 1024) + ((wp ^ t) * 32) + (lane >> 2) * 4,
              stg + r * 128 + (((lane & 7) ^ (2 * (((r >> 1) ^ (r >> 3)) & 3))) * 16), dst + (r * 256 + (lane & 7))};
  keep(x.a, zero); keep(x.b, zero); keep(x.dst, zero);
  return x;
}
template <bool FRAG> DEV void xg_put(const XgAddr& x, const uint32_t (&w)[8][2]) {
#pragma unroll
  for (int n = 0; n < 8; ++n) {
    const uint32_t b = (x.a ^ ((n & 3) * 32)) + (FRAG ? n * 1024 : (n >> 2) * 4096 + (n & 3) * 256);
    sts1(b, prmt(w[n][0], w[n][1], 0x5410)); sts1(b + 128, prmt(w[n][0], w[n][1], 0x7632));
  }
}
DEV void xg_store(const XgAddr& x, uint32_t tag) {
  const uint32_t m = (~x.b >> 4) & 1;
#pragma unroll
  for (int k = 0; k < 4; ++k) {
    const uint4 v = lds4((x.b ^ ((k & 1) * 64)) + k * 2048);
    str4(x.dst + k * 4096, tagged(v.x, m, tag), v.y, v.z, v.w);
  }
}
template <int N, int M> DEV void fold(float (&v)[M], int lane, int bit) {
  const bool b = lane & bit;
#pragma unroll
  for (int k = 0; k < N; ++k) { const float sn = b ? v[k] : v[k + N], kp = b ? v[k + N] : v[k]; v[k] = kp + __shfl_xor_sync(0xffffffffu, sn, bit); }
}
DEV void refetch(uint32_t dst, const uint4* src, int half, int e, int w) {
#pragma unroll 1
  for (int r = 0; r < 2; ++r) {
    if (w == 0) { mbar_expect1(B_R + 8 * e, half); bulk(dst + r * half, src + r * (half >> 4), half, B_R + 8 * e); }
    mbar_wait(B_R + 8 * e, r);
    bar_sync(NB_WG + e, 128);
  }
}
DEV uint32_t kvslot(int cg, int pos) { return (pos & 2 ? SM_XA : SM_S1) + (cg < 4 ? 5 : 2) * 8192 + (pos & 1) * 4096; }
DEV uint32_t xstage(int q, int e) { return ((q + 1) & 2) ? SM_R + ((q & 2) + e) * 16384 : e ? SM_XB : SM_XA; }
DEV void cmul(float& orr, float& oi, float ar, float ai, float br, float bi) {
  float r = ar * br - ai * bi, i = ar * bi + ai * br; orr = r; oi = i;
}
DEV void cexp_(float al, float bt, float s, float& er, float& ei) {
  float mag = ex2(al * s), ph = bt * s;
  ph -= rintf(ph);
  float ang = ph * 6.283185307179586f;
  er = mag * __cosf(ang); ei = mag * __sinf(ang);
}

#define KS 2048
DEV void put8(uint32_t a, const float (&r)[8], const float (&i)[8]) {
  sts4(a, pack2(r[0], r[1]), pack2(r[2], r[3]), pack2(r[4], r[5]), pack2(r[6], r[7]));
  sts4(a + 1024, pack2(i[0], i[1]), pack2(i[2], i[3]), pack2(i[4], i[5]), pack2(i[6], i[7]));
}
DEV void tables(const uint32_t (&pv)[8], int k4, int w, int lane) {
  PW(4 * k4 + w)
  [[maybe_unused]] const int layer = 0;
  const float dt = bfr(__expf(bflo(pv[6])));
  const float al = dt * bflo(pv[0]) * 1.4426950408889634f, bt = dt * bflo(pv[1]) * 0.15915494309189535f;
  float qr[8], qi[8], yr[8], yi[8];
  cmul(qr[0], qi[0], bflo(pv[4]), bflo(pv[5]), dt * bflo(pv[2]), dt * bflo(pv[3]));
  PROFD(2, a_par, __float_as_uint(qr[0] + al + bt));
  float e1r, e1i, eMr, eMi, eLr, eLi;
  cexp_(al, bt, 1.f, e1r, e1i); cexp_(al, -bt, 8.f, yr[1], yi[1]); cexp_(al, -bt, 64.f, eMr, eMi); cexp_(al, bt, 256.f, eLr, eLi);
  const uint32_t ad = SB + k4 * 32768 + (w & 1) * 512 + lane * 16, am = ad + (w >> 1) * KS, an = ad + (8 + 3 * (w >> 1)) * KS;
  yr[0] = 1.f; yi[0] = 0.f;
#pragma unroll
  for (int k = 1; k < 8; ++k) {
    cmul(qr[k], qi[k], qr[k - 1], qi[k - 1], e1r, e1i);
    if (k > 1) cmul(yr[k], yi[k], yr[k - 1], yi[k - 1], yr[1], yi[1]);
  }
  put8(an, qr, qi);
#pragma unroll
  for (int j = 0; j < 4; ++j) {
    put8(am + j * 2 * KS, yr, yi);
#pragma unroll
    for (int k = 0; k < 8; ++k) {
      if (j == 0 && k == 0) { yr[0] = eMr; yi[0] = eMi; } else if (j < 3) cmul(yr[k], yi[k], yr[k], yi[k], eMr, eMi);
    }
    if (j == 0) {
#pragma unroll
      for (int k = 0; k < 8; ++k) { const int o = k < 4 ? 2 * k : k < 6 ? 2 * k - 8 : k - 2; cmul(qr[k], qi[k], qr[o], qi[o], eLr, eLi); }
      put8(an + KS, qr, qi);
    } else if (j == 1) {
#pragma unroll
      for (int k = 0; k < 5; ++k) cmul(qr[k], qi[k], qr[k ? k - 1 : 6], qi[k ? k - 1 : 6], eLr, eLi);
      put8(an + 2 * KS, qr, qi);
    }
  }
  PROF(3, a_tab);
}

DEV void sts16_if(uint32_t a, uint32_t v, bool c) { asm volatile("{.reg .pred q; .reg .b16 h; setp.ne.u32 q,%2,0; cvt.u16.u32 h,%1; @q st.shared.u16 [%0],h;}" :: "r"(a), "r"(v), "r"((uint32_t)c) : "memory"); }
DEV void sts1_if(uint32_t a, uint32_t v, bool c) { asm volatile("{.reg .pred q; setp.ne.u32 q,%2,0; @q st.shared.u32 [%0],%1;}" :: "r"(a), "r"(v), "r"((uint32_t)c) : "memory"); }
DEV void taps(uint32_t dskip, int k4, int w, int lane) {
  PW(4 * k4 + w)
  [[maybe_unused]] const int layer = 0;
  fence_async_smem();
  bar_sync((k4 & 1) ? NB_WG + k4 : NB_Q, (k4 & 1) ? 128 : 448);
  float d[24];
  undef(d);
  const uint64_t da = mkdesc(SB + k4 * 32768, 1024, KS, 0);
  wg_fence();
#pragma unroll
  for (int j = 0; j < 8; ++j) wg_ss48(d, da + j * 8, da + KS / 2 + j * 8, j);
  wg_commit();
  const int b = 8 * w + (lane >> 2), t = lane & 3, id = 32 * w + lane;
  constexpr int DO = T_O - T_E;
  const uint32_t te = SM_TAP + k4 * TAP_SZ + T_E, a0 = te - 16 * b - 4 * t;
  const uint32_t a1 = a0 - 512 - 4 * t, a2 = te - 2 * (511 + b) - 64 * t, a3 = te + (T_C - T_E) - 2 * (127 + b) - 128 * t;
  wg_wait<0>();
  PROF(4, a_mma);
  {
    const uint32_t v = pack2(d[1] + d[15], d[0] + d[14] + (id ? 0.f : bflo(dskip)));
    sts1(a0 + DO - 2, v); sts16(a0 - 2, v); sts16(a0, v >> 16);
  }
  {
    const uint32_t v = pack2(d[5] + d[19], d[4] + d[18]), u = prmt(v, v, 0x3232);
    const bool lo = t < 2, k512 = id == 2;
    sts1_if(k512 ? te - 2 * 512 : a1, u, (lo && id) || k512);
    sts1_if(k512 ? te - 2 * 514 : a1 - 4, k512 ? u : v, lo || k512);
    sts1_if(k512 ? te + DO - 2 * 513 : a1 + DO - 2, u, lo || k512);
    sts16(lo ? a1 + DO - 4 : a2 + DO - 194, v);
    sts16(lo ? (id ? a1 + DO + 2 : a1) : k512 ? te + DO - 2 * 511 : a2 + DO, u);
    sts16_if(a2 - 194, v, !lo);
    sts16_if(k512 ? te + DO - 2 * 514 : a2, u, !lo);
  }
  {
    const uint32_t v = pack2(d[8] + d[22], d[9] + d[23]);
    sts16_if(id ? a3 : te - 2 * 639, v, t < 2 || id == 2);
    sts16_if(a3 - 64, v >> 16, t < 2);
    sts16_if(te + DO - 2 * 639, v, id == 0);
  }
  bar_sync(NB_WG + k4, 128);
  mbar_arrive1_if(B_K, w == 0);
}

DEV uint32_t cpy(uint32_t v, uint32_t id) {
  uint32_t d; asm volatile("prmt.b32 %0,%1,%1,%2;" : "=r"(d) : "r"(v), "r"(id)); return d;
}
DEV uint32_t uoff(int s) { return (s ^ ((s >> 3) & 3)) * 16; }
template <bool FULL> DEV void boxes(const uint32_t (&u)[10], uint32_t a, uint32_t a9, uint32_t a7, uint32_t (&pv)[4]) {
  uint32_t v[8], p[8], x[4], y[4];
#pragma unroll
  for (int j = 0; j < 8; ++j) { v[j] = prmt(u[j], u[j + 1], 0x5432); p[j] = hadd2(u[j], v[j]); }
#pragma unroll
  for (int j = 0; j < 4; ++j) { x[j] = hadd2(hadd2(p[j + 1], p[j + 2]), u[j + 3]); y[j] = hadd2(v[j + 3], p[j + 4]); }
  sts4(a + R_A5, x[0], x[1], x[2], x[3]);
  sts4(a + R_A3, y[0], y[1], y[2], y[3]);
  if (FULL) {
#pragma unroll
    for (int j = 0; j < 4; ++j) { x[j] = hadd2(x[j], hadd2(v[j], v[j + 3])); y[j] = hadd2(x[j], hadd2(u[j], u[j + 4])); pv[j] = p[j + 4]; }
    sts4(a7, x[0], x[1], x[2], x[3]);
    sts4(a9, y[0], y[1], y[2], y[3]);
  }
}
DEV uint32_t shfl_up(uint32_t v, int d) { uint32_t r; asm volatile("shfl.sync.up.b32 %0,%1,%2,0,0xffffffff;" : "=r"(r) : "r"(v), "r"(d) : "memory"); return r; }
DEV void halo(uint32_t (&u)[10], uint32_t a, uint32_t b, int lane) {
  asm volatile("{.reg .pred p,q; setp.eq.s32 p,%8,0; setp.lt.s32 q,%8,2;\n@p ld.shared.v4.u32 {%2,%3,%4,%5},[%6];\n@q ld.shared.v2.u32 {%0,%1},[%7];}"
    : "+r"(u[0]), "+r"(u[1]), "+r"(u[2]), "+r"(u[3]), "+r"(u[4]), "+r"(u[5]) : "r"(a), "r"(b), "r"(lane));
}
#define W1 4
#define ROT 2
#define G1 -1
#define G2 1
#define G3 8
#define TPS 0x7134
#define GMASK ((G1 >= 0 ? 2 : 0) | (G2 >= 0 ? 4 : 0) | (G3 >= 0 ? 8 : 0))
#define GATE1(g, n, p) if (g >= 0 && (g & 3) == p) mbar_arrive1_if(B_G + 8 * n, k4 == (g >> 2));
#define GATE(p) GATE1(G1, 0, p) GATE1(G2, 1, p) GATE1(G3, 2, p)
#define TMASK(p) (((TPS & 15) == p) | ((((TPS >> 4) & 15) == p) << 1) | ((((TPS >> 8) & 15) == p) << 2) | ((((TPS >> 12) & 15) == p) << 3))
#define TURN(p) if (TMASK(p) == 15) bar_arrive(NB_T + 1 + k4, 256); else if (TMASK(p)) { if ((TMASK(p) >> k4) & 1) bar_arrive(NB_T + 1 + k4, 256); }
DEV void w_load(const CUtensorMap* mW, int cg, int h) {
  mbar_expect1(B_W + 8 * h, 24576);
  tma3(SM_S0 + (h & 3) * 24576, mW, 64 * cg, 64 * h, B_W + 8 * h);
}

DEV void conv(const Params& P, const CUtensorMap* mW, int c, int k4, int w, int layer) {
  const uint32_t zero = P.zero;
  PW(4 * k4 + w)
  int lane = lane_here(zero);
  const int g = lane >> 2, t = lane & 3, v = w ^ (ROT * (k4 & 1)), tid = 32 * v + lane;
  const uint32_t reg = SM_R + k4 * 16384, tp = SM_TAP + k4 * TAP_SZ;
  const uint32_t g0 = tp + ((g & 1) ? T_O : T_E) + 2 * (2 * t - g);
  uint32_t F[18][4], U[20], qc[4][4];
#define LO(q, a) q[0] = lds1(a); q[2] = lds1(a + 16);
#define HI(q, a) q[1] = lds1(a - 128); q[3] = lds1(a - 112);
  {
    const uint32_t ga = g0 - 32 * (w & 1) - 576 * (w >> 1), g2 = tp + T_C - 258 - 32 * w + 4 * (t - g);
    F[0][2] = lds1(ga + 48);
#pragma unroll
    for (int j = 0; j < 8; ++j) { F[j][0] = lds1(ga + 32 - 32 * j); F[j][1] = lds1(ga + 16 - 32 * j); }
#pragma unroll
    for (int j = 0; j < 20; ++j) U[j] = lds1(ga - 224 - 16 * j);
#pragma unroll
    for (int j = 0; j < 4; ++j) { LO(qc[j], g2 + 32 * j) HI(qc[j], g2 + 32 * j) }
  }
  if (layer) { mbar_wait(B_ED, 0); mbar_wait(B_ED + 8, 0); }
  sts4z_if(reg + lane * 16 + (w ? w * 3584 + 1024 : 0), w < 3);
  PROF(5, a_pre);
  if (k4 == 3 && w == 3) {
    mbar_wait(B_E, layer);
    mbar_wait(B_K, 0);
#pragma unroll
    for (int h = 0; h < 4; ++h) w_load(mW, c & 7, h);
  }
  const uint32_t bo = reg + R_B + tid * 16 + (v >> 1) * 1056, be = tid == 127 ? reg + R_B + 1024 : bo + (tid == 63 ? 2112 : 1056);
  const uint32_t a9 = (lane & 1) ? be : bo, a7 = (lane & 1) ? bo : be, ua = reg + R_U + uoff(tid);
  const uint32_t h1 = reg + R_U + v * 512 - 64, h2 = h1 + 24 - 16 * lane;
  keep(a9 & a7 & ua & h2, zero);
  mbar_wait(k4 && ((GMASK >> k4) & 1) ? B_G - 8 + 8 * k4 : B_E, layer);
  PROF(6, a_x);
  uint4 x[2];
  uint32_t pv[4];
  {
    uint4 s[4];
    uint32_t u[2][10];
#pragma unroll
    for (int z = 0; z < 2; ++z) { x[z] = lds4(reg + R_B + tid * 16 + z * 2048); s[2 * z] = lds4(SM_RES + tid * 16 + z * 2048); s[2 * z + 1] = lds4(SM_RES + tid * 16 + z * 2048 + 4096); }
    for (int it = 0;; ++it) {
      const uint32_t m = min(min(min((both(x[0].x, x[1].x, layer) | lane) & 1, min(s[0].x, s[0].z)), min(s[1].x, s[1].z)), min(min(s[2].x, s[2].z), min(s[3].x, s[3].z)));
      if (__builtin_expect(__all_sync(0xffffffffu, m != 0u), 1)) break;
      EVENT(16 + layer * 4 + k4);
      const int o = tid | here(zero);
#pragma unroll
      for (int z = 0; z < 2; ++z) x[z] = ldr4(&P.S->XG[(128 * k4 + c) * 256 + o] + z * 128);
#pragma unroll
      for (int z = 0; z < 4; ++z) {
        s[z] = ldr4(&P.S->SR[layer][c >> 4][o] + ((z >> 1) * 128 + (z & 1) * 256));
        sts4(SM_RES + tid * 16 + (z >> 1) * 2048 + (z & 1) * 4096, s[z].x, s[z].y, s[z].z, s[z].w);
      }
      spin_guard(it);
    }
#pragma unroll
    for (int z = 0; z < 2; ++z) {
      u[z][6] = hmul2(hsub2(x[z].x, s[2 * z].y), s[2 * z].x); u[z][7] = hmul2(hsub2(x[z].y, s[2 * z].w), s[2 * z].z);
      u[z][8] = hmul2(hsub2(x[z].z, s[2 * z + 1].y), s[2 * z + 1].x); u[z][9] = hmul2(hsub2(x[z].w, s[2 * z + 1].w), s[2 * z + 1].z);
      sts4(ua + z * 2048, u[z][6], u[z][7], u[z][8], u[z][9]);
    }
    u[1][0] = 0; u[1][1] = s[3].x; u[1][2] = s[2].x; u[1][3] = s[2].y; u[1][4] = s[2].z; u[1][5] = s[2].w;
    if (v < 2) {
#pragma unroll
      for (int j = 1; j < 6; ++j) u[1][j] = shfl_up(u[1][j < 2 ? 8 + j : 4 + j], j < 2 ? 2 : 1);
    }
#pragma unroll
    for (int j = 0; j < 6; ++j) u[0][j] = shfl_up(u[0][j < 2 ? 8 + j : 4 + j], j < 2 ? 2 : 1);
    bar_sync(NB_WG + k4, 128);
    GATE(0)
    PROF(7, a_u);
    halo(u[0], h1, h2, lane);
    halo(u[1], h1 + 2048, h2 + 2048, lane + 16 * (v & 2));
    sts4z_if(reg + R_B + 1040, tid == 0);
    boxes<true>(u[0], reg + tid * 16, a9, a7, pv);
    if (v < 2) boxes<false>(u[1], reg + tid * 16 + 2048, 0, 0, pv);
  }
  GATE(1)
  fence_async_smem();
  if (k4 == 3 && w == 0) {
    const uint32_t src = SM_RES + 8192;
#pragma unroll
    for (int z = 0; z < 4; ++z) sts4(src + lane * 16 + z * 512, 0, 0, 0, 0);
    fence_async_smem();
    __syncwarp();
#pragma unroll
    for (int z = 0; z < 2; ++z) {
      bulk_store(&P.S->H[(c + 8) * 256] + z * 128, src, 2048);
      bulk_store(P.S->F + ((c >> 3) * 64 + 4 * (c & 7)) + z * 32, src, 16);
    }
    bulk_store(&P.S->PS[c * 64], src, 1024);
    bulk_store(&P.S->ST[c * 4], src, 64);
    if (c < 8 && layer) bulk_store(&P.S->CS[c * 48], src, 768);
    if (c < 5) bulk_store(P.S->C + (c + 5 - 5 * layer) * 1024, src, 128 * NCOPY * NSUB);
    asm volatile("cp.async.bulk.commit_group;" ::: "memory");
  }
  const uint32_t id = opq(0x3210u);
#pragma unroll
  for (int j = 0; j < 8; ++j) { F[j][3] = cpy(F[j][0], id); if (j) F[j][2] = cpy(F[j - 1][1], id); }
  PROF(8, a_box);
  bar_sync(NB_T + k4, k4 ? 256 : 128);
  PROF(9, a_turn);
  float acc[32], f1[24], f3[16];
  uint32_t qa[4][4], qb[4][4], fp[4];
  const uint64_t db = mkdesc(reg + R_U, 16, 512, 2) + 2;
#define STEP(mm, n) wg_fence(); mm; wg_commit(); wg_wait<n>();
#define D(j, n) STEP(wg_rs64k(acc, F[j], db - 2 * j, j), n)
#define C(j, n) STEP(wg_rs32t(f3, qc[j], mkdesc(reg + R_B, 128, 1040, 0) + 16 * j, j), n)
#define NIL(q, y) { const uint32_t z = y & zero; q[2][1] = cpy(z, 0); q[2][3] = cpy(z, 1); q[3][1] = cpy(z, 2); q[3][3] = cpy(z, 3); }
#define X(j) F[j][0] = cpy(U[2 * j - 16], ix); F[j][1] = cpy(U[2 * j - 15], ix); F[j][3] = cpy(F[j][0], ix); F[j][2] = cpy(F[j - 1][1], ix);
  const uint32_t g1 = g0 - 2 * 576 - 16 * w;
  const uint64_t d1 = mkdesc(reg + R_A5, 128, 512, 0);
  constexpr int O3 = (R_A3 - R_A5) / 16;
  uint32_t ix = id;
  undef(acc);
  D(0, 4) TURN(0) D(1, 4) D(2, 4) D(3, 4) D(4, 4) D(5, 2)
  undef(f3);
  C(0, 3) C(1, 3) TURN(1) C(2, 3) X(8) C(3, W1) X(9) LO(qa[0], g1)
  D(6, W1) HI(qa[0], g1) X(10) D(7, W1) LO(qa[1], g1 + 32) X(11) D(8, W1) HI(qa[1], g1 + 32) D(9, 4) LO(qa[2], g1 - 64)
  fp[0] = pack2(f3[0], f3[1]); fp[1] = pack2(f3[4], f3[5]); fp[2] = pack2(f3[8] + f3[2], f3[9] + f3[3]); fp[3] = pack2(f3[12] + f3[6], f3[13] + f3[7]);
  ix |= fp[0] & fp[1] & fp[2] & fp[3] & zero;
  X(12) D(10, 4) TURN(2) LO(qa[3], g1 - 32) X(13) X(14) D(11, 4) LO(qb[0], g1 - 192) X(15) D(12, 4) HI(qb[0], g1 - 192) X(16)
  D(13, 4) LO(qb[1], g1 - 160) X(17) D(14, 4) TURN(3) HI(qb[1], g1 - 160) NIL(qa, qa[1][0])
  D(15, 4) LO(qb[2], g1 - 256) D(16, 3) LO(qb[3], g1 - 224) NIL(qb, qa[1][1]) D(17, 2) TURN(4)
  PROF(10, a_den);
  undef(f1);
  wg_fence();
#pragma unroll
  for (int j = 0; j < 4; ++j) wg_rs48t(f1, qa[j], d1 + 16 * (j & 1) - 32 * (j >> 1), j);
  wg_commit();
  wg_wait<1>();
  TURN(5)
  wg_fence();
#pragma unroll
  for (int j = 0; j < 4; ++j) wg_rs48t(f1, qb[j], d1 + O3 + 16 * (j & 1) - 32 * (j >> 1), 1);
  wg_commit();
  TURN(6)
  lane = lane_here(zero);
  bar_sync(NB_WG + k4, 128);
  {
    const int p = (lane + 9 * (w >> 1)) & 31;
    const uint32_t ya = reg + ((w >> 1) ? R_B : R_U) + p * 64 + (((2 * (w & 1)) ^ ((p >> 1) & 3)) * 16), up = p < lane ? 2048 : 0;
#pragma unroll
    for (int z = 0; z < 4; ++z) {
      const float* a = acc + 16 * (z >> 1) + 2 * (z & 1);
      stsm4t((ya + (up ^ ((z >> 1) * 2048))) ^ ((z & 1) * 16), pack2(a[0], a[1]), pack2(a[4], a[5]), pack2(a[8], a[9]), pack2(a[12], a[13]));
    }
  }
  asm volatile("cp.async.bulk.wait_group 0;" ::: "memory");
  const uint32_t fa = reg + R_A5 + (lane >> 3) * 512 + w * 128 + (lane & 7) * 16;
  const uint32_t fc = reg + R_A3 + uoff(64 * (lane >> 4) + 16 * w + 2 * (lane & 7) + 1 - ((lane >> 3) & 1));
  uint32_t k1024 = lds16(tp + T_E - 2 * 639 + (fa & fc & zero));
  wg_wait<0>();
  GATE(2)
  PROF(11, a_far);
  bar_sync(NB_WG + k4, 128);
  stsm4(fc, fp[0], fp[1], fp[2], fp[3]);
  stsm4(fa, pack2(f1[0], f1[1]), pack2(f1[4], f1[5]), pack2(f1[8] + f1[2], f1[9] + f1[3]), pack2(f1[12] + f1[6], f1[13] + f1[7]));
  stsm2(fa + 2048, pack2(f1[16] + f1[10], f1[17] + f1[11]), pack2(f1[20] + f1[14], f1[21] + f1[15]));
  {
    const int o = 32 * v + lane;
    const uint32_t a = reg + uoff(o), b = reg + R_A5 + o * 16;
    uint4 y[2] = {hadd8(lds4(a + R_U), lds4(o >= 36 ? a + R_B : reg)), hadd8(lds4(a + R_U + 2048), lds4(a + R_B + 2048))};
    bar_sync(NB_WG + k4, 128);
    TURN(7)
    PROF(12, a_sts);
    const uint4 f = lds4(v >= 2 ? b - 1024 : reg), f2 = lds4(b + 1024);
    uint4 h = lds4(a + R_A3);
    const int e0 = (o >> 3) * 8192 + (128 * k4 + c) * 16 + (((o & 4) + ((o >> 1) & 1)) ^ (c & 7)) * 2 + (o & 1);
    const uint32_t me = (e0 & 3) == ((c >> 1) & 3), m0 = me & ~c, m1 = me & c, tag = 1 - layer;
    uint32_t* cp = cnt_at(P, 1 + 5 * layer + k4, c, lane);
    keep(cp, zero);
    k1024 = prmt(k1024, k1024, 0x1010);
    h = make_uint4(hfma2(pv[0], k1024, h.x), hfma2(pv[1], k1024, h.y), hfma2(pv[2], k1024, h.z), hfma2(pv[3], k1024, h.w));
    y[0] = hadd8(y[0], f); y[1] = hadd8(y[1], hadd8(f2, h));
    cnt_add(cp, 1 | (y[0].x & y[1].x & zero), (o ^ 96) < NCOPY);
#pragma unroll
    for (int z = 0; z < 2; ++z) {
      const uint4 r = hadd8(x[z], y[z]);
      str2((uint2*)P.S->XF + e0 + z * 131072, tagged(prmt(r.x, r.y, 0x5410), m0, tag), tagged(prmt(r.z, r.w, 0x5410), m1, tag));
      str2((uint2*)P.S->XF + (e0 ^ 4) + z * 131072, tagged(prmt(r.x, r.y, 0x7632), m0, tag), tagged(prmt(r.z, r.w, 0x7632), m1, tag));
    }
  }
  TURN(9)
  GATE(3)
  PROF(13, a_out);
}

#define WGATE 1
#define FH 1
#define QPIN 1
#define XORD 1
DEV void x_load(const Params& P, int c, int q, int layer) {
#pragma unroll
  for (int z = 0; z < 2; ++z) {
    const int e = z ^ (XORD && q == 3 && !(c & 4));
    mbar_expect1(B_X + 16 * q + 8 * e, 16384);
    bulk(xstage(q, e), P.S->XF + ((2 * (c >> 3) + 1 - e) * 4096 + q * 1024), 16384, B_X + 16 * q + 8 * e);
  }
}

DEV void means(uint32_t (&m)[4], int row, int lane, int layer, uint32_t zero) {
  mbar_wait(B_CS, 0);
  mbar_wait(B_ST, layer);
  const uint32_t a = SM_MISC + row * 4 + (lane & 28), k = (lane & 3) ? 0u : ~0u;
  m[0] = lds1(a) & k; m[1] = lds1(a + 32) & k; m[2] = m[0] & zero; m[3] = m[1] & zero;
}

DEV void attn_phase(const Params& P, int c, int e, int w, int lane, int layer) {
  PW(4 * e + w)
  const int cg = c & 7, J = 2 * (c >> 3) + 1 - e;
  float acc[96];
  zerov(acc);
  uint32_t m[4] = {0, 0, 0, 0};
#pragma unroll 1
  for (int q = 0;; ++q) {
    const uint64_t da = mkdesc(xstage(q, e), 16, 1024, 1), db = mkdesc(SM_S0 + (q & 1) * 49152, 8192, 1024, 1);
    const uint32_t wr = mbar_test2(B_W + 16 * q, layer), xa = xstage(q, e) + w * 4096 + lane * 132;
    mbar_wait(B_X + 16 * q + 8 * e, layer);
    for (int it = 0;; ++it) {
      const uint32_t ok = both(lds1(xa), lds1(xa ^ 32), layer) & both(lds1(xa ^ 64), lds1(xa ^ 96), layer);
      if (__all_sync(0xffffffffu, ok & 1)) break;
      EVENT(8 * layer + 2 * q + e);
#pragma unroll 1
      for (int j = 0; j < 8; ++j) cp16(xstage(q, e) + w * 4096 + j * 512 + lane * 16, P.S->XF + (J * 4096 + q * 1024 + w * 256 + j * 32 + lane));
      asm volatile("cp.async.wait_all;" ::: "memory");
      fence_async_smem();
      __syncwarp();
      spin_guard(it);
    }
    bool all = __all_sync(0xffffffffu, wr);
    if (q == 0 && e && w == 0) {
      bar_sync(NB_H, 256);
      cnt_wait(P, 2 + 5 * layer, c, lane);
      x_load(P, c, 1, layer);
      PROF(27, m_xi);
    }
    if (q == 3 && e) means(m, 16 * w, lane, layer, P.zero);
    if (!all) { mbar_wait(B_W + 16 * q, layer); all = mbar_test(B_W + 16 * q + 8, layer); }
    bar_sync(e ? NB_Q : q ? NB_T : NB_T + 4, 256);
    PROF(14 + q, m_q);
    wg_fence();
#pragma unroll
    for (int k = 0; k < 8; ++k) {
      if (k == 4) { wg_commit(); if (!all) mbar_wait(B_W + 16 * q + 8, layer); wg_fence(); }
      wg_ss192(acc, da + k * 128, db + (k >> 2) * 1536 + (k & 3) * 128, 1);
    }
    wg_commit();
    if (q == 3) break;
    bar_arrive(e ? NB_T : NB_Q, 256);
    if (FH) { wg_wait<1>(); mbar_arrive1_if(B_FH + 8 * q, e && q < 2); }
    wg_wait<0>();
    mbar_arrive1(B_F + 8 * q);
  }
  const int pos = 2 - 2 * e + (w >> 1);
  uint4* h = P.S->H + ((c + 8) * 256 + (w & 1) * 128 + lane);
  const uint32_t kw = kvslot(cg, pos + 1) + (w & 1) * 2048 + lane * 16;
  {
    if (!e) means(m, 64 + 16 * w, lane, layer, P.zero);
    PROF(28, m_sub);
    wg_fence();
    wg_rs192t(acc, m, mkdesc(SM_CS, 0, 32, 0));
    wg_commit();
    bar_arrive_if(NB_Q, 256, !e);
    keep(h, kw & P.zero);
    mbar_wait(B_F + 16, layer);
    wg_wait<0>();
    mbar_arrive1(B_F + 24);
  }
  PROF(18, m_qkv);
  uint32_t Q[4][4], K[4][3][2], V[4][3][2];
  uint32_t pin = P.zero;
#pragma unroll
  for (int z = 0; z < 4; ++z) {
    V[z][1][0] = pack2(acc[64 + 8 * z], acc[65 + 8 * z]); V[z][1][1] = pack2(acc[68 + 8 * z], acc[69 + 8 * z]);
    K[z][1][0] = pack2(acc[32 + 8 * z], acc[33 + 8 * z]); K[z][1][1] = pack2(acc[36 + 8 * z], acc[37 + 8 * z]);
    pin &= V[z][1][0] & V[z][1][1];
    K[z][2][0] = nz(pack2(acc[34 + 8 * z], acc[35 + 8 * z])); K[z][2][1] = pack2(acc[38 + 8 * z], acc[39 + 8 * z]);
    V[z][2][0] = pack2(acc[66 + 8 * z], acc[67 + 8 * z]); V[z][2][1] = pack2(acc[70 + 8 * z], acc[71 + 8 * z]);
    str4_if(h + z * 32, K[z][2][0], K[z][2][1], V[z][2][0], V[z][2][1], pos == 3);
  }
#pragma unroll
  for (int z = 0; z < 8; ++z) V[z >> 1][2][z & 1] = movm(z < 7 ? V[z >> 1][2][z & 1] : V[3][2][1] | pin);
  if (pos == 0) mbar_wait(B_F + 24, layer);
#pragma unroll
  for (int z = 0; z < 4; ++z) sts4_if(kw + z * 512, K[z][2][0], K[z][2][1], V[z][2][0], V[z][2][1], pos < 3);
  bar_arrive(NB_H + pos + 1, 128);
  PROF(19, m_kv);
  lane |= here(P.zero);
  int g = lane >> 2, t = lane & 3;
  const uint32_t ra = SM_STAT + 256 + (32 - 32 * e + 8 * w) * 16, ob = e ? SM_S1 : SM_XA;
  const float r0 = lds1f(ra + (g >> 1) * 16 + (g & 1) * 4), r1 = lds1f(ra + 64 + (g >> 1) * 16 + (g & 1) * 4);
  const uint4 k1 = lds4(ra + 16 * t), k2 = lds4(ra + 64 + 16 * t);
#pragma unroll
  for (int z = 0; z < 8; ++z) {
    V[z >> 1][1][z & 1] = movm(V[z >> 1][1][z & 1]);
    Q[z >> 1][2 * (z & 1)] = pack2(acc[4 * z], acc[4 * z + 1]);
    Q[z >> 1][2 * (z & 1) + 1] = pack2(acc[4 * z + 2], acc[4 * z + 3]);
    pin &= Q[z >> 1][2 * (z & 1)] & Q[z >> 1][2 * (z & 1) + 1];
  }
  {
    const bool p0 = 2 * t > g, p1 = 2 * t + 1 > g, first = c < 8 && pos == 0;
    const uint32_t M = (p0 ? 0xFFFFu : 0u) | (p1 ? 0xFFFF0000u : 0u);
    const float sc0 = r0 * (0.25f * 1.4426950408889634f), sc1 = r1 * (0.25f * 1.4426950408889634f);
    const float sk2 = __uint_as_float(p0 ? k1.x : k2.x) * sc1, sk3 = __uint_as_float(p1 ? k1.y : k2.y) * sc1;
    const int oo = cg * 512 + (2 * (w & 2) + (w & 1)) * 64 + (lane ^ (g >> 1));
    uint4* O = P.S->O + (J * 4096 + oo);
    keep(oo, pin & M & __float_as_uint(sk2) & __float_as_uint(sk3) & __float_as_uint(sc0));
    mbar_wait(B_F + 24, layer);
    float L[4][4];
#pragma unroll
    for (int z = 0; z < 4; ++z) {
      float S[4];
      mma16z(L[z], Q[z][0], Q[z][1], Q[z][2], Q[z][3], K[z][1][0], K[z][1][1]);
      mma16z(S, Q[z][0], Q[z][1], Q[z][2], Q[z][3], K[z][2][0], K[z][2][1]);
      L[z][2] = (p0 ? L[z][2] : S[2]) * sk2; L[z][3] = (p1 ? L[z][3] : S[3]) * sk3;
      if (QPIN) pin &= __float_as_uint(L[z][2]) & __float_as_uint(L[z][3]);
    }
    bar_sync(NB_H + pos + pin, pos ? 128 : 160);
    const uint4 k0 = lds4(ra - 192 + 16 * t);
#pragma unroll
    for (int z = 0; z < 4; ++z) {
      const uint4 hv = lds4(kvslot(cg, pos) + (w & 1) * 2048 + lane * 16 + z * 512);
      K[z][0][0] = hv.x; K[z][0][1] = hv.y; V[z][0][0] = hv.z; V[z][0][1] = hv.w;
    }
    PROF(20, m_halo);
    const float sk0 = __uint_as_float(p0 ? k0.x : k1.x) * sc0, sk1 = __uint_as_float(p1 ? k0.y : k1.y) * sc0;
    const uint32_t rm[4] = {k0.z & M, k1.z & ~M, k1.z & M, k2.z & ~M}, s0 = k0.w | P.zero, s1 = k1.w | P.zero;
#pragma unroll
    for (int h2 = 0; h2 < 2; ++h2) {
      uint32_t A[2], B[2], mx[2];
#pragma unroll
      for (int z = 0; z < 2; ++z) {
        const int h = 2 * h2 + z;
        float S[4];
        mma16z(S, Q[h][0], Q[h][1], Q[h][2], Q[h][3], K[h][0][0], K[h][0][1]);
        if (first) { S[0] = __uint_as_float(0xFF800000u); S[1] = S[0]; }
        A[z] = pack2((p0 ? S[0] : L[h][0]) * sk0, L[h][2]);
        B[z] = pack2((p1 ? S[1] : L[h][1]) * sk1, L[h][3]);
      }
#pragma unroll
      for (int z = 0; z < 2; ++z) mx[z] = hmax2(A[z], B[z]);
#pragma unroll
      for (int z = 0; z < 2; ++z) mx[z] = hmax2(mx[z], __shfl_xor_sync(0xffffffffu, mx[z], 1));
#pragma unroll
      for (int z = 0; z < 2; ++z) mx[z] = hmax2(mx[z], __shfl_xor_sync(0xffffffffu, mx[z], 2));
      float Oa[2][3][4];
#pragma unroll
      for (int z = 0; z < 2; ++z) {
        const int h = 2 * h2 + z;
        const uint32_t a = hsub2(A[z], mx[z]), b = hsub2(B[z], mx[z]);
        const uint32_t w0 = pack2(ex2(bflo(a)), ex2(bflo(b))), w1 = pack2(ex2(bfhi(a)), ex2(bfhi(b)));
        const uint32_t u0 = hmul2(w0, rm[0]), u1 = hmul2(w0, rm[1]), u2 = hmul2(w1, rm[2]), u3 = hmul2(w1, rm[3]);
        const uint32_t z0 = w0 & P.zero, z1 = w1 & P.zero;
        mma16z(Oa[z][2], u0, z0, u1, u2, s0, s1);
#pragma unroll
        for (int d = 0; d < 2; ++d) mma16z(Oa[z][d], u0, z0, u1, u2, V[h][0][d], V[h][1][d]);
        mma8(Oa[z][2], z1, u3, k2.w);
#pragma unroll
        for (int d = 0; d < 2; ++d) mma8(Oa[z][d], z1, u3, V[h][2][d]);
      }
#pragma unroll
      for (int r = 0; r < 4; r += 2) {
        const float i0 = rcp(Oa[0][2][r]), i1 = rcp(Oa[1][2][r]);
        const uint32_t o0 = pack2(Oa[0][0][r] * i0, Oa[0][0][r + 1] * i0), o1 = pack2(Oa[0][1][r] * i0, Oa[0][1][r + 1] * i0);
        const uint32_t o2 = pack2(Oa[1][0][r] * i1, Oa[1][0][r + 1] * i1), o3 = pack2(Oa[1][1][r] * i1, Oa[1][1][r + 1] * i1);
        str4(O + h2 * 32 + r * 64, o0, o1, o2, o3);
        sts4(ob + oo * 16 + h2 * 512 + r * 1024, o0, o1, o2, o3);
      }
    }
  }
  bar_arrive(NB_T + 1 + e, 160);
  fence_async_smem();
  PROF(21, m_att);
  lane = lane_here(P.zero); g = lane >> 2; t = lane & 3;
  uint32_t res[8][2];
  mbar_wait(B_RES, layer);
  {
    const uint32_t a = SM_RES + e * 8192 + (lane >> 4) * 1024 + (lane & 7) * 128 + (((2 * (w & 2) + ((lane >> 2) & 2) + (w & 1)) ^ (lane & 7)) * 16);
#pragma unroll
    for (int j = 0; j < 8; j += 2) ldsm4t(res[j][0], res[j][1], res[j + 1][0], res[j + 1][1], a + j * 1024);
  }
  PROF(26, m_res);
  if (WGATE) bar_sync(NB_T, 256); else bar_sync(NB_WG + e, 128);
  XgAddr xa = xg_addr<true>(P.S->XG + (64 * cg * 256 + 8 * J), ob, w, lane, P.zero);
  uint4* ps = &P.S->PS[((4 * J + w) * 8 + cg) * 8 + g];
  keep(ps, P.zero);
  if (layer) {
    xa.a = ob + w * 2048 + (lane & 15) * 128 + (((lane >> 4) ^ (lane & 7)) * 16);
    xa.b = ob + w * 2048 + (lane >> 3) * 128 + (((lane & 7) ^ (lane >> 3)) * 16);
    xa.dst = (uint4*)P.out + ((64 * J + 16 * w + 2 * (lane >> 3)) * 64 + 8 * cg + (lane & 7));
  }
  uint32_t y[8][2];
#pragma unroll 1
  for (int it = 0;; ++it) {
    float ac[32];
#pragma unroll
    for (int j = 0; j < 16; ++j) {
      asm volatile("shl.b32 %0,%1,16;" : "=f"(ac[2 * j]) : "r"(res[j >> 1][j & 1]));
      asm volatile("and.b32 %0,%1,0xFFFF0000;" : "=f"(ac[2 * j + 1]) : "r"(res[j >> 1][j & 1]));
    }
#pragma unroll 1
    for (int n = 0; n < 8; ++n) {
      const int s = n == 0 ? cg : n - (n <= cg);
      mbar_wait(n ? B_O + 64 * e + 8 * s : B_WO, layer);
      if (n == 1) PROF(22, m_o1);
      if (n == 7) PROF(23, m_o7);
      const uint64_t da = mkdesc(ob + s * 8192, 16, 1024, 2), db = mkdesc(SM_R + s * 8192, 16, 1024, 1);
      wg_fence();
#pragma unroll
      for (int k = 0; k < 4; ++k) wg_ss64(ac, da + (k >> 1) * 32 + (k & 1) * 2, db + k * 128, 1);
      wg_commit();
    }
    wg_wait<0>();
    const bool bad = ac[0] != ac[0] || ac[2] != ac[2];
#pragma unroll
    for (int j = 0; j < 8; ++j) {
      y[j][0] = pack2(ac[4 * j], ac[4 * j + 1]); y[j][1] = pack2(ac[4 * j + 2], ac[4 * j + 3]);
    }
    if (!bar_any(NB_WG + e, 128, bad) || it == 16) break;
    EVENT(24 + 2 * layer + e);
    refetch(ob, P.S->O + J * 4096, 32768, e, w);
  }
  PROF(24, m_wo);
  if (layer == 0) {
    const float4 s = gram(y, g, P.zero);
    xg_put<true>(xa, y);
    str4_if(ps, nz(__float_as_uint(s.x)), __float_as_uint(s.y), __float_as_uint(s.z), __float_as_uint(s.w), t == (g >> 1));
    mbar_arrive1(B_ED + 8 * e);
    bar_sync(NB_WG + e, 128);
    xg_store(xa, 0);
    bar_arrive(NB_T + 3, 288);
  } else {
#pragma unroll
    for (int j = 0; j < 8; j += 2) stsm4(xa.a ^ (j * 16), y[j][0], y[j][1], y[j + 1][0], y[j + 1][1]);
    __syncwarp();
#pragma unroll
    for (int k = 0; k < 4; ++k) {
      const uint4 v = lds4((xa.b ^ ((k & 1) * 64)) + k * 512);
      stw4(xa.dst + ((k & 1) * 8 + (k >> 1)) * 64, v.x, v.y, v.z, v.w);
    }
  }
  PROF(25, m_epi);
}

#define HDELAY 300
#define ODELAY 200
#define FDELAY 300
#define PZB B_X + 48
#define WOQ 2
#define H5 1
#define SRDELAY 350

DEV void o_load(const Params& P, int c, int e, int lane, int layer) {
  PW(8 + e)
  const int J = 2 * (c >> 3) + 1 - e;
#pragma unroll 1
  for (int s = 0; s < 8; ++s) mbar_expect1(B_O + 64 * e + 8 * s, s == (c & 7) ? 0 : 8192);
  const uint4* src = P.S->O + J * 4096;
  const uint32_t* fp = P.S->F + (J * 32 + (lane & 28));
  keep(fp, P.zero);
  bar_sync(NB_T + 1 + e, 160);
  flag_set1(P.S->F + (J * 32 + 4 * (c & 7)));
  if (ODELAY) delay(ODELAY);
  PROF(26, a_go);
  poll(fp, 1);
  PROF(25, h_seen);
  bar_sync_if(NB_Q, 64, e);
#pragma unroll 1
  for (int n = 0; n < 7; ++n) {
    const int s = n + (n >= (c & 7));
    bulk((e ? SM_S1 : SM_XA) + s * 8192, src + s * 512, 8192, B_O + 64 * e + 8 * s);
  }
  bar_arrive_if(NB_Q, 64, !e);
  PROF(28, a_o);
}

DEV void stats(const Params& P, int c, int w, int lane, int layer) {
  PW(12 + w)
  lane = opq(lane);
  const int r = 2 * (lane >> 3), k = (2 * (c & 3) + ((lane >> 2) & 1)) ^ r, e = 1 - ((c >> 2) & 1);
  const uint32_t o = (32 * w + r) * 128 + k * 16 + (lane & 3) * 4;
  const uint32_t no0 = (lane & 7) != r, no1 = ((lane & 7) ^ 4) != r + 1;
  uint32_t* st = (uint32_t*)P.S->ST + (16 * c + 2 * (lane & 7) + (lane >> 4));
  keep(st, P.zero);
  float v[4] = {0.f, 0.f, 0.f, 0.f};
#pragma unroll 1
  for (int q = 0; q < 4; ++q) {
    mbar_wait(B_X + 16 * q + 8 * e, layer);
    PROF(19 + q, s_l);
    uint32_t x[8];
    for (int it = 0;; ++it) {
#pragma unroll
      for (int z = 0; z < 8; ++z) x[z] = lds1v(xstage(q, e) + (o ^ ((z & 1) * 144)) + (z >> 1) * 1024);
      const uint32_t ok = (both(x[0], x[2], layer) & both(x[4], x[6], layer) | no0) & (both(x[1], x[3], layer) & both(x[5], x[7], layer) | no1);
      if (__all_sync(0xffffffffu, ok & 1)) break;
      spin_guard(it);
    }
    mbar_arrive1(B_F + 8 * q);
#pragma unroll
    for (int z = 0; z < 8; ++z) {
      const float lo = bflo(x[z]), hi = bfhi(x[z]);
      v[0] += lo; v[1] += lo * lo; v[2] += hi; v[3] += hi * hi;
    }
  }
  PROFD(14, s_part, __float_as_uint(v[0]));
  fold<2>(v, lane, 16); fold<1>(v, lane, 8);
  PROFD(16, s_fold, __float_as_uint(v[0]));
  if (w) {
    sts1(SM_MISC - 128 + w * 128 + lane * 4, __float_as_uint(v[0]));
    bar_arrive(NB_P, 128);
  } else {
    mbar_wait(B_ST + 8, layer);
    bar_sync(NB_P, 128);
    v[0] += lds1f(SM_MISC + lane * 4) + lds1f(SM_MISC + 128 + lane * 4) + lds1f(SM_MISC + 256 + lane * 4);
    float m;
    const float sd = ln_sd(v[0], __shfl_xor_sync(0xffffffffu, v[0], 8), m);
    if (!(lane & 8)) str1(st, pack2(m, sd));
    PROF(17, s_pub);
    uint4 s;
    for (int it = 0;; ++it) {
      s = ldr4(P.S->ST + ((c >> 3) * 32 + lane));
      if (__all_sync(0xffffffffu, min4(s) != 0u)) break;
      spin_guard(it);
    }
    PROF(18, s_seen);
    const float r0 = rcp(bfhi(s.x)), r1 = rcp(bfhi(s.y)), r2 = rcp(bfhi(s.z)), r3 = rcp(bfhi(s.w));
    const uint32_t sg = 0x80008000u;
    sts4(SM_MISC + lane * 16, prmt(s.x, s.x, 0x1010) ^ sg, prmt(s.y, s.y, 0x1010) ^ sg, prmt(s.z, s.z, 0x1010) ^ sg, prmt(s.w, s.w, 0x1010) ^ sg);
    sts4(SM_STAT + 256 + lane * 32, __float_as_uint(r0), __float_as_uint(r1), pack2(r0, r1), prmt(s.x, s.y, 0x7632));
    sts4(SM_STAT + 272 + lane * 32, __float_as_uint(r2), __float_as_uint(r3), pack2(r2, r3), prmt(s.z, s.w, 0x7632));
    __syncwarp();
    mbar_arrive1(B_ST);
  }
  PROF(15, s_stat);
  if (w == 1) {
    mbar_wait(B_ST, layer);
    if (c >= 8) {
      uint2 s;
      for (int it = 0;; ++it) {
        s = ldr2((const uint2*)P.S->ST + ((c >> 3) * 64 - 12 + (lane & 11)));
        if (__all_sync(0xffffffffu, min(s.x, s.y) != 0u)) break;
        spin_guard(it);
      }
      const float r0 = rcp(bfhi(s.x)), r1 = rcp(bfhi(s.y));
      sts4(SM_STAT + 64 + (lane & 11) * 16, __float_as_uint(r0), __float_as_uint(r1), pack2(r0, r1), prmt(s.x, s.y, 0x7632));
    }
    bar_arrive(NB_H, 160);
  }
  if (w >= 2) {
    const uint4* h = P.S->H + (c * 256 + (w & 1) * 128 + lane);
    uint4 hv[4];
#pragma unroll
    for (int z = 0; z < 4; ++z) hv[z] = make_uint4(0, 0, 0, 0);
    bar_sync(NB_RL, 128);
    PROFD(26, s_hb, lds1v(SM_MISC));
    delay(HDELAY);
    for (int it = 0; c >= 8; ++it) {
#pragma unroll
      for (int z = 0; z < 4; ++z) hv[z] = ldr4(h + z * 32);
      if (__all_sync(0xffffffffu, min(min(hv[0].x, hv[1].x), min(hv[2].x, hv[3].x)) != 0u)) break;
      spin_guard(it);
    }
    mbar_wait(B_F + 24, layer);
#pragma unroll
    for (int z = 0; z < 4; ++z) sts4(kvslot(c & 7, 0) + (w & 1) * 2048 + lane * 16 + z * 512, hv[z].x, hv[z].y, movm(hv[z].z), movm(hv[z].w));
    bar_arrive(NB_H, 160);
    PROF(25, s_halo);
  }
}

DEV void finalize(const Params& P, int c, int lane, int layer) {
  PW(12)
  uint2* so = (uint2*)P.S->SR[layer] + ((lane >> 3) * 1024 + (lane & 2) * 256 + 4 * c + ((lane >> 1) & 2) + (lane & 1));
  const uint4* ps = &P.S->PS[c * 64 + lane];
  keep(so, P.zero); keep(ps, P.zero);
  uint4 a, b;
  if (layer == 0) {
    bar_sync(NB_P, 256);
    a = lds4(SM_RES + 8192 + lane * 16); b = lds4(SM_RES + 8704 + lane * 16);
  } else {
    mbar_wait(B_ED + 8 - 2 * (c & 4), 0);
    delay(FDELAY);
    for (int it = 0;; ++it) {
      a = ldr4(ps); b = ldr4(ps + 32);
      if (__all_sync(0xffffffffu, min(a.x, b.x) != 0u)) break;
      spin_guard(it);
    }
  }
  float z[4] = {__uint_as_float(a.x) + __uint_as_float(b.x), __uint_as_float(a.y) + __uint_as_float(b.y),
                __uint_as_float(a.z) + __uint_as_float(b.z), __uint_as_float(a.w) + __uint_as_float(b.w)};
#pragma unroll
  for (int o = 8; o < 32; o <<= 1)
#pragma unroll
    for (int k = 0; k < 4; ++k) z[k] += __shfl_xor_sync(0xffffffffu, z[k], o);
  const float m0 = z[0] * (1.f / 512.f), m1 = z[2] * (1.f / 512.f);
  const float r0 = rsq(fmaxf(z[1] * (1.f / 512.f) - m0 * m0, 0.f) + 1e-5f), r1 = rsq(fmaxf(z[3] * (1.f / 512.f) - m1 * m1, 0.f) + 1e-5f);
  const uint32_t wr = nz(pack2(r0, r1)), wm = pack2(m0, m1);
  str2(so, wr, wm); str2(so + 4096, wr, wm);
  bar_arrive_if(NB_Q, 448, !layer);
  PROF(23, s_sr);
}

DEV void announce(const Params& P, int c, int lane, int layer) {
  PW(13)
  uint32_t* cp = cnt_at(P, 5 * layer, c, lane);
  keep(cp, P.zero);
  bar_sync(NB_T + 3, 288);
  cnt_add(cp, 1, lane < NCOPY);
  if (!layer) { bar_sync(NB_Q, 448); fence_async_smem(); }
  PROF(24, s_own);
}

DEV void fetch(const Params& P, int c, int lane, int layer) {
  PW(13)
  mbar_expect1(B_E, 24576);
  cnt_wait(P, 5 * layer, c, lane);
#pragma unroll
  for (int k = 0; k < 4; ++k) bulk(SM_R + k * 16384 + R_B, P.S->XG + (128 * k + c) * 256, 4096, B_E);
  if (layer) delay(SRDELAY);
  bulk(SM_RES, P.S->SR[layer][c >> 4], 8192, B_E);
  if (!layer) { l2_prefetch(P.wqkv + c * 6144, 12288); l2_prefetch(P.wo + c * 2048, 4096); }
  PROF(25, s_all);
}

DEV float2 cs_rows(const Params& P, int row, int col, int lane) {
  float cs[8];
#pragma unroll
  for (int k = 0; k < 8; ++k) cs[k] = 0.f;
  uint4 v[8];
#pragma unroll
  for (int k = 0; k < 8; ++k) v[k] = ldnc4(P.wqkv + ((row + (lane >> 3)) * 1536 + col + 8 * (lane & 7)) + 4 * k * 1536);
#pragma unroll
  for (int k = 0; k < 8; ++k) {
    cs[0] += bflo(v[k].x); cs[1] += bfhi(v[k].x); cs[2] += bflo(v[k].y); cs[3] += bfhi(v[k].y);
    cs[4] += bflo(v[k].z); cs[5] += bfhi(v[k].z); cs[6] += bflo(v[k].w); cs[7] += bfhi(v[k].w);
  }
  fold<4>(cs, lane, 16); fold<2>(cs, lane, 8);
  return make_float2(cs[0], cs[1]);
}
DEV void cs_put(const Params& P, int b, int lane, float x, float y) {
  const uint32_t hi = pack2(x, y);
  uint32_t* p = (uint32_t*)P.S->CS + ((b & 7) * 192 + (b >> 3) * 64 + (lane & 7) * 8 + (lane >> 3));
  str1(p, nz(hi)); str1(p + 4, nz(pack2(x - bflo(hi), y - bfhi(hi))));
}
DEV void cs_spare(const Params& P, const CUtensorMap* mW, int j, int n, int warp, int lane) {
  mbar_init1(B_W + 8 * warp, warp < 8 ? 1 : 12);
  sts2f(SM_TAP + lane * 8, __uint_as_float(0x3F803F80u), __uint_as_float(0x3F803F80u));
  fence_async_smem();
  __syncthreads();
#pragma unroll 1
  for (int cg = j, ph = 0; cg < 8; cg += n, ph ^= 1) {
    if (warp == 12) {
#pragma unroll 1
      for (int h = 0; h < 8; ++h) {
        mbar_wait(B_W + 64 + 8 * h, ph ^ 1);
        mbar_expect1(B_W + 8 * h, 24576);
        tma3(SB + h * 24576, mW, 64 * cg, 64 * h, B_W + 8 * h);
      }
    } else if (warp < 12) {
      float d[4];
      zerov(d);
#pragma unroll 1
      for (int h = 0; h < 8; ++h) {
        mbar_wait(B_W + 8 * h, ph);
        wg_fence();
#pragma unroll
        for (int k = 0; k < 4; ++k) wg_ss8(d, mkdesc(SB + h * 24576 + (warp >> 2) * 8192, 16, 1024, 1) + k * 128, mkdesc(SM_TAP, 128, 128, 0));
        wg_commit();
        wg_wait<0>();
        mbar_arrive1(B_W + 64 + 8 * h);
      }
      const float x = (lane & 2) ? d[2] : d[0], y = __shfl_xor_sync(0xffffffffu, x, 4);
      const uint32_t hi = pack2(x, y), lo = pack2(x - bflo(hi), y - bfhi(hi));
      if (!(lane & 4)) str1((uint32_t*)P.S->CS + (cg * 192 + warp * 16 + (lane & 3) * 4 + (lane >> 3)), nz((lane & 1) ? lo : hi));
      __syncwarp();
    }
  }
}
DEV void cs_alone(const Params& P, int b, int lane) {
  float x = 0.f, y = 0.f;
#pragma unroll 1
  for (int k = 0; k < 16; ++k) { const float2 u = cs_rows(P, 32 * k, 64 * b, lane); x += u.x; y += u.y; }
  cs_put(P, b, lane, x, y);
}
DEV void cs_get(const Params& P, int cg, int lane) {
  const uint4* p = (const uint4*)P.S->CS + (cg * 48 + min(lane, 23) * 2);
  uint4 a, b;
  for (int it = 0;; ++it) {
    a = ldr4(p); b = ldr4(p + 1);
    if (__all_sync(0xffffffffu, min(min4(a), min4(b)) != 0u)) break;
    spin_guard(it);
  }
  sts4(SM_CS + min(lane, 23) * 32, a.x, a.y, a.z, a.w); sts4(SM_CS + min(lane, 23) * 32 + 16, b.x, b.y, b.z, b.w);
  fence_async_smem();
  __syncwarp();
  mbar_arrive1(B_CS);
}

DEV void x0_get(uint32_t (&x)[8][2], uint32_t a) {
  asm volatile("cp.async.wait_group 0;" ::: "memory");
#pragma unroll
  for (int z = 0; z < 4; ++z) {
    const uint4 v = lds4(a + z * 512);
    x[2 * (z & 2)][z & 1] = v.x; x[2 * (z & 2) + 1][z & 1] = v.y; x[2 * (z & 2) + 2][z & 1] = v.z; x[2 * (z & 2) + 3][z & 1] = v.w;
  }
}

DEV void par_load(const Params& P, int ch, int m, uint32_t (&pv)[8], bool c) {
  const int mo = ch * 128 + m;
  pv[0] = ld16_if(P.Are + mo, c); pv[1] = ld16_if(P.Aim + mo, c); pv[2] = ld16_if(P.Bre + mo, c); pv[3] = ld16_if(P.Bim + mo, c);
  pv[4] = ld16_if(P.Cre + mo, c); pv[5] = ld16_if(P.Cim + mo, c); pv[6] = ld16_if(P.logdt + ch, c); pv[7] = ld16_if(P.dskip + ch, c);
}

template <bool BY_SM> __global__ void __launch_bounds__(NTHR, 1)
fused_kernel(const __grid_constant__ Params P, const __grid_constant__ CUtensorMap mapW,
             const __grid_constant__ CUtensorMap mapWo) {
  extern __shared__ __align__(1024) uint8_t smem_raw[];
  uint32_t smid; asm("mov.u32 %0,%%smid;" : "=r"(smid));
  const int role = P.role[(BY_SM ? smid : blockIdx.x) + (threadIdx.x >> 10)];
  uint32_t pv[8];
  par_load(P, (threadIdx.x & 384) + (role & 127), threadIdx.x & 127, pv, threadIdx.x < 384 && role < 128);
  const int warp0 = __shfl_sync(0xffffffffu, threadIdx.x >> 5, 0), lane0 = threadIdx.x & 31, c = __shfl_sync(0xffffffffu, role, 0);
  if (c >= 128) {
    if (threadIdx.x < NCOPY * NSUB)
#pragma unroll 1
      for (int it = 0; it < 256 && ldr1(P.S->C + 32 * threadIdx.x) < 128 / NSUB; ++it) __nanosleep(200);
    __syncwarp();
    cs_spare(P, &mapW, c - 128, gridDim.x - 128, warp0, lane0);
    return;
  }
  const int cg = c & 7;
  PW(warp0)
  uint32_t dskip;
  {
    [[maybe_unused]] const int layer = 0;
    const int lane = lane0, g = lane >> 2, t = lane & 3, warp = warp0, k4 = warp >> 2, w = warp & 3;
    __syncthreads();
    const uint16_t* r = P.x0 + ((k4 < 2 ? 8192 * c + 64 * warp : (128 * (c >> 3) + 16 * (warp - 8)) * 512 + 64 * cg) + 1024 * g + 8 * t);
    const uint32_t xa = SM_R + k4 * 16384 + w * 2048 + lane * 16;
#pragma unroll
    for (int z = 0; z < 4; ++z) cp16(xa + z * 512, r + (z & 1) * 512 + (z & 2) * 16);
    asm volatile("cp.async.commit_group;" ::: "memory");
    sts4(SM_TAP + k4 * TAP_SZ + (32 * w + lane) * 16, 0, 0, 0, 0);
    sts4z_if(SM_TAP + k4 * TAP_SZ + 2048 + (32 * w + lane) * 16, w < 3);
    const XgAddr xd = xg_addr<false>(P.S->XG + (64 * cg * 256 + 16 * (c >> 3) + 8 * (k4 & 1)), SM_R + k4 * 16384 + 8192, w, lane, P.zero);
    uint32_t x[8][2];
    if (k4 == 3) {
      if (threadIdx.x == 448) {
        asm volatile("prefetch.tensormap [%0];" :: "l"(&mapW) : "memory");
        asm volatile("prefetch.tensormap [%0];" :: "l"(&mapWo) : "memory");
      }
      __syncwarp();
      par_load(P, 128 * k4 + c, 32 * w + lane, pv, true);
      if (s2u(smem_raw) != SB) __trap();
      sts4(SM_STAT - 32 + min(lane, 17) * 16, 0x3F800000u, 0x3F800000u, 0x3F803F80u, 0x3F803F80u);
      x0_get(x, xa);
      PROF(27, a_ld);
      xg_put<false>(xd, x);
      bar_sync(NB_WG + 3, 128);
      xg_store(xd, 1);
      bar_arrive(NB_T + 3, 288);
#pragma unroll
      for (int n = 0; n < 14; ++n) mbar_init1(SM_BAR + (n < 10 ? w * 80 : 240 + w * 32) + n * 8, n < 10 ? 1 : (CNT >> (8 * w + 2 * (n - 10 & 2))) & 15);
      bar_sync(NB_Q, 448);
    }
    tables(pv, k4, w, lane);
    if (k4 < 3) {
      x0_get(x, xa);
      if (k4 < 2) {
        const float4 s = gram(x, g, P.zero);
        if (t == (g >> 1)) sts4f(SM_RES + 8192 + (warp * 8 + g) * 16, s.x, s.y, s.z, s.w);
        __syncwarp();
        bar_arrive_if(NB_P, 256, warp != 7);
      } else {
        xg_put<false>(xd, x);
        bar_sync(NB_WG + 2, 128);
        xg_store(xd, 1);
        bar_arrive(NB_T + 3, 288);
      }
    }
    dskip = pv[7];
    PROF(1, a_x0);
  }
#pragma unroll 1
  for (int layer = 0; layer < 2; ++layer) {
    int lane = lane_here(P.zero);
    const int warp = warp0 | (layer & P.zero), k4 = warp >> 2, w = warp & 3;
    if (warp == (layer ? 12 : 7)) finalize(P, c, lane, layer);
    if (warp == (layer ? 13 : 6)) { announce(P, c, lane, layer); fetch(P, c, lane, layer); }
    if (layer == 0) {
      taps(dskip, k4, w, lane);
    }
    conv(P, &mapW, c, k4, w, layer);
    lane = lane_here(P.zero);
    if (k4 < 2) {
      bar_arrive_if(NB_H, 256, warp != 4);
      if (warp == 0) {
        mbar_wait(B_K, 0);
        cnt_wait(P, 1 + 5 * layer, c, lane);
        x_load(P, c, 0, layer);
        PROF(27, m_xi);
      }
      attn_phase(P, c, k4, w, lane, layer);
    } else {
      bar_arrive_if(NB_RL, 256, warp >= 10);
      if (k4 == 3) {
        stats(P, c, w, lane, layer);
      } else if (w < 2) {
        bar_sync_if(NB_RL, 256, w);
        cnt_wait(P, 3 + 5 * layer + w, c, lane);
        bar_sync_if(NB_RL, 256, !w);
        if (w) mbar_wait(B_F, layer);
        x_load(P, c, 2 + w, layer);
        if (H5 && w) w_load(&mapW, cg, 5);
        PROF(14, h_xi);
        if (w == 1) str4(&P.S->SR[layer][lane >> 2][4 * c + (lane & 3)], 0, 0, 0, 0);
      } else if (w == 2) {
        mbar_expect1(B_WO, 65536);
        mbar_expect1(B_RES, 16384);
#pragma unroll 1
        for (int q = 0; q < 4; ++q) {
          if (FH && q < 2) { mbar_wait(B_FH + 8 * q, layer); w_load(&mapW, cg, 4 + 2 * q); }
          mbar_wait(B_F + 8 * q, layer);
          if (!FH && q < 2) w_load(&mapW, cg, 4 + 2 * q);
          if (q == 1 || (q == 0 && !H5)) w_load(&mapW, cg, 5 + 2 * q);
          if (WOQ == 0 && ((q + 1) & 2)) tma5(SM_R + (q & 2) * 16384, &mapWo, 64 * cg, 4 * (q & 2), B_WO);
          if (WOQ && q == 2) {
            if (WOQ >= 2) mbar_wait(B_ST, layer);
            tma5(SM_R, &mapWo, 64 * cg, 0, B_WO);
            if (WOQ < 3) tma5(SM_R + 32768, &mapWo, 64 * cg, 8, B_WO);
          }
          if (q == 3) {
#pragma unroll
            for (int e = 0; e < 2; ++e) bulk(SM_RES + e * 8192, P.S->XF + ((2 * (c >> 3) + 1 - e) * 4096 + cg * 512), 8192, B_RES);
          }
          PROF(15 + q, h_w);
        }
      }
      if (warp == 11) {
        if (!BY_SM && c < 24 && layer == 0) cs_alone(P, c, lane);
#pragma unroll
        for (int z = 0; z < 8; ++z) sts4(SM_RES + 10240 + lane * 16 + z * 512, ~0u, ~0u, ~0u, ~0u);
        fence_async_smem();
        mbar_wait(PZB, layer);
#pragma unroll
        for (int z = 0; z < 4; ++z) bulk_store(&P.S->O[((c >> 3) * 16 + cg) * 512] + ((z >> 1) * 4096 + (z & 1) * 256), SM_RES + 10240, 4096);
        asm volatile("cp.async.bulk.commit_group;\ncp.async.bulk.wait_group 0;" ::: "memory");
        mbar_arrive1(B_ST + 8);
        PROF(18, h_pz);
      }
      if (warp == 8 && layer == 0) { cs_get(P, cg, lane); PROF(20, h_cs); }
      if (warp < 10) o_load(P, c, w, lane, layer);
    }
    asm volatile("mov.b32 %0,0;" : "=r"(dskip));
  }
}

typedef CUresult (*EncodeFn)(CUtensorMap*, CUtensorMapDataType, cuuint32_t, void*, const cuuint64_t*, const cuuint64_t*,
                             const cuuint32_t*, const cuuint32_t*, CUtensorMapInterleave, CUtensorMapSwizzle,
                             CUtensorMapL2promotion, CUtensorMapFloatOOBfill);

#define PLAIN false
static int place_roles(uint8_t* role) {
  int dev = 0, nsm = 0;
  cudaGetDevice(&dev);
  cudaDeviceGetAttribute(&nsm, cudaDevAttrMultiProcessorCount, dev);
  if (nsm <= 128 || nsm > 144 || (nsm & 1)) return 0;
  cudaFuncSetAttribute(fused_kernel<true>, cudaFuncAttributeNonPortableClusterSizeAllowed, 1);
  int occ[9] = {0};
  for (int k = 2; k <= 8; ++k) {
    cudaLaunchConfig_t cfg = {};
    cudaLaunchAttribute at[1];
    at[0].id = cudaLaunchAttributeClusterDimension;
    at[0].val.clusterDim.x = 2 * k; at[0].val.clusterDim.y = 1; at[0].val.clusterDim.z = 1;
    cfg.gridDim = dim3(2 * k); cfg.blockDim = dim3(NTHR); cfg.dynamicSmemBytes = SM_TOTAL; cfg.attrs = at; cfg.numAttrs = 1;
    if (cudaOccupancyMaxActiveClusters(&occ[k], fused_kernel<true>, &cfg) != cudaSuccess) { cudaGetLastError(); occ[k] = 0; }
  }
  int n[10];
  n[7] = occ[8]; n[6] = occ[7]; n[5] = occ[6] - 0; n[4] = occ[5];
  n[3] = occ[4] - n[7]; n[1] = occ[2] - n[3] - n[5] - n[7]; n[0] = n[2] = n[1];
  n[8] = occ[3] - n[2] - n[5];
  const int ntpc = nsm / 2;
  int sum = 0;
  bool ok = n[0] > 0 && n[0] <= 8;
  for (int r = 0; r < 9; ++r) { ok = ok && n[r] >= 0 && (r == 0 || n[r] <= n[r - 1]); sum += n[r]; }
  if (!ok || sum > ntpc) { for (int r = 0; r < 9; ++r) n[r] = r < 8 ? 8 : 0; sum = 64; }
  int tp[8][9], cnt[8] = {0}, pool[72], np = 0, id = 0;
  for (int r = 0; r < 9; ++r)
    for (int g = n[0] - n[r]; g < n[0]; ++g) tp[g][cnt[g]++] = id++;
  for (; id < ntpc; ++id) pool[np++] = id;
  int order[72], no = 0;
  for (int g = 0; g < n[0]; ++g) {
    const int full = cnt[g] / 4 * 4;
    for (int k = 0; k < cnt[g]; ++k) { if (k < full) order[no++] = tp[g][k]; else pool[np++] = tp[g][k]; }
  }
  for (int k = 0; k < np; ++k) order[no++] = pool[k];
  for (int k = 0; k < ntpc; ++k) { role[2 * order[k]] = 2 * k; role[2 * order[k] + 1] = 2 * k + 1; }
  return nsm;
}

extern "C" void kernel_launch(void* const* d_in, const int* in_sizes, int n_in, void* d_out, int out_size) {
  (void)in_sizes; (void)n_in; (void)out_size;
  static EncodeFn enc = nullptr;
  static uint8_t role[144];
  static int nsm = 0;
  static void* scratch = nullptr;
  if (!enc) {
    void* fn = nullptr;
    cudaDriverEntryPointQueryResult qr;
    cudaGetDriverEntryPoint("cuTensorMapEncodeTiled", &fn, cudaEnableDefault, &qr);
    enc = (EncodeFn)fn;
    cudaFuncSetAttribute(fused_kernel<true>, cudaFuncAttributeMaxDynamicSharedMemorySize, SM_TOTAL);
    cudaFuncSetAttribute(fused_kernel<PLAIN>, cudaFuncAttributeMaxDynamicSharedMemorySize, SM_TOTAL);
    nsm = place_roles(role);
    cudaGetSymbolAddress(&scratch, g_S);
  }
  CUtensorMap mW, mWo;
  {
    cuuint64_t dim[3] = {512, 512, 3}, str[2] = {3072, 1024};
    cuuint32_t box[3] = {64, 64, 3}, es[3] = {1, 1, 1};
    enc(&mW, CU_TENSOR_MAP_DATA_TYPE_BFLOAT16, 3, d_in[10], dim, str, box, es, CU_TENSOR_MAP_INTERLEAVE_NONE,
        CU_TENSOR_MAP_SWIZZLE_128B, CU_TENSOR_MAP_L2_PROMOTION_NONE, CU_TENSOR_MAP_FLOAT_OOB_FILL_NONE);
  }
  {
    cuuint64_t dim[5] = {512, 2, 4, 4, 16}, str[4] = {1024, 8192, 2048, 32768};
    cuuint32_t box[5] = {64, 2, 4, 4, 8}, es[5] = {1, 1, 1, 1, 1};
    enc(&mWo, CU_TENSOR_MAP_DATA_TYPE_BFLOAT16, 5, d_in[11], dim, str, box, es, CU_TENSOR_MAP_INTERLEAVE_NONE,
        CU_TENSOR_MAP_SWIZZLE_128B, CU_TENSOR_MAP_L2_PROMOTION_NONE, CU_TENSOR_MAP_FLOAT_OOB_FILL_NONE);
  }
  Params P;
  P.x0 = (const uint16_t*)d_in[0]; P.Are = (const uint16_t*)d_in[1]; P.Aim = (const uint16_t*)d_in[2];
  P.Bre = (const uint16_t*)d_in[3]; P.Bim = (const uint16_t*)d_in[4]; P.Cre = (const uint16_t*)d_in[5];
  P.Cim = (const uint16_t*)d_in[6]; P.logdt = (const uint16_t*)d_in[7]; P.dskip = (const uint16_t*)d_in[8];
  P.wqkv = (const uint16_t*)d_in[10]; P.wo = (const uint16_t*)d_in[11]; P.out = (uint16_t*)d_out;
  for (int k = 0; k < 144; ++k) P.role[k] = nsm > 0 ? role[k] : k;
  P.pad = 0;
  P.zero = 0;
  P.S = (Scratch*)scratch;
  if (nsm > 0) fused_kernel<true><<<nsm, NTHR, SM_TOTAL, cudaStreamPerThread>>>(P, mW, mWo);
  else fused_kernel<PLAIN><<<128, NTHR, SM_TOTAL, cudaStreamPerThread>>>(P, mW, mWo);
}
```

```cpp
#include <cuda_runtime.h>
#include <cuda_bf16.h>
#include <cuda.h>
#include <stdint.h>

#define DEV __device__ __forceinline__

#define NCOPY 4
#define NSUB 1
constexpr int NTHR = 512;
constexpr int SPIN_LIMIT = 1 << 22;

constexpr uint32_t SB = 1024;
constexpr uint32_t SM_XA   = SB;
constexpr uint32_t SM_S0   = SM_XA + 16384;
constexpr uint32_t SM_S1   = SM_S0 + 49152;
constexpr uint32_t SM_XB   = SM_S1 + 49152;
constexpr uint32_t SM_R    = SM_XB + 16384;
constexpr uint32_t SM_RES  = SM_R + 65536;
constexpr uint32_t SM_TAP  = SM_RES + 16384;
constexpr int TAP_SZ = 3584;
constexpr uint32_t SM_CS   = SM_TAP + 4 * TAP_SZ;
constexpr uint32_t SM_STAT = SM_CS + 800;
constexpr uint32_t SM_MISC = SM_STAT + 1280;
constexpr uint32_t SM_BAR  = SM_MISC + 512;
constexpr int SM_TOTAL = SM_BAR + 448 - SB;
constexpr int R_U = 512, R_A5 = 5120, R_A3 = 8704, R_B = 11776;
constexpr int T_E = 1536, T_O = T_E + 1602, T_C = 3714;
constexpr uint32_t B_W = SM_BAR, B_X = SM_BAR + 64, B_O = SM_BAR + 128, B_WO = SM_BAR + 256, B_RES = SM_BAR + 264;
constexpr uint32_t B_ST = SM_BAR + 272, B_R = SM_BAR + 288, B_E = SM_BAR + 304;
constexpr uint32_t B_F = SM_BAR + 320, B_G = SM_BAR + 352, B_K = SM_BAR + 376, B_ED = SM_BAR + 384, B_CS = SM_BAR + 400, B_FH = SM_BAR + 416;
constexpr uint32_t CNT = 0x141444CC;
constexpr int NB_WG = 1, NB_T = 5, NB_Q = 10, NB_H = 11, NB_P = 14, NB_RL = 15;

struct Scratch {
  uint32_t F[32 * 32];
  uint4    H[17 * 8 * 256];
  uint4    SR[2][8][512];
  uint4    ST[32 * 16];
  uint4    PS[128 * 64];
  uint4    CS[8 * 48];
  uint32_t C[10 * 32 * 32];
  uint4    XF[32 * 4096];
  uint4    O[32 * 8 * 512];
  uint4    XG[512 * 256];
};
__device__ __align__(1024) Scratch g_S;

struct Params {
  const uint16_t *logdt, *dskip, *Are, *Aim, *Bre, *Bim, *Cre, *Cim, *x0, *wqkv, *wo;
  uint16_t* out;
  Scratch* S;
  uint32_t zero, pad;
  uint8_t role[144];
};
#define EVENT(n) do {} while (0)
#define PROFD(slot, name, v) do {} while (0)
#define PROF(slot, name) do {} while (0)
#define PW(x)

DEV uint32_t s2u(const void* p) { return (uint32_t)__cvta_generic_to_shared(p); }
template <class T> DEV T opq(T x) { asm volatile("" : "+r"(x)); return x; }
DEV uint32_t pack2(float lo, float hi) { uint32_t d; asm("cvt.rn.bf16x2.f32 %0,%1,%2;" : "=r"(d) : "f"(hi), "f"(lo)); return d; }
DEV float bflo(uint32_t v) { return __uint_as_float(v << 16); }
DEV float bfhi(uint32_t v) { return __uint_as_float(v & 0xFFFF0000u); }
DEV float bfr(float x) { return bflo(pack2(x, 0.f)); }
DEV uint32_t hadd2(uint32_t a, uint32_t b) { uint32_t d; asm("add.rn.bf16x2 %0,%1,%2;" : "=r"(d) : "r"(a), "r"(b)); return d; }
DEV uint32_t hsub2(uint32_t a, uint32_t b) { uint32_t d; asm("sub.rn.bf16x2 %0,%1,%2;" : "=r"(d) : "r"(a), "r"(b)); return d; }
DEV uint32_t hmul2(uint32_t a, uint32_t b) { uint32_t d; asm("mul.rn.bf16x2 %0,%1,%2;" : "=r"(d) : "r"(a), "r"(b)); return d; }
DEV uint32_t hfma2(uint32_t a, uint32_t b, uint32_t c) { uint32_t d; asm("fma.rn.bf16x2 %0,%1,%2,%3;" : "=r"(d) : "r"(a), "r"(b), "r"(c)); return d; }
DEV uint32_t hmax2(uint32_t a, uint32_t b) { uint32_t d; asm("max.bf16x2 %0,%1,%2;" : "=r"(d) : "r"(a), "r"(b)); return d; }
DEV uint32_t prmt(uint32_t a, uint32_t b, uint32_t s) { uint32_t d; asm("prmt.b32 %0,%1,%2,%3;" : "=r"(d) : "r"(a), "r"(b), "r"(s)); return d; }
DEV uint32_t nz(uint32_t v) { uint32_t d; asm("max.u32 %0,%1,1;" : "=r"(d) : "r"(v)); return d; }
DEV uint32_t tagged(uint32_t v, uint32_t m, uint32_t tag) { uint32_t d; asm("lop3.b32 %0,%1,%2,%3,0xB8;" : "=r"(d) : "r"(v), "r"(m), "r"(tag)); return d; }
DEV uint32_t both(uint32_t a, uint32_t b, uint32_t x) { uint32_t d; asm("lop3.b32 %0,%1,%2,%3,0x42;" : "=r"(d) : "r"(a), "r"(b), "r"(x)); return d; }
DEV uint4 hadd8(const uint4& a, const uint4& b) { return make_uint4(hadd2(a.x, b.x), hadd2(a.y, b.y), hadd2(a.z, b.z), hadd2(a.w, b.w)); }
DEV uint32_t min4(const uint4& v) { return min(min(v.x, v.y), min(v.z, v.w)); }
DEV float rcp(float x) { float y; asm("rcp.approx.ftz.f32 %0,%1;" : "=f"(y) : "f"(x)); return y; }
DEV float sqrt_(float x) { float y; asm("sqrt.approx.ftz.f32 %0,%1;" : "=f"(y) : "f"(x)); return y; }
DEV float rsq(float x) { float y; asm("rsqrt.approx.ftz.f32 %0,%1;" : "=f"(y) : "f"(x)); return y; }
DEV float ex2(float x) { float y; asm("ex2.approx.ftz.f32 %0,%1;" : "=f"(y) : "f"(x)); return y; }

DEV uint4 ldr4(const void* p) { uint4 v; asm volatile("ld.relaxed.gpu.global.v4.u32 {%0,%1,%2,%3},[%4];" : "=r"(v.x), "=r"(v.y), "=r"(v.z), "=r"(v.w) : "l"(p) : "memory"); return v; }
DEV void ldr4_if(uint4& v, const void* p, bool c) {
  asm volatile("{.reg .pred q; setp.ne.u32 q,%5,0; @q ld.relaxed.gpu.global.v4.u32 {%0,%1,%2,%3},[%4];}"
    : "+r"(v.x), "+r"(v.y), "+r"(v.z), "+r"(v.w) : "l"(p), "r"((uint32_t)c) : "memory");
}
DEV uint2 ldr2(const void* p) { uint2 v; asm volatile("ld.relaxed.gpu.global.v2.u32 {%0,%1},[%2];" : "=r"(v.x), "=r"(v.y) : "l"(p) : "memory"); return v; }
DEV uint32_t ldr1(const void* p) { uint32_t v; asm volatile("ld.relaxed.gpu.global.u32 %0,[%1];" : "=r"(v) : "l"(p) : "memory"); return v; }
DEV void str4(void* p, uint32_t a, uint32_t b, uint32_t c, uint32_t d) { asm volatile("st.relaxed.gpu.global.v4.u32 [%0],{%1,%2,%3,%4};" :: "l"(p), "r"(a), "r"(b), "r"(c), "r"(d) : "memory"); }
DEV void str4_if(void* p, uint32_t a, uint32_t b, uint32_t c, uint32_t d, bool q) {
  asm volatile("{.reg .pred q; setp.ne.u32 q,%5,0; @q st.relaxed.gpu.global.v4.u32 [%0],{%1,%2,%3,%4};}" :: "l"(p), "r"(a), "r"(b), "r"(c), "r"(d), "r"((uint32_t)q) : "memory");
}
DEV void str2(void* p, uint32_t a, uint32_t b) { asm volatile("st.relaxed.gpu.global.v2.u32 [%0],{%1,%2};" :: "l"(p), "r"(a), "r"(b) : "memory"); }
DEV void str1(void* p, uint32_t a) { asm volatile("st.relaxed.gpu.global.u32 [%0],%1;" :: "l"(p), "r"(a) : "memory"); }
DEV void stw4(void* p, uint32_t a, uint32_t b, uint32_t c, uint32_t d) { asm volatile("st.global.v4.u32 [%0],{%1,%2,%3,%4};" :: "l"(p), "r"(a), "r"(b), "r"(c), "r"(d) : "memory"); }
DEV uint4 ldnc4(const void* p) { uint4 v; asm volatile("ld.global.nc.v4.u32 {%0,%1,%2,%3},[%4];" : "=r"(v.x), "=r"(v.y), "=r"(v.z), "=r"(v.w) : "l"(p)); return v; }
DEV uint4 ldw4(const void* p) { uint4 v; asm volatile("ld.global.v4.u32 {%0,%1,%2,%3},[%4];" : "=r"(v.x), "=r"(v.y), "=r"(v.z), "=r"(v.w) : "l"(p) : "memory"); return v; }
DEV void cp16(uint32_t d, const void* p) { asm volatile("cp.async.cg.shared.global [%0],[%1],16;" :: "r"(d), "l"(p) : "memory"); }
DEV uint32_t ld16_if(const void* p, bool c) { uint32_t v = 0; asm volatile("{.reg .pred q; setp.ne.u32 q,%2,0; @q ld.global.u16 %0,[%1];}" : "+r"(v) : "l"(p), "r"((uint32_t)c) : "memory"); return v; }
DEV uint32_t ldnc16(const void* p) { uint32_t v; asm volatile("ld.global.u16 %0,[%1];" : "=r"(v) : "l"(p) : "memory"); return v; }

DEV uint32_t lds1v(uint32_t a) { uint32_t v; asm volatile("ld.volatile.shared.u32 %0,[%1];" : "=r"(v) : "r"(a) : "memory"); return v; }
DEV uint4 lds4v(uint32_t a) { uint4 v; asm volatile("ld.volatile.shared.v4.u32 {%0,%1,%2,%3},[%4];" : "=r"(v.x), "=r"(v.y), "=r"(v.z), "=r"(v.w) : "r"(a) : "memory"); return v; }
DEV uint32_t lds1(uint32_t a) { uint32_t v; asm volatile("ld.shared.u32 %0,[%1];" : "=r"(v) : "r"(a)); return v; }
DEV uint2 lds2(uint32_t a) { uint2 v; asm volatile("ld.shared.v2.u32 {%0,%1},[%2];" : "=r"(v.x), "=r"(v.y) : "r"(a)); return v; }
DEV uint4 lds4(uint32_t a) { uint4 v; asm volatile("ld.shared.v4.u32 {%0,%1,%2,%3},[%4];" : "=r"(v.x), "=r"(v.y), "=r"(v.z), "=r"(v.w) : "r"(a)); return v; }
DEV uint32_t lds16(uint32_t a) { uint32_t v; asm volatile("ld.shared.u16 %0,[%1];" : "=r"(v) : "r"(a)); return v; }
DEV float lds1f(uint32_t a) { float v; asm volatile("ld.shared.f32 %0,[%1];" : "=f"(v) : "r"(a)); return v; }
DEV float2 lds2f(uint32_t a) { float2 v; asm volatile("ld.shared.v2.f32 {%0,%1},[%2];" : "=f"(v.x), "=f"(v.y) : "r"(a)); return v; }
DEV float4 lds4f(uint32_t a) { float4 v; asm volatile("ld.shared.v4.f32 {%0,%1,%2,%3},[%4];" : "=f"(v.x), "=f"(v.y), "=f"(v.z), "=f"(v.w) : "r"(a)); return v; }
DEV void sts1(uint32_t a, uint32_t v) { asm volatile("st.shared.u32 [%0],%1;" :: "r"(a), "r"(v) : "memory"); }
DEV void sts16(uint32_t a, uint32_t v) { asm volatile("{.reg .b16 h; cvt.u16.u32 h,%1; st.shared.u16 [%0],h;}" :: "r"(a), "r"(v) : "memory"); }
DEV void sts2f(uint32_t a, float x, float y) { asm volatile("st.shared.v2.f32 [%0],{%1,%2};" :: "r"(a), "f"(x), "f"(y) : "memory"); }
DEV void sts4f(uint32_t a, float x, float y, float z, float w) { asm volatile("st.shared.v4.f32 [%0],{%1,%2,%3,%4};" :: "r"(a), "f"(x), "f"(y), "f"(z), "f"(w) : "memory"); }
DEV void sts4(uint32_t a, uint32_t x, uint32_t y, uint32_t z, uint32_t w) { asm volatile("st.shared.v4.u32 [%0],{%1,%2,%3,%4};" :: "r"(a), "r"(x), "r"(y), "r"(z), "r"(w) : "memory"); }
DEV void sts4_if(uint32_t a, uint32_t x, uint32_t y, uint32_t z, uint32_t w, bool c) {
  asm volatile("{.reg .pred q; setp.ne.u32 q,%5,0; @q st.shared.v4.u32 [%0],{%1,%2,%3,%4};}" :: "r"(a), "r"(x), "r"(y), "r"(z), "r"(w), "r"((uint32_t)c) : "memory");
}
DEV void sts4z_if(uint32_t a, bool c) { asm volatile("{.reg .pred q; setp.ne.u32 q,%1,0; @q st.shared.v4.u32 [%0],{%2,%2,%2,%2};}" :: "r"(a), "r"((uint32_t)c), "r"(0) : "memory"); }

DEV void ldsm4t(uint32_t& r0, uint32_t& r1, uint32_t& r2, uint32_t& r3, uint32_t a) { asm volatile("ldmatrix.sync.aligned.m8n8.x4.trans.shared.b16 {%0,%1,%2,%3},[%4];" : "=r"(r0), "=r"(r1), "=r"(r2), "=r"(r3) : "r"(a) : "memory"); }
DEV void stsm4(uint32_t a, uint32_t r0, uint32_t r1, uint32_t r2, uint32_t r3) { asm volatile("stmatrix.sync.aligned.m8n8.x4.shared.b16 [%0],{%1,%2,%3,%4};" :: "r"(a), "r"(r0), "r"(r1), "r"(r2), "r"(r3) : "memory"); }
DEV void stsm2(uint32_t a, uint32_t r0, uint32_t r1) { asm volatile("stmatrix.sync.aligned.m8n8.x2.shared.b16 [%0],{%1,%2};" :: "r"(a), "r"(r0), "r"(r1) : "memory"); }
DEV void stsm4t(uint32_t a, uint32_t r0, uint32_t r1, uint32_t r2, uint32_t r3) { asm volatile("stmatrix.sync.aligned.m8n8.x4.trans.shared.b16 [%0],{%1,%2,%3,%4};" :: "r"(a), "r"(r0), "r"(r1), "r"(r2), "r"(r3) : "memory"); }
DEV uint32_t movm(uint32_t a) { uint32_t d; asm volatile("movmatrix.sync.aligned.m8n8.trans.b16 %0,%1;" : "=r"(d) : "r"(a)); return d; }
DEV void mma16(float (&d)[4], uint32_t a0, uint32_t a1, uint32_t a2, uint32_t a3, uint32_t b0, uint32_t b1) {
  asm volatile("mma.sync.aligned.m16n8k16.row.col.f32.bf16.bf16.f32 {%0,%1,%2,%3},{%4,%5,%6,%7},{%8,%9},{%0,%1,%2,%3};"
    : "+f"(d[0]), "+f"(d[1]), "+f"(d[2]), "+f"(d[3]) : "r"(a0), "r"(a1), "r"(a2), "r"(a3), "r"(b0), "r"(b1));
}
DEV void mma16z(float (&d)[4], uint32_t a0, uint32_t a1, uint32_t a2, uint32_t a3, uint32_t b0, uint32_t b1) {
  asm volatile("mma.sync.aligned.m16n8k16.row.col.f32.bf16.bf16.f32 {%0,%1,%2,%3},{%4,%5,%6,%7},{%8,%9},{%10,%10,%10,%10};"
    : "=f"(d[0]), "=f"(d[1]), "=f"(d[2]), "=f"(d[3]) : "r"(a0), "r"(a1), "r"(a2), "r"(a3), "r"(b0), "r"(b1), "f"(0.f));
}
DEV void mma8z(float (&d)[4], uint32_t a0, uint32_t a1, uint32_t b0) {
  asm volatile("mma.sync.aligned.m16n8k8.row.col.f32.bf16.bf16.f32 {%0,%1,%2,%3},{%4,%5},{%6},{%7,%7,%7,%7};"
    : "=f"(d[0]), "=f"(d[1]), "=f"(d[2]), "=f"(d[3]) : "r"(a0), "r"(a1), "r"(b0), "f"(0.f));
}
DEV void mma8(float (&d)[4], uint32_t a0, uint32_t a1, uint32_t b0) {
  asm volatile("mma.sync.aligned.m16n8k8.row.col.f32.bf16.bf16.f32 {%0,%1,%2,%3},{%4,%5},{%6},{%0,%1,%2,%3};"
    : "+f"(d[0]), "+f"(d[1]), "+f"(d[2]), "+f"(d[3]) : "r"(a0), "r"(a1), "r"(b0));
}

DEV void bar_sync(int id, int n) { asm volatile("bar.sync %0,%1;" :: "r"(id), "r"(n) : "memory"); }
DEV void bar_arrive(int id, int n) { asm volatile("bar.arrive %0,%1;" :: "r"(id), "r"(n) : "memory"); }
DEV void bar_sync_if(int id, int n, int c) { asm volatile("{.reg .pred q; setp.ne.s32 q,%2,0; @q bar.sync %0,%1;}" :: "r"(id), "r"(n), "r"(c) : "memory"); }
DEV void bar_arrive_if(int id, int n, int c) { asm volatile("{.reg .pred q; setp.ne.s32 q,%2,0; @q bar.arrive %0,%1;}" :: "r"(id), "r"(n), "r"(c) : "memory"); }
DEV bool bar_any(int id, int n, bool c) {
  uint32_t r; asm volatile("{.reg .pred p,q; setp.ne.u32 q,%3,0; bar.red.or.pred p,%1,%2,q; selp.u32 %0,1,0,p;}" : "=r"(r) : "r"(id), "r"(n), "r"((uint32_t)c) : "memory");
  return __any_sync(0xffffffffu, r);
}
DEV void fence_async_glob() { asm volatile("fence.proxy.async.global;" ::: "memory"); }
DEV void fence_async_smem() { asm volatile("fence.proxy.async.shared::cta;" ::: "memory"); }
DEV void fence_gpu() { asm volatile("fence.acq_rel.gpu;" ::: "memory"); }
DEV void mbar_wait(uint32_t b, uint32_t ph) {
  asm volatile("{\n.reg .pred p;\nW: mbarrier.try_wait.parity.shared::cta.b64 p,[%0],%1;\n@!p bra W;\n}" :: "r"(b), "r"(ph) : "memory");
}
DEV bool mbar_test(uint32_t b, uint32_t ph) {
  uint32_t r; asm volatile("{.reg .pred p; mbarrier.test_wait.parity.shared::cta.b64 p,[%1],%2; selp.u32 %0,1,0,p;}" : "=r"(r) : "r"(b), "r"(ph) : "memory");
  return __all_sync(0xffffffffu, r);
}
DEV uint32_t mbar_test2(uint32_t b, uint32_t ph) {
  uint32_t r; asm volatile("{.reg .pred p,q; mbarrier.test_wait.parity.shared::cta.b64 p,[%1],%2; mbarrier.test_wait.parity.shared::cta.b64 q,[%1+8],%2;\n"
                           "and.pred p,p,q; selp.u32 %0,1,0,p;}" : "=r"(r) : "r"(b), "r"(ph) : "memory");
  return r;
}
DEV void spin_guard(int it) { asm volatile("{.reg .pred p; setp.gt.s32 p,%0,%1; @p trap;}" :: "r"(it), "n"(SPIN_LIMIT)); }
DEV uint32_t here(uint32_t zero) {
  uint32_t d; asm volatile("mov.u32 %0,%%clock;" : "=r"(d) :: "memory"); return d & zero;
}
DEV int lane_here(uint32_t zero) {
  uint32_t d; asm volatile("mov.u32 %0,%%laneid;" : "=r"(d)); return d | here(zero);
}
DEV void delay(uint32_t n) {
  asm volatile("{\n.reg .pred p;\n.reg .u32 a,b;\nmov.u32 a,%%clock;\nW: mov.u32 b,%%clock;\nsub.u32 b,b,a;\nsetp.lt.u32 p,b,%0;\n@p bra.uni W;\n}" :: "r"(n) : "memory");
}
DEV void poll(const uint32_t* p, uint32_t n) {
  for (int it = 0; !__all_sync(0xffffffffu, ldr1(p) >= n); ++it) spin_guard(it);
}
DEV uint32_t* cnt_at(const Params& P, int n, int c, int lane) { return P.S->C + (32 * (NSUB * lane + c % NSUB) + n * 1024); }
DEV void cnt_add(uint32_t* p, uint32_t one, bool q) { asm volatile("{.reg .pred p; setp.ne.u32 p,%2,0; @p red.relaxed.gpu.global.add.u32 [%0],%1;}" :: "l"(p), "r"(one), "r"((uint32_t)q) : "memory"); }
DEV void cnt_wait(const Params& P, int n, int c, int lane) { poll(P.S->C + (32 * (NSUB * (c / (128 / NCOPY)) + lane % NSUB) + n * 1024), 128 / NSUB); }
DEV void mbar_init1(uint32_t b, int n) { asm volatile("{.reg .pred p; elect.sync _|p,0xffffffff; @p mbarrier.init.shared::cta.b64 [%0],%1;}" :: "r"(b), "r"(n) : "memory"); }
DEV void mbar_arrive1(uint32_t b) { asm volatile("{.reg .pred p; elect.sync _|p,0xffffffff; @p mbarrier.arrive.shared::cta.b64 _,[%0];}" :: "r"(b) : "memory"); }
DEV void mbar_arrive1_if(uint32_t b, int c) {
  asm volatile("{.reg .pred p,q; setp.ne.s32 q,%1,0; elect.sync _|p,0xffffffff; and.pred p,p,q; @p mbarrier.arrive.shared::cta.b64 _,[%0];}" :: "r"(b), "r"(c) : "memory");
}
DEV void mbar_expect1(uint32_t b, int bytes) { asm volatile("{.reg .pred p; elect.sync _|p,0xffffffff; @p mbarrier.arrive.expect_tx.shared::cta.b64 _,[%0],%1;}" :: "r"(b), "r"(bytes) : "memory"); }
DEV void flag_set1(uint32_t* q) { asm volatile("{.reg .pred p; elect.sync _|p,0xffffffff; @p st.relaxed.gpu.global.u32 [%0],1;}" :: "l"(q) : "memory"); }
DEV void tma3(uint32_t dst, const CUtensorMap* m, int c0, int c1, uint32_t bar) {
  asm volatile("{.reg .pred p; elect.sync _|p,0xffffffff;\n"
    "@p cp.async.bulk.tensor.3d.shared::cluster.global.mbarrier::complete_tx::bytes [%0],[%1,{%2,%3,%5}],[%4];}"
    :: "r"(dst), "l"(m), "r"(c0), "r"(c1), "r"(bar), "r"(0) : "memory");
}
DEV void tma5(uint32_t dst, const CUtensorMap* m, int c0, int c4, uint32_t bar) {
  asm volatile("{.reg .pred p; elect.sync _|p,0xffffffff;\n"
    "@p cp.async.bulk.tensor.5d.shared::cluster.global.mbarrier::complete_tx::bytes [%0],[%1,{%2,%5,%5,%5,%3}],[%4];}"
    :: "r"(dst), "l"(m), "r"(c0), "r"(c4), "r"(bar), "r"(0) : "memory");
}
DEV void bulk(uint32_t dst, const void* src, int bytes, uint32_t bar) {
  asm volatile("{.reg .pred p; elect.sync _|p,0xffffffff;\n@p cp.async.bulk.shared::cluster.global.mbarrier::complete_tx::bytes [%0],[%1],%2,[%3];}" :: "r"(dst), "l"(src), "r"(bytes), "r"(bar) : "memory");
}
DEV void bulk_store(void* dst, uint32_t src, int bytes) {
  asm volatile("{.reg .pred p; elect.sync _|p,0xffffffff;\n@p cp.async.bulk.global.shared::cta.bulk_group [%0],[%1],%2;}" :: "l"(dst), "r"(src), "r"(bytes) : "memory");
}
DEV void l2_prefetch(const void* src, int bytes) {
  asm volatile("{.reg .pred p; elect.sync _|p,0xffffffff;\n@p cp.async.bulk.prefetch.L2.global [%0],%1;}" :: "l"(src), "r"(bytes) : "memory");
}

DEV uint64_t mkdesc(uint32_t addr, uint32_t lbo, uint32_t sbo, uint32_t swz) {
  return (uint64_t)((addr >> 4) | ((lbo >> 4) << 16)) | ((uint64_t)((sbo >> 4) | (swz << 30)) << 32);
}
DEV void wg_fence() { asm volatile("wgmma.fence.sync.aligned;" ::: "memory"); }
DEV void wg_commit() { asm volatile("wgmma.commit_group.sync.aligned;" ::: "memory"); }
template <int N> DEV void wg_wait() { asm volatile("wgmma.wait_group.sync.aligned %0;" :: "n"(N) : "memory"); }
template <int N> DEV void zerov(float (&d)[N]) {
#pragma unroll
  for (int i = 0; i < N; ++i) asm volatile("mov.b32 %0,0;" : "=f"(d[i]));
}
template <int N> DEV void undef(float (&d)[N]) {
#pragma unroll
  for (int i = 0; i < N; ++i) asm volatile("" : "=f"(d[i]));
}
#define R4(d, o) "+f"(d[o]), "+f"(d[o + 1]), "+f"(d[o + 2]), "+f"(d[o + 3])
#define R8(d, o) R4(d, o), R4(d, o + 4)
#define R16(d, o) R8(d, o), R8(d, o + 8)
#define R32(d, o) R16(d, o), R16(d, o + 16)
#define L0 "%0,%1,%2,%3,%4,%5,%6,%7,%8,%9,"
#define L10(a) "%" #a "0,%" #a "1,%" #a "2,%" #a "3,%" #a "4,%" #a "5,%" #a "6,%" #a "7,%" #a "8,%" #a "9,"
#define WG_HEAD(pr, n) "{.reg .pred p; setp.ne.s32 p,%" #pr ",0;\nwgmma.mma_async.sync.aligned.m64n" #n "k16.f32.bf16.bf16 {"
DEV void wg_rs64k(float (&d)[32], const uint32_t (&a)[4], uint64_t db, int acc) {
  asm volatile(WG_HEAD(37, 64) L0 L10(1) L10(2) "%30,%31},{%32,%33,%34,%35},%36,p,1,1,0;}"
    : R32(d, 0) : "r"(a[0]), "r"(a[1]), "r"(a[2]), "r"(a[3]), "l"(db), "r"(acc));
}
DEV void wg_rs48t(float (&d)[24], const uint32_t (&a)[4], uint64_t db, int acc) {
  asm volatile(WG_HEAD(29, 48) L0 L10(1) "%20,%21,%22,%23},{%24,%25,%26,%27},%28,p,1,1,1;}"
    : R16(d, 0), R8(d, 16) : "r"(a[0]), "r"(a[1]), "r"(a[2]), "r"(a[3]), "l"(db), "r"(acc));
}
DEV void wg_rs32t(float (&d)[16], const uint32_t (&a)[4], uint64_t db, int acc) {
  asm volatile(WG_HEAD(21, 32) L0 "%10,%11,%12,%13,%14,%15},{%16,%17,%18,%19},%20,p,1,1,1;}"
    : R16(d, 0) : "r"(a[0]), "r"(a[1]), "r"(a[2]), "r"(a[3]), "l"(db), "r"(acc));
}
DEV void wg_ss8(float (&d)[4], uint64_t da, uint64_t db) {
  asm volatile("wgmma.mma_async.sync.aligned.m64n8k16.f32.bf16.bf16 {%0,%1,%2,%3},%4,%5,1,1,1,1,0;" : R4(d, 0) : "l"(da), "l"(db));
}
DEV void wg_ss48(float (&d)[24], uint64_t da, uint64_t db, int acc) {
  asm volatile(WG_HEAD(26, 48) L0 L10(1) "%20,%21,%22,%23},%24,%25,p,1,1,1,1;}" : R16(d, 0), R8(d, 16) : "l"(da), "l"(db), "r"(acc));
}
DEV void wg_ss64(float (&d)[32], uint64_t da, uint64_t db, int acc) {
  asm volatile(WG_HEAD(34, 64) L0 L10(1) L10(2) "%30,%31},%32,%33,p,1,1,0,1;}" : R32(d, 0) : "l"(da), "l"(db), "r"(acc));
}
DEV void wg_ss192(float (&d)[96], uint64_t da, uint64_t db, int acc) {
  asm volatile(WG_HEAD(98, 192) L0 L10(1) L10(2) L10(3) L10(4) L10(5) L10(6) L10(7) L10(8) "%90,%91,%92,%93,%94,%95},%96,%97,p,1,1,1,1;}"
    : R32(d, 0), R32(d, 32), R32(d, 64) : "l"(da), "l"(db), "r"(acc));
}

DEV void wg_rs192t(float (&d)[96], const uint32_t (&a)[4], uint64_t db) {
  asm volatile("wgmma.mma_async.sync.aligned.m64n192k16.f32.bf16.bf16 {" L0 L10(1) L10(2) L10(3) L10(4) L10(5) L10(6) L10(7) L10(8) "%90,%91,%92,%93,%94,%95},{%96,%97,%98,%99},%100,1,1,1,1;"
    : R32(d, 0), R32(d, 32), R32(d, 64) : "r"(a[0]), "r"(a[1]), "r"(a[2]), "r"(a[3]), "l"(db));
}

DEV float ln_sd(float s, float q, float& m) {
  m = s * (1.f / 512.f);
  return bfr(sqrt_(bfr(bfr(fmaxf(q * (1.f / 512.f) - m * m, 0.f)) + 1e-5f)));
}
DEV float4 gram(const uint32_t (&w)[8][2], int g, uint32_t zero) {
  float s[4], q[4][4];
  const uint32_t o0 = 0x3F803F80u | zero, o1 = 0x3F803F80u ^ zero;
#pragma unroll
  for (int j = 0; j < 8; ++j) {
#pragma unroll
    for (int h = 0; h < 2; ++h) { if (j < 2) mma8z(q[2 * j + h], w[j][0], w[j][1], w[j][h]); else mma8(q[2 * (j & 1) + h], w[j][0], w[j][1], w[j][h]); }
    if (j == 1) mma16z(s, w[0][0], w[0][1], w[1][0], w[1][1], o0, o1);
    else if (j & 1) mma16(s, w[j - 1][0], w[j - 1][1], w[j][0], w[j][1], o0, o1);
  }
  const bool od = g & 1;
  return make_float4(s[0], od ? q[0][1] + q[2][1] : q[0][0] + q[2][0], s[2], od ? q[1][3] + q[3][3] : q[1][2] + q[3][2]);
}
DEV void keep(uint32_t v, uint32_t zero) {
  asm volatile("{.reg .pred p; setp.ne.u32 p,%1,0; @p st.shared.u32 [%0],%0;}" :: "r"(v), "r"(zero) : "memory");
}
DEV void keep(const void* v, uint32_t zero) { asm volatile("{.reg .pred p; setp.ne.u32 p,%1,0; @p st.global.u32 [%0],%1;}" :: "l"(v), "r"(zero) : "memory"); }
struct XgAddr { uint32_t a, b; uint4* dst; };
template <bool FRAG> DEV XgAddr xg_addr(uint4* dst, uint32_t stg, int wp, int lane, uint32_t zero) {
  const int t = lane & 3, r = 4 * wp + (lane >> 3);
  XgAddr x = {stg + t * (FRAG ? 256 : 1024) + ((wp ^ t) * 32) + (lane >> 2) * 4,
              stg + r * 128 + (((lane & 7) ^ (2 * (((r >> 1) ^ (r >> 3)) & 3))) * 16), dst + (r * 256 + (lane & 7))};
  keep(x.a, zero); keep(x.b, zero); keep(x.dst, zero);
  return x;
}
template <bool FRAG> DEV void xg_put(const XgAddr& x, const uint32_t (&w)[8][2]) {
#pragma unroll
  for (int n = 0; n < 8; ++n) {
    const uint32_t b = (x.a ^ ((n & 3) * 32)) + (FRAG ? n * 1024 : (n >> 2) * 4096 + (n & 3) * 256);
    sts1(b, prmt(w[n][0], w[n][1], 0x5410)); sts1(b + 128, prmt(w[n][0], w[n][1], 0x7632));
  }
}
DEV void xg_store(const XgAddr& x, uint32_t tag) {
  const uint32_t m = (~x.b >> 4) & 1;
#pragma unroll
  for (int k = 0; k < 4; ++k) {
    const uint4 v = lds4((x.b ^ ((k & 1) * 64)) + k * 2048);
    str4(x.dst + k * 4096, tagged(v.x, m, tag), v.y, v.z, v.w);
  }
}
template <int N, int M> DEV void fold(float (&v)[M], int lane, int bit) {
  const bool b = lane & bit;
#pragma unroll
  for (int k = 0; k < N; ++k) { const float sn = b ? v[k] : v[k + N], kp = b ? v[k + N] : v[k]; v[k] = kp + __shfl_xor_sync(0xffffffffu, sn, bit); }
}
DEV int piece(int n, int cg) { return n ? n - (n <= cg) : cg; }
DEV uint32_t kvslot(int pos) { return (pos & 2 ? SM_XA : SM_S1) + 16384 + (pos & 1) * 4096; }
DEV uint32_t xstage(int q, int e) { return ((q + 1) & 2) ? SM_R + ((q & 2) + e) * 16384 : e ? SM_XB : SM_XA; }
DEV void cmul(float& orr, float& oi, float ar, float ai, float br, float bi) {
  float r = ar * br - ai * bi, i = ar * bi + ai * br; orr = r; oi = i;
}
DEV void cexp_(float al, float bt, float s, float& er, float& ei) {
  float mag = ex2(al * s), ph = bt * s;
  ph -= rintf(ph);
  float ang = ph * 6.283185307179586f;
  er = mag * __cosf(ang); ei = mag * __sinf(ang);
}

#define KS 2048
DEV void put8(uint32_t a, const float (&r)[8], const float (&i)[8]) {
  sts4(a, pack2(r[0], r[1]), pack2(r[2], r[3]), pack2(r[4], r[5]), pack2(r[6], r[7]));
  sts4(a + 1024, pack2(i[0], i[1]), pack2(i[2], i[3]), pack2(i[4], i[5]), pack2(i[6], i[7]));
}
DEV void tables(const uint32_t (&pv)[8], int k4, int w, int lane) {
  PW(4 * k4 + w)
  [[maybe_unused]] const int layer = 0;
  const float dt = bfr(__expf(bflo(pv[6])));
  const float al = dt * bflo(pv[0]) * 1.4426950408889634f, bt = dt * bflo(pv[1]) * 0.15915494309189535f;
  float qr[8], qi[8], yr[8], yi[8];
  cmul(qr[0], qi[0], bflo(pv[4]), bflo(pv[5]), dt * bflo(pv[2]), dt * bflo(pv[3]));
  PROFD(2, a_par, __float_as_uint(qr[0] + al + bt));
  float e1r, e1i, eMr, eMi, eLr, eLi;
  cexp_(al, bt, 1.f, e1r, e1i); cexp_(al, -bt, 8.f, yr[1], yi[1]); cexp_(al, -bt, 64.f, eMr, eMi); cexp_(al, bt, 256.f, eLr, eLi);
  const uint32_t ad = SB + k4 * 32768 + (w & 1) * 512 + lane * 16, am = ad + (w >> 1) * KS, an = ad + (8 + 3 * (w >> 1)) * KS;
  yr[0] = 1.f; yi[0] = 0.f;
#pragma unroll
  for (int k = 1; k < 8; ++k) {
    cmul(qr[k], qi[k], qr[k - 1], qi[k - 1], e1r, e1i);
    if (k > 1) cmul(yr[k], yi[k], yr[k - 1], yi[k - 1], yr[1], yi[1]);
  }
  put8(an, qr, qi);
#pragma unroll
  for (int j = 0; j < 4; ++j) {
    put8(am + j * 2 * KS, yr, yi);
#pragma unroll
    for (int k = 0; k < 8; ++k) {
      if (j == 0 && k == 0) { yr[0] = eMr; yi[0] = eMi; } else if (j < 3) cmul(yr[k], yi[k], yr[k], yi[k], eMr, eMi);
    }
    if (j == 0) {
#pragma unroll
      for (int k = 0; k < 8; ++k) { const int o = k < 4 ? 2 * k : k < 6 ? 2 * k - 8 : k - 2; cmul(qr[k], qi[k], qr[o], qi[o], eLr, eLi); }
      put8(an + KS, qr, qi);
    } else if (j == 1) {
#pragma unroll
      for (int k = 0; k < 5; ++k) cmul(qr[k], qi[k], qr[k ? k - 1 : 6], qi[k ? k - 1 : 6], eLr, eLi);
      put8(an + 2 * KS, qr, qi);
    }
  }
  PROF(3, a_tab);
}

DEV void sts16_if(uint32_t a, uint32_t v, bool c) { asm volatile("{.reg .pred q; .reg .b16 h; setp.ne.u32 q,%2,0; cvt.u16.u32 h,%1; @q st.shared.u16 [%0],h;}" :: "r"(a), "r"(v), "r"((uint32_t)c) : "memory"); }
DEV void sts1_if(uint32_t a, uint32_t v, bool c) { asm volatile("{.reg .pred q; setp.ne.u32 q,%2,0; @q st.shared.u32 [%0],%1;}" :: "r"(a), "r"(v), "r"((uint32_t)c) : "memory"); }
DEV void taps(uint32_t dskip, int k4, int w, int lane) {
  PW(4 * k4 + w)
  [[maybe_unused]] const int layer = 0;
  fence_async_smem();
  bar_sync((k4 & 1) ? NB_WG + k4 : NB_Q, (k4 & 1) ? 128 : 448);
  float d[24];
  undef(d);
  const uint64_t da = mkdesc(SB + k4 * 32768, 1024, KS, 0);
  wg_fence();
#pragma unroll
  for (int j = 0; j < 8; ++j) wg_ss48(d, da + j * 8, da + KS / 2 + j * 8, j);
  wg_commit();
  const int b = 8 * w + (lane >> 2), t = lane & 3, id = 32 * w + lane;
  constexpr int DO = T_O - T_E;
  const uint32_t te = SM_TAP + k4 * TAP_SZ + T_E, a0 = te - 16 * b - 4 * t;
  const uint32_t a1 = a0 - 512 - 4 * t, a2 = te - 2 * (511 + b) - 64 * t, a3 = te + (T_C - T_E) - 2 * (127 + b) - 128 * t;
  wg_wait<0>();
  PROF(4, a_mma);
  {
    const uint32_t v = pack2(d[1] + d[15], d[0] + d[14] + (id ? 0.f : bflo(dskip)));
    sts1(a0 + DO - 2, v); sts16(a0 - 2, v); sts16(a0, v >> 16);
  }
  {
    const uint32_t v = pack2(d[5] + d[19], d[4] + d[18]), u = prmt(v, v, 0x3232);
    const bool lo = t < 2, k512 = id == 2;
    sts1_if(k512 ? te - 2 * 512 : a1, u, (lo && id) || k512);
    sts1_if(k512 ? te - 2 * 514 : a1 - 4, k512 ? u : v, lo || k512);
    sts1_if(k512 ? te + DO - 2 * 513 : a1 + DO - 2, u, lo || k512);
    sts16(lo ? a1 + DO - 4 : a2 + DO - 194, v);
    sts16(lo ? (id ? a1 + DO + 2 : a1) : k512 ? te + DO - 2 * 511 : a2 + DO, u);
    sts16_if(a2 - 194, v, !lo);
    sts16_if(k512 ? te + DO - 2 * 514 : a2, u, !lo);
  }
  {
    const uint32_t v = pack2(d[8] + d[22], d[9] + d[23]);
    sts16_if(id ? a3 : te - 2 * 639, v, t < 2 || id == 2);
    sts16_if(a3 - 64, v >> 16, t < 2);
    sts16_if(te + DO - 2 * 639, v, id == 0);
  }
  bar_sync(NB_WG + k4, 128);
  mbar_arrive1_if(B_K, w == 0);
}

DEV uint32_t cpy(uint32_t v, uint32_t id) {
  uint32_t d; asm volatile("prmt.b32 %0,%1,%1,%2;" : "=r"(d) : "r"(v), "r"(id)); return d;
}
DEV uint32_t uoff(int s) { return (s ^ ((s >> 3) & 3)) * 16; }
template <bool FULL> DEV void boxes(const uint32_t (&u)[10], uint32_t a, uint32_t a9, uint32_t a7, uint32_t (&pv)[4]) {
  uint32_t v[8], p[8], x[4], y[4];
#pragma unroll
  for (int j = 0; j < 8; ++j) { v[j] = prmt(u[j], u[j + 1], 0x5432); p[j] = hadd2(u[j], v[j]); }
#pragma unroll
  for (int j = 0; j < 4; ++j) { x[j] = hadd2(hadd2(p[j + 1], p[j + 2]), u[j + 3]); y[j] = hadd2(v[j + 3], p[j + 4]); }
  sts4(a + R_A5, x[0], x[1], x[2], x[3]);
  sts4(a + R_A3, y[0], y[1], y[2], y[3]);
  if (FULL) {
#pragma unroll
    for (int j = 0; j < 4; ++j) { x[j] = hadd2(x[j], hadd2(v[j], v[j + 3])); y[j] = hadd2(x[j], hadd2(u[j], u[j + 4])); pv[j] = p[j + 4]; }
    sts4(a7, x[0], x[1], x[2], x[3]);
    sts4(a9, y[0], y[1], y[2], y[3]);
  }
}
DEV uint32_t shfl_up(uint32_t v, int d) { uint32_t r; asm volatile("shfl.sync.up.b32 %0,%1,%2,0,0xffffffff;" : "=r"(r) : "r"(v), "r"(d) : "memory"); return r; }
DEV void halo(uint32_t (&u)[10], uint32_t a, uint32_t b, int lane) {
  asm volatile("{.reg .pred p,q; setp.eq.s32 p,%8,0; setp.lt.s32 q,%8,2;\n@p ld.shared.v4.u32 {%2,%3,%4,%5},[%6];\n@q ld.shared.v2.u32 {%0,%1},[%7];}"
    : "+r"(u[0]), "+r"(u[1]), "+r"(u[2]), "+r"(u[3]), "+r"(u[4]), "+r"(u[5]) : "r"(a), "r"(b), "r"(lane));
}
#define W1 4
#define ROT 2
#define G1 -1
#define G2 1
#define G3 8
#define TPS 0x7134
#define GMASK ((G1 >= 0 ? 2 : 0) | (G2 >= 0 ? 4 : 0) | (G3 >= 0 ? 8 : 0))
#define GATE1(g, n, p) if (g >= 0 && (g & 3) == p) mbar_arrive1_if(B_G + 8 * n, k4 == (g >> 2));
#define GATE(p) GATE1(G1, 0, p) GATE1(G2, 1, p) GATE1(G3, 2, p)
#define TMASK(p) (((TPS & 15) == p) | ((((TPS >> 4) & 15) == p) << 1) | ((((TPS >> 8) & 15) == p) << 2) | ((((TPS >> 12) & 15) == p) << 3))
#define TURN(p) if (TMASK(p) == 15) bar_arrive(NB_T + 1 + k4, 256); else if (TMASK(p)) { if ((TMASK(p) >> k4) & 1) bar_arrive(NB_T + 1 + k4, 256); }
DEV void w_load(const CUtensorMap* mW, int cg, int h) {
  mbar_expect1(B_W + 8 * h, 24576);
  tma3(SM_S0 + (h & 3) * 24576, mW, 64 * cg, 64 * h, B_W + 8 * h);
}

DEV void conv(const Params& P, const CUtensorMap* mW, int c, int k4, int w, int layer) {
  const uint32_t zero = P.zero;
  PW(4 * k4 + w)
  int lane = lane_here(zero);
  const int g = lane >> 2, t = lane & 3, v = w ^ (ROT * (k4 & 1)), tid = 32 * v + lane;
  const uint32_t reg = SM_R + k4 * 16384, tp = SM_TAP + k4 * TAP_SZ;
  const uint32_t g0 = tp + ((g & 1) ? T_O : T_E) + 2 * (2 * t - g);
  uint32_t F[18][4], U[20], qc[4][4];
#define LO(q, a) q[0] = lds1(a); q[2] = lds1(a + 16);
#define HI(q, a) q[1] = lds1(a - 128); q[3] = lds1(a - 112);
  {
    const uint32_t ga = g0 - 32 * (w & 1) - 576 * (w >> 1), g2 = tp + T_C - 258 - 32 * w + 4 * (t - g);
    F[0][2] = lds1(ga + 48);
#pragma unroll
    for (int j = 0; j < 8; ++j) { F[j][0] = lds1(ga + 32 - 32 * j); F[j][1] = lds1(ga + 16 - 32 * j); }
#pragma unroll
    for (int j = 0; j < 20; ++j) U[j] = lds1(ga - 224 - 16 * j);
#pragma unroll
    for (int j = 0; j < 4; ++j) { LO(qc[j], g2 + 32 * j) HI(qc[j], g2 + 32 * j) }
  }
  if (layer) { mbar_wait(B_ED, 0); mbar_wait(B_ED + 8, 0); }
  sts4z_if(reg + lane * 16 + (w ? w * 3584 + 1024 : 0), w < 3);
  PROF(5, a_pre);
  if (k4 == 3 && w == 3) {
    mbar_wait(B_E, layer);
    mbar_wait(B_K, 0);
#pragma unroll
    for (int h = 0; h < 4; ++h) w_load(mW, c & 7, h);
  }
  const uint32_t bo = reg + R_B + tid * 16 + (v >> 1) * 1056, be = tid == 127 ? reg + R_B + 1024 : bo + (tid == 63 ? 2112 : 1056);
  const uint32_t a9 = (lane & 1) ? be : bo, a7 = (lane & 1) ? bo : be, ua = reg + R_U + uoff(tid);
  const uint32_t h1 = reg + R_U + v * 512 - 64, h2 = h1 + 24 - 16 * lane;
  keep(a9 & a7 & ua & h2, zero);
  mbar_wait(k4 && ((GMASK >> k4) & 1) ? B_G - 8 + 8 * k4 : B_E, layer);
  PROF(6, a_x);
  uint4 x[2];
  uint32_t pv[4];
  {
    uint4 s[4];
    uint32_t u[2][10];
#pragma unroll
    for (int z = 0; z < 2; ++z) { x[z] = lds4(reg + R_B + tid * 16 + z * 2048); s[2 * z] = lds4(SM_RES + tid * 16 + z * 2048); s[2 * z + 1] = lds4(SM_RES + tid * 16 + z * 2048 + 4096); }
    for (int it = 0;; ++it) {
      const uint32_t m = min(min(min((both(x[0].x, x[1].x, layer) | lane) & 1, min(s[0].x, s[0].z)), min(s[1].x, s[1].z)), min(min(s[2].x, s[2].z), min(s[3].x, s[3].z)));
      if (__builtin_expect(__all_sync(0xffffffffu, m != 0u), 1)) break;
      EVENT(16 + layer * 4 + k4);
      const int o = tid | here(zero);
#pragma unroll
      for (int z = 0; z < 2; ++z) x[z] = ldr4(&P.S->XG[(128 * k4 + c) * 256 + o] + z * 128);
#pragma unroll
      for (int z = 0; z < 4; ++z) {
        s[z] = ldr4(&P.S->SR[layer][c >> 4][o] + ((z >> 1) * 128 + (z & 1) * 256));
        sts4(SM_RES + tid * 16 + (z >> 1) * 2048 + (z & 1) * 4096, s[z].x, s[z].y, s[z].z, s[z].w);
      }
      spin_guard(it);
    }
#pragma unroll
    for (int z = 0; z < 2; ++z) {
      u[z][6] = hmul2(hsub2(x[z].x, s[2 * z].y), s[2 * z].x); u[z][7] = hmul2(hsub2(x[z].y, s[2 * z].w), s[2 * z].z);
      u[z][8] = hmul2(hsub2(x[z].z, s[2 * z + 1].y), s[2 * z + 1].x); u[z][9] = hmul2(hsub2(x[z].w, s[2 * z + 1].w), s[2 * z + 1].z);
      sts4(ua + z * 2048, u[z][6], u[z][7], u[z][8], u[z][9]);
    }
    u[1][0] = 0; u[1][1] = s[3].x; u[1][2] = s[2].x; u[1][3] = s[2].y; u[1][4] = s[2].z; u[1][5] = s[2].w;
    if (v < 2) {
#pragma unroll
      for (int j = 1; j < 6; ++j) u[1][j] = shfl_up(u[1][j < 2 ? 8 + j : 4 + j], j < 2 ? 2 : 1);
    }
#pragma unroll
    for (int j = 0; j < 6; ++j) u[0][j] = shfl_up(u[0][j < 2 ? 8 + j : 4 + j], j < 2 ? 2 : 1);
    bar_sync(NB_WG + k4, 128);
    GATE(0)
    PROF(7, a_u);
    halo(u[0], h1, h2, lane);
    halo(u[1], h1 + 2048, h2 + 2048, lane + 16 * (v & 2));
    sts4z_if(reg + R_B + 1040, tid == 0);
    boxes<true>(u[0], reg + tid * 16, a9, a7, pv);
    if (v < 2) boxes<false>(u[1], reg + tid * 16 + 2048, 0, 0, pv);
  }
  GATE(1)
  fence_async_smem();
  if (k4 == 3 && w == 0) {
    const uint32_t src = SM_RES + 8192;
#pragma unroll
    for (int z = 0; z < 4; ++z) sts4(src + lane * 16 + z * 512, 0, 0, 0, 0);
    fence_async_smem();
    __syncwarp();
#pragma unroll
    for (int z = 0; z < 2; ++z) {
      bulk_store(&P.S->H[(c + 8) * 256] + z * 128, src, 2048);
      bulk_store(P.S->F + ((c >> 3) * 64 + 4 * (c & 7)) + z * 32, src, 16);
    }
    bulk_store(&P.S->PS[c * 64], src, 1024);
    bulk_store(&P.S->ST[c * 4], src, 64);
    if (c < 8 && layer) bulk_store(&P.S->CS[c * 48], src, 768);
    if (c < 5) bulk_store(P.S->C + (c + 5 - 5 * layer) * 1024, src, 128 * NCOPY * NSUB);
    asm volatile("cp.async.bulk.commit_group;" ::: "memory");
  }
  const uint32_t id = opq(0x3210u);
#pragma unroll
  for (int j = 0; j < 8; ++j) { F[j][3] = cpy(F[j][0], id); if (j) F[j][2] = cpy(F[j - 1][1], id); }
  PROF(8, a_box);
  bar_sync(NB_T + k4, k4 ? 256 : 128);
  PROF(9, a_turn);
  float acc[32], f1[24], f3[16];
  uint32_t qa[4][4], qb[4][4], fp[4];
  const uint64_t db = mkdesc(reg + R_U, 16, 512, 2) + 2;
#define STEP(mm, n) wg_fence(); mm; wg_commit(); wg_wait<n>();
#define D(j, n) STEP(wg_rs64k(acc, F[j], db - 2 * j, j), n)
#define C(j, n) STEP(wg_rs32t(f3, qc[j], mkdesc(reg + R_B, 128, 1040, 0) + 16 * j, j), n)
#define NIL(q, y) { const uint32_t z = y & zero; q[2][1] = cpy(z, 0); q[2][3] = cpy(z, 1); q[3][1] = cpy(z, 2); q[3][3] = cpy(z, 3); }
#define X(j) F[j][0] = cpy(U[2 * j - 16], ix); F[j][1] = cpy(U[2 * j - 15], ix); F[j][3] = cpy(F[j][0], ix); F[j][2] = cpy(F[j - 1][1], ix);
  const uint32_t g1 = g0 - 2 * 576 - 16 * w;
  const uint64_t d1 = mkdesc(reg + R_A5, 128, 512, 0);
  constexpr int O3 = (R_A3 - R_A5) / 16;
  uint32_t ix = id;
  undef(acc);
  D(0, 4) TURN(0) D(1, 4) D(2, 4) D(3, 4) D(4, 4) D(5, 2)
  undef(f3);
  C(0, 3) C(1, 3) TURN(1) C(2, 3) X(8) C(3, W1) X(9) LO(qa[0], g1)
  D(6, W1) HI(qa[0], g1) X(10) D(7, W1) LO(qa[1], g1 + 32) X(11) D(8, W1) HI(qa[1], g1 + 32) D(9, 4) LO(qa[2], g1 - 64)
  fp[0] = pack2(f3[0], f3[1]); fp[1] = pack2(f3[4], f3[5]); fp[2] = pack2(f3[8] + f3[2], f3[9] + f3[3]); fp[3] = pack2(f3[12] + f3[6], f3[13] + f3[7]);
  ix |= fp[0] & fp[1] & fp[2] & fp[3] & zero;
  X(12) D(10, 4) TURN(2) LO(qa[3], g1 - 32) X(13) X(14) D(11, 4) LO(qb[0], g1 - 192) X(15) D(12, 4) HI(qb[0], g1 - 192) X(16)
  D(13, 4) LO(qb[1], g1 - 160) X(17) D(14, 4) TURN(3) HI(qb[1], g1 - 160) NIL(qa, qa[1][0])
  D(15, 4) LO(qb[2], g1 - 256) D(16, 3) LO(qb[3], g1 - 224) NIL(qb, qa[1][1]) D(17, 2) TURN(4)
  PROF(10, a_den);
  undef(f1);
  wg_fence();
#pragma unroll
  for (int j = 0; j < 4; ++j) wg_rs48t(f1, qa[j], d1 + 16 * (j & 1) - 32 * (j >> 1), j);
  wg_commit();
  wg_wait<1>();
  TURN(5)
  wg_fence();
#pragma unroll
  for (int j = 0; j < 4; ++j) wg_rs48t(f1, qb[j], d1 + O3 + 16 * (j & 1) - 32 * (j >> 1), 1);
  wg_commit();
  TURN(6)
  lane = lane_here(zero);
  bar_sync(NB_WG + k4, 128);
  {
    const int p = (lane + 9 * (w >> 1)) & 31;
    const uint32_t ya = reg + ((w >> 1) ? R_B : R_U) + p * 64 + (((2 * (w & 1)) ^ ((p >> 1) & 3)) * 16), up = p < lane ? 2048 : 0;
#pragma unroll
    for (int z = 0; z < 4; ++z) {
      const float* a = acc + 16 * (z >> 1) + 2 * (z & 1);
      stsm4t((ya + (up ^ ((z >> 1) * 2048))) ^ ((z & 1) * 16), pack2(a[0], a[1]), pack2(a[4], a[5]), pack2(a[8], a[9]), pack2(a[12], a[13]));
    }
  }
  asm volatile("cp.async.bulk.wait_group 0;" ::: "memory");
  const uint32_t fa = reg + R_A5 + (lane >> 3) * 512 + w * 128 + (lane & 7) * 16;
  const uint32_t fc = reg + R_A3 + uoff(64 * (lane >> 4) + 16 * w + 2 * (lane & 7) + 1 - ((lane >> 3) & 1));
  uint32_t k1024 = lds16(tp + T_E - 2 * 639 + (fa & fc & zero));
  wg_wait<0>();
  GATE(2)
  PROF(11, a_far);
  bar_sync(NB_WG + k4, 128);
  stsm4(fc, fp[0], fp[1], fp[2], fp[3]);
  stsm4(fa, pack2(f1[0], f1[1]), pack2(f1[4], f1[5]), pack2(f1[8] + f1[2], f1[9] + f1[3]), pack2(f1[12] + f1[6], f1[13] + f1[7]));
  stsm2(fa + 2048, pack2(f1[16] + f1[10], f1[17] + f1[11]), pack2(f1[20] + f1[14], f1[21] + f1[15]));
  {
    const int o = 32 * v + lane;
    const uint32_t a = reg + uoff(o), b = reg + R_A5 + o * 16;
    uint4 y[2] = {hadd8(lds4(a + R_U), lds4(o >= 36 ? a + R_B : reg)), hadd8(lds4(a + R_U + 2048), lds4(a + R_B + 2048))};
    bar_sync(NB_WG + k4, 128);
    TURN(7)
    PROF(12, a_sts);
    const uint4 f = lds4(v >= 2 ? b - 1024 : reg), f2 = lds4(b + 1024);
    uint4 h = lds4(a + R_A3);
    const int e0 = (o >> 3) * 8192 + (128 * k4 + c) * 16 + (((o & 4) + ((o >> 1) & 1)) ^ (c & 7)) * 2 + (o & 1);
    const uint32_t me = (e0 & 3) == ((c >> 1) & 3), m0 = me & ~c, m1 = me & c, tag = 1 - layer;
    uint32_t* cp = cnt_at(P, 1 + 5 * layer + k4, c, lane);
    keep(cp, zero);
    k1024 = prmt(k1024, k1024, 0x1010);
    h = make_uint4(hfma2(pv[0], k1024, h.x), hfma2(pv[1], k1024, h.y), hfma2(pv[2], k1024, h.z), hfma2(pv[3], k1024, h.w));
    y[0] = hadd8(y[0], f); y[1] = hadd8(y[1], hadd8(f2, h));
    cnt_add(cp, 1 | (y[0].x & y[1].x & zero), (o ^ 96) < NCOPY);
#pragma unroll
    for (int z = 0; z < 2; ++z) {
      const uint4 r = hadd8(x[z], y[z]);
      str2((uint2*)P.S->XF + e0 + z * 131072, tagged(prmt(r.x, r.y, 0x5410), m0, tag), tagged(prmt(r.z, r.w, 0x5410), m1, tag));
      str2((uint2*)P.S->XF + (e0 ^ 4) + z * 131072, tagged(prmt(r.x, r.y, 0x7632), m0, tag), tagged(prmt(r.z, r.w, 0x7632), m1, tag));
    }
  }
  TURN(9)
  GATE(3)
  PROF(13, a_out);
}

#define FH 1
#define QPIN 1
#define XORD 1
DEV void x_load(const Params& P, int c, int q, int layer) {
#pragma unroll
  for (int z = 0; z < 2; ++z) {
    const int e = z ^ (XORD && q == 3 && !(c & 4));
    mbar_expect1(B_X + 16 * q + 8 * e, 16384);
    bulk(xstage(q, e), P.S->XF + ((2 * (c >> 3) + 1 - e) * 4096 + q * 1024), 16384, B_X + 16 * q + 8 * e);
  }
}

DEV void means(uint32_t (&m)[4], int row, int lane, int layer, uint32_t zero) {
  mbar_wait(B_CS, 0);
  mbar_wait(B_ST, layer);
  const uint32_t a = SM_MISC + row * 4 + (lane & 28), k = (lane & 3) ? 0u : ~0u;
  m[0] = lds1(a) & k; m[1] = lds1(a + 32) & k; m[2] = m[0] & zero; m[3] = m[1] & zero;
}

DEV void attn_phase(const Params& P, int c, int e, int w, int lane, int layer) {
  PW(4 * e + w)
  const int cg = c & 7, J = 2 * (c >> 3) + 1 - e;
  float acc[96];
  zerov(acc);
  uint32_t m[4] = {0, 0, 0, 0};
#pragma unroll 1
  for (int q = 0;; ++q) {
    const uint64_t da = mkdesc(xstage(q, e), 16, 1024, 1), db = mkdesc(SM_S0 + (q & 1) * 49152, 8192, 1024, 1);
    const uint32_t wr = mbar_test2(B_W + 16 * q, layer), xa = xstage(q, e) + w * 4096 + lane * 132;
    mbar_wait(B_X + 16 * q + 8 * e, layer);
    for (int it = 0;; ++it) {
      const uint32_t ok = both(lds1(xa), lds1(xa ^ 32), layer) & both(lds1(xa ^ 64), lds1(xa ^ 96), layer);
      if (__all_sync(0xffffffffu, ok & 1)) break;
      EVENT(8 * layer + 2 * q + e);
#pragma unroll 1
      for (int j = 0; j < 8; ++j) cp16(xstage(q, e) + w * 4096 + j * 512 + lane * 16, P.S->XF + (J * 4096 + q * 1024 + w * 256 + j * 32 + lane));
      asm volatile("cp.async.wait_all;" ::: "memory");
      fence_async_smem();
      __syncwarp();
      spin_guard(it);
    }
    bool all = __all_sync(0xffffffffu, wr);
    if (q == 0 && e && w == 0) {
      bar_sync(NB_H, 256);
      cnt_wait(P, 2 + 5 * layer, c, lane);
      x_load(P, c, 1, layer);
      PROF(27, m_xi);
    }
    if (q == 3 && e) means(m, 16 * w, lane, layer, P.zero);
    if (!all) { mbar_wait(B_W + 16 * q, layer); all = mbar_test(B_W + 16 * q + 8, layer); }
    bar_sync(e ? NB_Q : q ? NB_T : NB_T + 4, 256);
    PROF(14 + q, m_q);
    wg_fence();
#pragma unroll
    for (int k = 0; k < 8; ++k) {
      if (k == 4) { wg_commit(); if (!all) mbar_wait(B_W + 16 * q + 8, layer); wg_fence(); }
      wg_ss192(acc, da + k * 128, db + (k >> 2) * 1536 + (k & 3) * 128, 1);
    }
    wg_commit();
    if (q == 3) break;
    bar_arrive(e ? NB_T : NB_Q, 256);
    if (FH) { wg_wait<1>(); mbar_arrive1_if(B_FH + 8 * q, e && q < 2); }
    wg_wait<0>();
    mbar_arrive1(B_F + 8 * q);
  }
  const int pos = 2 - 2 * e + (w >> 1);
  uint4* h = P.S->H + ((c + 8) * 256 + (w & 1) * 128 + lane);
  const uint32_t kw = kvslot(pos + 1) + (w & 1) * 2048 + lane * 16;
  {
    if (!e) means(m, 64 + 16 * w, lane, layer, P.zero);
    PROF(28, m_sub);
    wg_fence();
    wg_rs192t(acc, m, mkdesc(SM_CS, 0, 32, 0));
    wg_commit();
    bar_arrive_if(NB_Q, 256, !e);
    keep(h, kw & P.zero);
    mbar_wait(B_F + 16, layer);
    wg_wait<0>();
    mbar_arrive1(B_F + 24);
  }
  PROF(18, m_qkv);
  uint32_t Q[4][4], K[4][3][2], V[4][3][2];
  uint32_t pin = P.zero;
#pragma unroll
  for (int z = 0; z < 4; ++z) {
    V[z][1][0] = pack2(acc[64 + 8 * z], acc[65 + 8 * z]); V[z][1][1] = pack2(acc[68 + 8 * z], acc[69 + 8 * z]);
    K[z][1][0] = pack2(acc[32 + 8 * z], acc[33 + 8 * z]); K[z][1][1] = pack2(acc[36 + 8 * z], acc[37 + 8 * z]);
    pin &= V[z][1][0] & V[z][1][1];
    K[z][2][0] = nz(pack2(acc[34 + 8 * z], acc[35 + 8 * z])); K[z][2][1] = pack2(acc[38 + 8 * z], acc[39 + 8 * z]);
    V[z][2][0] = pack2(acc[66 + 8 * z], acc[67 + 8 * z]); V[z][2][1] = pack2(acc[70 + 8 * z], acc[71 + 8 * z]);
    str4_if(h + z * 32, K[z][2][0], K[z][2][1], V[z][2][0], V[z][2][1], pos == 3);
  }
#pragma unroll
  for (int z = 0; z < 8; ++z) V[z >> 1][2][z & 1] = movm(z < 7 ? V[z >> 1][2][z & 1] : V[3][2][1] | pin);
  if (pos == 0) mbar_wait(B_F + 24, layer);
#pragma unroll
  for (int z = 0; z < 4; ++z) sts4_if(kw + z * 512, K[z][2][0], K[z][2][1], V[z][2][0], V[z][2][1], pos < 3);
  bar_arrive(NB_H + pos + 1, 128);
  PROF(19, m_kv);
  lane |= here(P.zero);
  int g = lane >> 2, t = lane & 3;
  const uint32_t ra = SM_STAT + 256 + (32 - 32 * e + 8 * w) * 16, ob = e ? SM_S1 : SM_XA;
  const float r0 = lds1f(ra + (g >> 1) * 16 + (g & 1) * 4), r1 = lds1f(ra + 64 + (g >> 1) * 16 + (g & 1) * 4);
  const uint4 k1 = lds4(ra + 16 * t), k2 = lds4(ra + 64 + 16 * t);
#pragma unroll
  for (int z = 0; z < 8; ++z) {
    V[z >> 1][1][z & 1] = movm(V[z >> 1][1][z & 1]);
    Q[z >> 1][2 * (z & 1)] = pack2(acc[4 * z], acc[4 * z + 1]);
    Q[z >> 1][2 * (z & 1) + 1] = pack2(acc[4 * z + 2], acc[4 * z + 3]);
    pin &= Q[z >> 1][2 * (z & 1)] & Q[z >> 1][2 * (z & 1) + 1];
  }
  {
    const bool p0 = 2 * t > g, p1 = 2 * t + 1 > g, first = c < 8 && pos == 0;
    const uint32_t M = (p0 ? 0xFFFFu : 0u) | (p1 ? 0xFFFF0000u : 0u);
    const float sc0 = r0 * (0.25f * 1.4426950408889634f), sc1 = r1 * (0.25f * 1.4426950408889634f);
    const float sk2 = __uint_as_float(p0 ? k1.x : k2.x) * sc1, sk3 = __uint_as_float(p1 ? k1.y : k2.y) * sc1;
    const int oo = (2 * (w & 2) + (w & 1)) * 64 + (lane ^ (g >> 1));
    uint4* O = P.S->O + (J * 4096 + cg * 512 + oo);
    keep(oo, pin & M & __float_as_uint(sk2) & __float_as_uint(sk3) & __float_as_uint(sc0));
    mbar_wait(B_F + 24, layer);
    float L[4][4];
#pragma unroll
    for (int z = 0; z < 4; ++z) {
      float S[4];
      mma16z(L[z], Q[z][0], Q[z][1], Q[z][2], Q[z][3], K[z][1][0], K[z][1][1]);
      mma16z(S, Q[z][0], Q[z][1], Q[z][2], Q[z][3], K[z][2][0], K[z][2][1]);
      L[z][2] = (p0 ? L[z][2] : S[2]) * sk2; L[z][3] = (p1 ? L[z][3] : S[3]) * sk3;
      if (QPIN) pin &= __float_as_uint(L[z][2]) & __float_as_uint(L[z][3]);
    }
    bar_sync(NB_H + pos + pin, pos ? 128 : 160);
    const uint4 k0 = lds4(ra - 192 + 16 * t);
#pragma unroll
    for (int z = 0; z < 4; ++z) {
      const uint4 hv = lds4(kvslot(pos) + (w & 1) * 2048 + lane * 16 + z * 512);
      K[z][0][0] = hv.x; K[z][0][1] = hv.y; V[z][0][0] = hv.z; V[z][0][1] = hv.w;
    }
    PROF(20, m_halo);
    const float sk0 = __uint_as_float(p0 ? k0.x : k1.x) * sc0, sk1 = __uint_as_float(p1 ? k0.y : k1.y) * sc0;
    const uint32_t rm[4] = {k0.z & M, k1.z & ~M, k1.z & M, k2.z & ~M}, s0 = k0.w | P.zero, s1 = k1.w | P.zero;
    uint4 ov[4];
#pragma unroll
    for (int h2 = 0; h2 < 2; ++h2) {
      uint32_t A[2], B[2], mx[2];
#pragma unroll
      for (int z = 0; z < 2; ++z) {
        const int h = 2 * h2 + z;
        float S[4];
        mma16z(S, Q[h][0], Q[h][1], Q[h][2], Q[h][3], K[h][0][0], K[h][0][1]);
        if (first) { S[0] = __uint_as_float(0xFF800000u); S[1] = S[0]; }
        A[z] = pack2((p0 ? S[0] : L[h][0]) * sk0, L[h][2]);
        B[z] = pack2((p1 ? S[1] : L[h][1]) * sk1, L[h][3]);
      }
#pragma unroll
      for (int z = 0; z < 2; ++z) mx[z] = hmax2(A[z], B[z]);
#pragma unroll
      for (int z = 0; z < 2; ++z) mx[z] = hmax2(mx[z], __shfl_xor_sync(0xffffffffu, mx[z], 1));
#pragma unroll
      for (int z = 0; z < 2; ++z) mx[z] = hmax2(mx[z], __shfl_xor_sync(0xffffffffu, mx[z], 2));
      float Oa[2][3][4];
#pragma unroll
      for (int z = 0; z < 2; ++z) {
        const int h = 2 * h2 + z;
        const uint32_t a = hsub2(A[z], mx[z]), b = hsub2(B[z], mx[z]);
        const uint32_t w0 = pack2(ex2(bflo(a)), ex2(bflo(b))), w1 = pack2(ex2(bfhi(a)), ex2(bfhi(b)));
        const uint32_t u0 = hmul2(w0, rm[0]), u1 = hmul2(w0, rm[1]), u2 = hmul2(w1, rm[2]), u3 = hmul2(w1, rm[3]);
        const uint32_t z0 = w0 & P.zero, z1 = w1 & P.zero;
        mma16z(Oa[z][2], u0, z0, u1, u2, s0, s1);
#pragma unroll
        for (int d = 0; d < 2; ++d) mma16z(Oa[z][d], u0, z0, u1, u2, V[h][0][d], V[h][1][d]);
        mma8(Oa[z][2], z1, u3, k2.w);
#pragma unroll
        for (int d = 0; d < 2; ++d) mma8(Oa[z][d], z1, u3, V[h][2][d]);
      }
#pragma unroll
      for (int r = 0; r < 4; r += 2) {
        const float i0 = rcp(Oa[0][2][r]), i1 = rcp(Oa[1][2][r]);
        const uint32_t o0 = pack2(Oa[0][0][r] * i0, Oa[0][0][r + 1] * i0), o1 = pack2(Oa[0][1][r] * i0, Oa[0][1][r + 1] * i0);
        const uint32_t o2 = pack2(Oa[1][0][r] * i1, Oa[1][0][r + 1] * i1), o3 = pack2(Oa[1][1][r] * i1, Oa[1][1][r + 1] * i1);
        str4(O + h2 * 32 + r * 64, o0, o1, o2, o3);
        ov[h2 + r] = make_uint4(o0, o1, o2, o3);
      }
    }
    bar_arrive(NB_T + 1 + e, 160);
#pragma unroll
    for (int z = 0; z < 4; ++z) sts4(ob + oo * 16 + (z & 1) * 512 + (z & 2) * 1024, ov[z].x, ov[z].y, ov[z].z, ov[z].w);
  }
  fence_async_smem();
  PROF(21, m_att);
  lane = lane_here(P.zero); g = lane >> 2; t = lane & 3;
  uint32_t res[8][2];
  mbar_wait(B_RES, layer);
  mbar_wait(B_WO, layer);
  {
    const uint32_t a = SM_RES + e * 8192 + (lane >> 4) * 1024 + (lane & 7) * 128 + (((2 * (w & 2) + ((lane >> 2) & 2) + (w & 1)) ^ (lane & 7)) * 16);
#pragma unroll
    for (int j = 0; j < 8; j += 2) ldsm4t(res[j][0], res[j][1], res[j + 1][0], res[j + 1][1], a + j * 1024);
  }
  PROF(26, m_res);
  XgAddr xa = xg_addr<true>(P.S->XG + (64 * cg * 256 + 8 * J), ob, w, lane, P.zero);
  uint4* ps = &P.S->PS[((4 * J + w) * 8 + cg) * 8 + g];
  keep(ps, P.zero);
  if (layer) {
    xa.a = ob + w * 2048 + (lane & 15) * 128 + (((lane >> 4) ^ (lane & 7)) * 16);
    xa.b = ob + w * 2048 + (lane >> 3) * 128 + (((lane & 7) ^ (lane >> 3)) * 16);
    xa.dst = (uint4*)P.out + ((64 * J + 16 * w + 2 * (lane >> 3)) * 64 + 8 * cg + (lane & 7));
  }
  uint32_t y[8][2];
#pragma unroll 1
  for (int it = 0;; ++it) {
    float ac[32];
#pragma unroll
    for (int j = 0; j < 16; ++j) {
      asm volatile("shl.b32 %0,%1,16;" : "=f"(ac[2 * j]) : "r"(res[j >> 1][j & 1]));
      asm volatile("and.b32 %0,%1,0xFFFF0000;" : "=f"(ac[2 * j + 1]) : "r"(res[j >> 1][j & 1]));
    }
    const uint64_t da = mkdesc(ob, 16, 1024, 2), db = mkdesc(SM_R, 16, 1024, 1);
    wg_fence();
    bar_sync_if(NB_T, 256, it == 0);
#pragma unroll 1
    for (int n = 0; n < 8; ++n) {
      mbar_wait(B_O + 64 * e + 8 * n, layer);
      if (n == 1) PROF(22, m_o1);
      if (n == 7) PROF(23, m_o7);
      wg_fence();
#pragma unroll
      for (int k = 0; k < 4; ++k) wg_ss64(ac, da + n * 512 + (k >> 1) * 32 + (k & 1) * 2, db + n * 512 + k * 128, 1);
      wg_commit();
    }
    wg_wait<0>();
    const bool bad = ac[0] != ac[0] || ac[2] != ac[2];
#pragma unroll
    for (int j = 0; j < 8; ++j) {
      y[j][0] = pack2(ac[4 * j], ac[4 * j + 1]); y[j][1] = pack2(ac[4 * j + 2], ac[4 * j + 3]);
    }
    if (!bar_any(NB_WG + e, 128, bad) || it == 16) break;
    EVENT(24 + 2 * layer + e);
#pragma unroll 1
    for (int n = 0; n < 8; ++n) {
      if (w == 0) { mbar_expect1(B_R + 8 * e, 8192); bulk(ob + n * 8192, P.S->O + (J * 4096 + piece(n, cg) * 512), 8192, B_R + 8 * e); }
      mbar_wait(B_R + 8 * e, n & 1);
      bar_sync(NB_WG + e, 128);
    }
  }
  PROF(24, m_wo);
  if (layer == 0) {
    const float4 s = gram(y, g, P.zero);
    xg_put<true>(xa, y);
    str4_if(ps, nz(__float_as_uint(s.x)), __float_as_uint(s.y), __float_as_uint(s.z), __float_as_uint(s.w), t == (g >> 1));
    mbar_arrive1(B_ED + 8 * e);
    bar_sync(NB_WG + e, 128);
    xg_store(xa, 0);
    bar_arrive(NB_T + 3, 288);
  } else {
#pragma unroll
    for (int j = 0; j < 8; j += 2) stsm4(xa.a ^ (j * 16), y[j][0], y[j][1], y[j + 1][0], y[j + 1][1]);
    __syncwarp();
#pragma unroll
    for (int k = 0; k < 4; ++k) {
      const uint4 v = lds4((xa.b ^ ((k & 1) * 64)) + k * 512);
      stw4(xa.dst + ((k & 1) * 8 + (k >> 1)) * 64, v.x, v.y, v.z, v.w);
    }
  }
  PROF(25, m_epi);
}

#define HDELAY 200
#define ODELAY 200
#define FDELAY 300
#define PZB B_X + 48
#define H5 1
#define SRDELAY 350

DEV void o_load(const Params& P, int c, int e, int lane, int layer) {
  PW(8 + e)
  const int J = 2 * (c >> 3) + 1 - e;
#pragma unroll
  for (int n = 0; n < 8; ++n) mbar_expect1(B_O + 64 * e + 8 * n, n ? 8192 : 0);
  const uint4* src = P.S->O + J * 4096;
  const uint32_t* fp = P.S->F + (J * 32 + (lane & 28));
  keep(fp, P.zero);
  bar_sync(NB_T + 1 + e, 160);
  flag_set1(P.S->F + (J * 32 + 4 * (c & 7)));
  delay(ODELAY);
  PROF(26, a_go);
  poll(fp, 1);
  PROF(25, h_seen);
  bar_sync_if(NB_Q, 64, e);
  uint32_t dst = e ? SM_S1 : SM_XA, bar = B_O + 64 * e;
#pragma unroll 1
  for (int n = c & 7; n > (c & 7) - 7; --n) {
    dst += 8192; bar += 8;
    bulk(dst, src + (n > 0 ? 0 : 512), 8192, bar);
    src += 512;
  }
  bar_arrive_if(NB_Q, 64, !e);
  PROF(28, a_o);
}

DEV void stats(const Params& P, int c, int w, int lane, int layer) {
  PW(12 + w)
  lane = opq(lane);
  const int r = 2 * (lane >> 3), k = (2 * (c & 3) + ((lane >> 2) & 1)) ^ r, e = 1 - ((c >> 2) & 1);
  const uint32_t o = (32 * w + r) * 128 + k * 16 + (lane & 3) * 4;
  const uint32_t no0 = (lane & 7) != r, no1 = ((lane & 7) ^ 4) != r + 1;
  uint32_t* st = (uint32_t*)P.S->ST + (16 * c + 2 * (lane & 7) + (lane >> 4));
  keep(st, P.zero);
  float v[4] = {0.f, 0.f, 0.f, 0.f};
#pragma unroll 1
  for (int q = 0; q < 4; ++q) {
    mbar_wait(B_X + 16 * q + 8 * e, layer);
    PROF(19 + q, s_l);
    uint32_t x[8];
    for (int it = 0;; ++it) {
#pragma unroll
      for (int z = 0; z < 8; ++z) x[z] = lds1v(xstage(q, e) + (o ^ ((z & 1) * 144)) + (z >> 1) * 1024);
      const uint32_t ok = (both(x[0], x[2], layer) & both(x[4], x[6], layer) | no0) & (both(x[1], x[3], layer) & both(x[5], x[7], layer) | no1);
      if (__all_sync(0xffffffffu, ok & 1)) break;
      spin_guard(it);
    }
    mbar_arrive1(B_F + 8 * q);
#pragma unroll
    for (int z = 0; z < 8; ++z) {
      const float lo = bflo(x[z]), hi = bfhi(x[z]);
      v[0] += lo; v[1] += lo * lo; v[2] += hi; v[3] += hi * hi;
    }
  }
  PROFD(14, s_part, __float_as_uint(v[0]));
  fold<2>(v, lane, 16); fold<1>(v, lane, 8);
  PROFD(16, s_fold, __float_as_uint(v[0]));
  if (w) {
    sts1(SM_MISC - 128 + w * 128 + lane * 4, __float_as_uint(v[0]));
    bar_arrive(NB_P, 128);
  } else {
    mbar_wait(B_ST + 8, layer);
    bar_sync(NB_P, 128);
    v[0] += lds1f(SM_MISC + lane * 4) + lds1f(SM_MISC + 128 + lane * 4) + lds1f(SM_MISC + 256 + lane * 4);
    float m;
    const float sd = ln_sd(v[0], __shfl_xor_sync(0xffffffffu, v[0], 8), m);
    if (!(lane & 8)) str1(st, pack2(m, sd));
    PROF(17, s_pub);
    uint4 s;
    for (int it = 0;; ++it) {
      s = ldr4(P.S->ST + ((c >> 3) * 32 + lane));
      if (__all_sync(0xffffffffu, min4(s) != 0u)) break;
      spin_guard(it);
    }
    PROF(18, s_seen);
    const float r0 = rcp(bfhi(s.x)), r1 = rcp(bfhi(s.y)), r2 = rcp(bfhi(s.z)), r3 = rcp(bfhi(s.w));
    const uint32_t sg = 0x80008000u;
    sts4(SM_MISC + lane * 16, prmt(s.x, s.x, 0x1010) ^ sg, prmt(s.y, s.y, 0x1010) ^ sg, prmt(s.z, s.z, 0x1010) ^ sg, prmt(s.w, s.w, 0x1010) ^ sg);
    sts4(SM_STAT + 256 + lane * 32, __float_as_uint(r0), __float_as_uint(r1), pack2(r0, r1), prmt(s.x, s.y, 0x7632));
    sts4(SM_STAT + 272 + lane * 32, __float_as_uint(r2), __float_as_uint(r3), pack2(r2, r3), prmt(s.z, s.w, 0x7632));
    __syncwarp();
    mbar_arrive1(B_ST);
  }
  PROF(15, s_stat);
  if (w == 1) {
    mbar_wait(B_ST, layer);
    if (c >= 8) {
      uint2 s;
      for (int it = 0;; ++it) {
        s = ldr2((const uint2*)P.S->ST + ((c >> 3) * 64 - 12 + (lane & 11)));
        if (__all_sync(0xffffffffu, min(s.x, s.y) != 0u)) break;
        spin_guard(it);
      }
      const float r0 = rcp(bfhi(s.x)), r1 = rcp(bfhi(s.y));
      sts4(SM_STAT + 64 + (lane & 11) * 16, __float_as_uint(r0), __float_as_uint(r1), pack2(r0, r1), prmt(s.x, s.y, 0x7632));
    }
    bar_arrive(NB_H, 160);
  }
  if (w >= 2) {
    const uint4* h = P.S->H + (c * 256 + (w & 1) * 128 + lane);
    uint4 hv[4];
#pragma unroll
    for (int z = 0; z < 4; ++z) hv[z] = make_uint4(0, 0, 0, 0);
    bar_sync(NB_RL, 128);
    PROFD(26, s_hb, lds1v(SM_MISC));
    delay(HDELAY);
    for (int it = 0; c >= 8; ++it) {
#pragma unroll
      for (int z = 0; z < 4; ++z) hv[z] = ldr4(h + z * 32);
      if (__all_sync(0xffffffffu, min(min(hv[0].x, hv[1].x), min(hv[2].x, hv[3].x)) != 0u)) break;
      spin_guard(it);
    }
    mbar_wait(B_F + 24, layer);
#pragma unroll
    for (int z = 0; z < 4; ++z) sts4(kvslot(0) + (w & 1) * 2048 + lane * 16 + z * 512, hv[z].x, hv[z].y, movm(hv[z].z), movm(hv[z].w));
    bar_arrive(NB_H, 160);
    PROF(25, s_halo);
  }
}

DEV void finalize(const Params& P, int c, int lane, int layer) {
  PW(12)
  uint2* so = (uint2*)P.S->SR[layer] + ((lane >> 3) * 1024 + (lane & 2) * 256 + 4 * c + ((lane >> 1) & 2) + (lane & 1));
  const uint4* ps = &P.S->PS[c * 64 + lane];
  keep(so, P.zero); keep(ps, P.zero);
  uint4 a, b;
  if (layer == 0) {
    bar_sync(NB_P, 256);
    a = lds4(SM_RES + 8192 + lane * 16); b = lds4(SM_RES + 8704 + lane * 16);
  } else {
    mbar_wait(B_ED + 8 - 2 * (c & 4), 0);
    delay(FDELAY);
    for (int it = 0;; ++it) {
      a = ldr4(ps); b = ldr4(ps + 32);
      if (__all_sync(0xffffffffu, min(a.x, b.x) != 0u)) break;
      spin_guard(it);
    }
  }
  float z[4] = {__uint_as_float(a.x) + __uint_as_float(b.x), __uint_as_float(a.y) + __uint_as_float(b.y),
                __uint_as_float(a.z) + __uint_as_float(b.z), __uint_as_float(a.w) + __uint_as_float(b.w)};
#pragma unroll
  for (int o = 8; o < 32; o <<= 1)
#pragma unroll
    for (int k = 0; k < 4; ++k) z[k] += __shfl_xor_sync(0xffffffffu, z[k], o);
  const float m0 = z[0] * (1.f / 512.f), m1 = z[2] * (1.f / 512.f);
  const float r0 = rsq(fmaxf(z[1] * (1.f / 512.f) - m0 * m0, 0.f) + 1e-5f), r1 = rsq(fmaxf(z[3] * (1.f / 512.f) - m1 * m1, 0.f) + 1e-5f);
  const uint32_t wr = nz(pack2(r0, r1)), wm = pack2(m0, m1);
  str2(so, wr, wm); str2(so + 4096, wr, wm);
  bar_arrive_if(NB_Q, 448, !layer);
  PROF(23, s_sr);
}

DEV void announce(const Params& P, int c, int lane, int layer) {
  PW(13)
  uint32_t* cp = cnt_at(P, 5 * layer, c, lane);
  keep(cp, P.zero);
  bar_sync(NB_T + 3, 288);
  cnt_add(cp, 1, lane < NCOPY);
  if (!layer) { bar_sync(NB_Q, 448); fence_async_smem(); }
  PROF(24, s_own);
}

DEV void fetch(const Params& P, int c, int lane, int layer) {
  PW(13)
  mbar_expect1(B_E, 24576);
  cnt_wait(P, 5 * layer, c, lane);
#pragma unroll
  for (int k = 0; k < 4; ++k) bulk(SM_R + k * 16384 + R_B, P.S->XG + (128 * k + c) * 256, 4096, B_E);
  if (layer) delay(SRDELAY);
  bulk(SM_RES, P.S->SR[layer][c >> 4], 8192, B_E);
  if (!layer) { l2_prefetch(P.wqkv + c * 6144, 12288); l2_prefetch(P.wo + c * 2048, 4096); }
  PROF(25, s_all);
}

DEV float2 cs_rows(const Params& P, int row, int col, int lane) {
  float cs[8];
#pragma unroll
  for (int k = 0; k < 8; ++k) cs[k] = 0.f;
  uint4 v[8];
#pragma unroll
  for (int k = 0; k < 8; ++k) v[k] = ldnc4(P.wqkv + ((row + (lane >> 3)) * 1536 + col + 8 * (lane & 7)) + 4 * k * 1536);
#pragma unroll
  for (int k = 0; k < 8; ++k) {
    cs[0] += bflo(v[k].x); cs[1] += bfhi(v[k].x); cs[2] += bflo(v[k].y); cs[3] += bfhi(v[k].y);
    cs[4] += bflo(v[k].z); cs[5] += bfhi(v[k].z); cs[6] += bflo(v[k].w); cs[7] += bfhi(v[k].w);
  }
  fold<4>(cs, lane, 16); fold<2>(cs, lane, 8);
  return make_float2(cs[0], cs[1]);
}
DEV void cs_put(const Params& P, int b, int lane, float x, float y) {
  const uint32_t hi = pack2(x, y);
  uint32_t* p = (uint32_t*)P.S->CS + ((b & 7) * 192 + (b >> 3) * 64 + (lane & 7) * 8 + (lane >> 3));
  str1(p, nz(hi)); str1(p + 4, nz(pack2(x - bflo(hi), y - bfhi(hi))));
}
DEV void cs_spare(const Params& P, const CUtensorMap* mW, int j, int n, int warp, int lane) {
  mbar_init1(B_W + 8 * warp, warp < 8 ? 1 : 12);
  sts2f(SM_TAP + lane * 8, __uint_as_float(0x3F803F80u), __uint_as_float(0x3F803F80u));
  fence_async_smem();
  __syncthreads();
#pragma unroll 1
  for (int cg = j, ph = 0; cg < 8; cg += n, ph ^= 1) {
    if (warp == 12) {
#pragma unroll 1
      for (int h = 0; h < 8; ++h) {
        mbar_wait(B_W + 64 + 8 * h, ph ^ 1);
        mbar_expect1(B_W + 8 * h, 24576);
        tma3(SB + h * 24576, mW, 64 * cg, 64 * h, B_W + 8 * h);
      }
    } else if (warp < 12) {
      float d[4];
      zerov(d);
#pragma unroll 1
      for (int h = 0; h < 8; ++h) {
        mbar_wait(B_W + 8 * h, ph);
        wg_fence();
#pragma unroll
        for (int k = 0; k < 4; ++k) wg_ss8(d, mkdesc(SB + h * 24576 + (warp >> 2) * 8192, 16, 1024, 1) + k * 128, mkdesc(SM_TAP, 128, 128, 0));
        wg_commit();
        wg_wait<0>();
        mbar_arrive1(B_W + 64 + 8 * h);
      }
      const float x = (lane & 2) ? d[2] : d[0], y = __shfl_xor_sync(0xffffffffu, x, 4);
      const uint32_t hi = pack2(x, y), lo = pack2(x - bflo(hi), y - bfhi(hi));
      if (!(lane & 4)) str1((uint32_t*)P.S->CS + (cg * 192 + warp * 16 + (lane & 3) * 4 + (lane >> 3)), nz((lane & 1) ? lo : hi));
      __syncwarp();
    }
  }
}
DEV void cs_alone(const Params& P, int b, int lane) {
  float x = 0.f, y = 0.f;
#pragma unroll 1
  for (int k = 0; k < 16; ++k) { const float2 u = cs_rows(P, 32 * k, 64 * b, lane); x += u.x; y += u.y; }
  cs_put(P, b, lane, x, y);
}
DEV void cs_get(const Params& P, int cg, int lane) {
  const uint4* p = (const uint4*)P.S->CS + (cg * 48 + min(lane, 23) * 2);
  uint4 a, b;
  for (int it = 0;; ++it) {
    a = ldr4(p); b = ldr4(p + 1);
    if (__all_sync(0xffffffffu, min(min4(a), min4(b)) != 0u)) break;
    spin_guard(it);
  }
  sts4(SM_CS + min(lane, 23) * 32, a.x, a.y, a.z, a.w); sts4(SM_CS + min(lane, 23) * 32 + 16, b.x, b.y, b.z, b.w);
  fence_async_smem();
  __syncwarp();
  mbar_arrive1(B_CS);
}

DEV void x0_get(uint32_t (&x)[8][2], uint32_t a) {
  asm volatile("cp.async.wait_group 0;" ::: "memory");
#pragma unroll
  for (int z = 0; z < 4; ++z) {
    const uint4 v = lds4(a + z * 512);
    x[2 * (z & 2)][z & 1] = v.x; x[2 * (z & 2) + 1][z & 1] = v.y; x[2 * (z & 2) + 2][z & 1] = v.z; x[2 * (z & 2) + 3][z & 1] = v.w;
  }
}

DEV void par_load(const Params& P, int ch, int m, uint32_t (&pv)[8], bool c) {
  const int mo = ch * 128 + m;
  pv[0] = ld16_if(P.Are + mo, c); pv[1] = ld16_if(P.Aim + mo, c); pv[2] = ld16_if(P.Bre + mo, c); pv[3] = ld16_if(P.Bim + mo, c);
  pv[4] = ld16_if(P.Cre + mo, c); pv[5] = ld16_if(P.Cim + mo, c); pv[6] = ld16_if(P.logdt + ch, c); pv[7] = ld16_if(P.dskip + ch, c);
}

template <bool BY_SM> __global__ void __launch_bounds__(NTHR, 1)
fused_kernel(const __grid_constant__ Params P, const __grid_constant__ CUtensorMap mapW,
             const __grid_constant__ CUtensorMap mapWo) {
  extern __shared__ __align__(1024) uint8_t smem_raw[];
  uint32_t smid; asm("mov.u32 %0,%%smid;" : "=r"(smid));
  const int role = P.role[(BY_SM ? smid : blockIdx.x) + (threadIdx.x >> 10)];
  uint32_t pv[8];
  par_load(P, (threadIdx.x & 384) + (role & 127), threadIdx.x & 127, pv, threadIdx.x < 384 && role < 128);
  const int warp0 = __shfl_sync(0xffffffffu, threadIdx.x >> 5, 0), lane0 = threadIdx.x & 31, c = __shfl_sync(0xffffffffu, role, 0);
  if (c >= 128) {
    if (threadIdx.x < NCOPY * NSUB)
#pragma unroll 1
      for (int it = 0; it < 256 && ldr1(P.S->C + 32 * threadIdx.x) < 128 / NSUB; ++it) __nanosleep(200);
    __syncwarp();
    cs_spare(P, &mapW, c - 128, gridDim.x - 128, warp0, lane0);
    return;
  }
  const int cg = c & 7;
  PW(warp0)
  uint32_t dskip;
  {
    [[maybe_unused]] const int layer = 0;
    const int lane = lane0, g = lane >> 2, t = lane & 3, warp = warp0, k4 = warp >> 2, w = warp & 3;
    __syncthreads();
    const uint16_t* r = P.x0 + ((k4 < 2 ? 8192 * c + 64 * warp : (128 * (c >> 3) + 16 * (warp - 8)) * 512 + 64 * cg) + 1024 * g + 8 * t);
    const uint32_t xa = SM_R + k4 * 16384 + w * 2048 + lane * 16;
#pragma unroll
    for (int z = 0; z < 4; ++z) cp16(xa + z * 512, r + (z & 1) * 512 + (z & 2) * 16);
    asm volatile("cp.async.commit_group;" ::: "memory");
    sts4(SM_TAP + k4 * TAP_SZ + (32 * w + lane) * 16, 0, 0, 0, 0);
    sts4z_if(SM_TAP + k4 * TAP_SZ + 2048 + (32 * w + lane) * 16, w < 3);
    const XgAddr xd = xg_addr<false>(P.S->XG + (64 * cg * 256 + 16 * (c >> 3) + 8 * (k4 & 1)), SM_R + k4 * 16384 + 8192, w, lane, P.zero);
    uint32_t x[8][2];
    if (k4 == 3) {
      if (threadIdx.x == 448) {
        asm volatile("prefetch.tensormap [%0];" :: "l"(&mapW) : "memory");
        asm volatile("prefetch.tensormap [%0];" :: "l"(&mapWo) : "memory");
      }
      __syncwarp();
      par_load(P, 128 * k4 + c, 32 * w + lane, pv, true);
      if (s2u(smem_raw) != SB) __trap();
      sts4(SM_STAT - 32 + min(lane, 17) * 16, 0x3F800000u, 0x3F800000u, 0x3F803F80u, 0x3F803F80u);
      x0_get(x, xa);
      PROF(27, a_ld);
      xg_put<false>(xd, x);
      bar_sync(NB_WG + 3, 128);
      xg_store(xd, 1);
      bar_arrive(NB_T + 3, 288);
#pragma unroll
      for (int n = 0; n < 14; ++n) mbar_init1(SM_BAR + (n < 10 ? w * 80 : 240 + w * 32) + n * 8, n < 10 ? 1 : (CNT >> (8 * w + 2 * (n - 10 & 2))) & 15);
      bar_sync(NB_Q, 448);
    }
    tables(pv, k4, w, lane);
    if (k4 < 3) {
      x0_get(x, xa);
      if (k4 < 2) {
        const float4 s = gram(x, g, P.zero);
        if (t == (g >> 1)) sts4f(SM_RES + 8192 + (warp * 8 + g) * 16, s.x, s.y, s.z, s.w);
        __syncwarp();
        bar_arrive_if(NB_P, 256, warp != 7);
      } else {
        xg_put<false>(xd, x);
        bar_sync(NB_WG + 2, 128);
        xg_store(xd, 1);
        bar_arrive(NB_T + 3, 288);
      }
    }
    dskip = pv[7];
    PROF(1, a_x0);
  }
#pragma unroll 1
  for (int layer = 0; layer < 2; ++layer) {
    int lane = lane_here(P.zero);
    const int warp = warp0 | (layer & P.zero), k4 = warp >> 2, w = warp & 3;
    if (warp == (layer ? 12 : 7)) finalize(P, c, lane, layer);
    if (warp == (layer ? 13 : 6)) { announce(P, c, lane, layer); fetch(P, c, lane, layer); }
    if (layer == 0) {
      taps(dskip, k4, w, lane);
    }
    conv(P, &mapW, c, k4, w, layer);
    lane = lane_here(P.zero);
    if (k4 < 2) {
      bar_arrive_if(NB_H, 256, warp != 4);
      if (warp == 0) {
        mbar_wait(B_K, 0);
        cnt_wait(P, 1 + 5 * layer, c, lane);
        x_load(P, c, 0, layer);
        PROF(27, m_xi);
      }
      attn_phase(P, c, k4, w, lane, layer);
    } else {
      bar_arrive_if(NB_RL, 256, warp >= 10);
      if (k4 == 3) {
        stats(P, c, w, lane, layer);
      } else if (w < 2) {
        bar_sync_if(NB_RL, 256, w);
        cnt_wait(P, 3 + 5 * layer + w, c, lane);
        bar_sync_if(NB_RL, 256, !w);
        if (w) mbar_wait(B_F, layer);
        x_load(P, c, 2 + w, layer);
        if (H5 && w) w_load(&mapW, cg, 5);
        PROF(14, h_xi);
        if (w == 1) str4(&P.S->SR[layer][lane >> 2][4 * c + (lane & 3)], 0, 0, 0, 0);
      } else if (w == 2) {
        mbar_expect1(B_WO, 65536);
        mbar_expect1(B_RES, 16384);
#pragma unroll 1
        for (int q = 0; q < 4; ++q) {
          if (FH && q < 2) { mbar_wait(B_FH + 8 * q, layer); w_load(&mapW, cg, 4 + 2 * q); }
          mbar_wait(B_F + 8 * q, layer);
          if (!FH && q < 2) w_load(&mapW, cg, 4 + 2 * q);
          if (q == 1 || (q == 0 && !H5)) w_load(&mapW, cg, 5 + 2 * q);
          if (q == 2) {
            mbar_wait(B_ST, layer);
#pragma unroll 1
            for (int n = 0; n < 8; ++n) tma5(SM_R + n * 8192, &mapWo, 64 * cg, 2 * piece(n, cg), B_WO);
          }
          if (q == 3) {
#pragma unroll
            for (int e = 0; e < 2; ++e) bulk(SM_RES + e * 8192, P.S->XF + ((2 * (c >> 3) + 1 - e) * 4096 + cg * 512), 8192, B_RES);
          }
          PROF(15 + q, h_w);
        }
      }
      if (warp == 11) {
        if (!BY_SM && c < 24 && layer == 0) cs_alone(P, c, lane);
#pragma unroll
        for (int z = 0; z < 8; ++z) sts4(SM_RES + 10240 + lane * 16 + z * 512, ~0u, ~0u, ~0u, ~0u);
        fence_async_smem();
        mbar_wait(PZB, layer);
#pragma unroll
        for (int z = 0; z < 4; ++z) bulk_store(&P.S->O[((c >> 3) * 16 + cg) * 512] + ((z >> 1) * 4096 + (z & 1) * 256), SM_RES + 10240, 4096);
        asm volatile("cp.async.bulk.commit_group;\ncp.async.bulk.wait_group 0;" ::: "memory");
        mbar_arrive1(B_ST + 8);
        PROF(18, h_pz);
      }
      if (warp == 8 && layer == 0) { cs_get(P, cg, lane); PROF(20, h_cs); }
      if (warp < 10) o_load(P, c, w, lane, layer);
    }
    asm volatile("mov.b32 %0,0;" : "=r"(dskip));
  }
}

typedef CUresult (*EncodeFn)(CUtensorMap*, CUtensorMapDataType, cuuint32_t, void*, const cuuint64_t*, const cuuint64_t*,
                             const cuuint32_t*, const cuuint32_t*, CUtensorMapInterleave, CUtensorMapSwizzle,
                             CUtensorMapL2promotion, CUtensorMapFloatOOBfill);

#define PLAIN false
static int place_roles(uint8_t* role) {
  int dev = 0, nsm = 0;
  cudaGetDevice(&dev);
  cudaDeviceGetAttribute(&nsm, cudaDevAttrMultiProcessorCount, dev);
  if (nsm <= 128 || nsm > 144 || (nsm & 1)) return 0;
  cudaFuncSetAttribute(fused_kernel<true>, cudaFuncAttributeNonPortableClusterSizeAllowed, 1);
  int occ[9] = {0};
  for (int k = 2; k <= 8; ++k) {
    cudaLaunchConfig_t cfg = {};
    cudaLaunchAttribute at[1];
    at[0].id = cudaLaunchAttributeClusterDimension;
    at[0].val.clusterDim.x = 2 * k; at[0].val.clusterDim.y = 1; at[0].val.clusterDim.z = 1;
    cfg.gridDim = dim3(2 * k); cfg.blockDim = dim3(NTHR); cfg.dynamicSmemBytes = SM_TOTAL; cfg.attrs = at; cfg.numAttrs = 1;
    if (cudaOccupancyMaxActiveClusters(&occ[k], fused_kernel<true>, &cfg) != cudaSuccess) { cudaGetLastError(); occ[k] = 0; }
  }
  int n[10];
  n[7] = occ[8]; n[6] = occ[7]; n[5] = occ[6] - 0; n[4] = occ[5];
  n[3] = occ[4] - n[7]; n[1] = occ[2] - n[3] - n[5] - n[7]; n[0] = n[2] = n[1];
  n[8] = occ[3] - n[2] - n[5];
  const int ntpc = nsm / 2;
  int sum = 0;
  bool ok = n[0] > 0 && n[0] <= 8;
  for (int r = 0; r < 9; ++r) { ok = ok && n[r] >= 0 && (r == 0 || n[r] <= n[r - 1]); sum += n[r]; }
  if (!ok || sum > ntpc) { for (int r = 0; r < 9; ++r) n[r] = r < 8 ? 8 : 0; sum = 64; }
  int tp[8][9], cnt[8] = {0}, pool[72], np = 0, id = 0;
  for (int r = 0; r < 9; ++r)
    for (int g = n[0] - n[r]; g < n[0]; ++g) tp[g][cnt[g]++] = id++;
  for (; id < ntpc; ++id) pool[np++] = id;
  int order[72], no = 0;
  for (int g = 0; g < n[0]; ++g) {
    const int full = cnt[g] / 4 * 4;
    for (int k = 0; k < cnt[g]; ++k) { if (k < full) order[no++] = tp[g][k]; else pool[np++] = tp[g][k]; }
  }
  for (int k = 0; k < np; ++k) order[no++] = pool[k];
  for (int k = 0; k < ntpc; ++k) { role[2 * order[k]] = 2 * k; role[2 * order[k] + 1] = 2 * k + 1; }
  return nsm;
}

extern "C" void kernel_launch(void* const* d_in, const int* in_sizes, int n_in, void* d_out, int out_size) {
  (void)in_sizes; (void)n_in; (void)out_size;
  static EncodeFn enc = nullptr;
  static uint8_t role[144];
  static int nsm = 0;
  static void* scratch = nullptr;
  if (!enc) {
    void* fn = nullptr;
    cudaDriverEntryPointQueryResult qr;
    cudaGetDriverEntryPoint("cuTensorMapEncodeTiled", &fn, cudaEnableDefault, &qr);
    enc = (EncodeFn)fn;
    cudaFuncSetAttribute(fused_kernel<true>, cudaFuncAttributeMaxDynamicSharedMemorySize, SM_TOTAL);
    cudaFuncSetAttribute(fused_kernel<PLAIN>, cudaFuncAttributeMaxDynamicSharedMemorySize, SM_TOTAL);
    nsm = place_roles(role);
    cudaGetSymbolAddress(&scratch, g_S);
  }
  CUtensorMap mW, mWo;
  {
    cuuint64_t dim[3] = {512, 512, 3}, str[2] = {3072, 1024};
    cuuint32_t box[3] = {64, 64, 3}, es[3] = {1, 1, 1};
    enc(&mW, CU_TENSOR_MAP_DATA_TYPE_BFLOAT16, 3, d_in[10], dim, str, box, es, CU_TENSOR_MAP_INTERLEAVE_NONE,
        CU_TENSOR_MAP_SWIZZLE_128B, CU_TENSOR_MAP_L2_PROMOTION_NONE, CU_TENSOR_MAP_FLOAT_OOB_FILL_NONE);
  }
  {
    cuuint64_t dim[5] = {512, 2, 4, 4, 16}, str[4] = {1024, 8192, 2048, 32768};
    cuuint32_t box[5] = {64, 2, 4, 4, 2}, es[5] = {1, 1, 1, 1, 1};
    enc(&mWo, CU_TENSOR_MAP_DATA_TYPE_BFLOAT16, 5, d_in[11], dim, str, box, es, CU_TENSOR_MAP_INTERLEAVE_NONE,
        CU_TENSOR_MAP_SWIZZLE_128B, CU_TENSOR_MAP_L2_PROMOTION_NONE, CU_TENSOR_MAP_FLOAT_OOB_FILL_NONE);
  }
  Params P;
  P.x0 = (const uint16_t*)d_in[0]; P.Are = (const uint16_t*)d_in[1]; P.Aim = (const uint16_t*)d_in[2];
  P.Bre = (const uint16_t*)d_in[3]; P.Bim = (const uint16_t*)d_in[4]; P.Cre = (const uint16_t*)d_in[5];
  P.Cim = (const uint16_t*)d_in[6]; P.logdt = (const uint16_t*)d_in[7]; P.dskip = (const uint16_t*)d_in[8];
  P.wqkv = (const uint16_t*)d_in[10]; P.wo = (const uint16_t*)d_in[11]; P.out = (uint16_t*)d_out;
  for (int k = 0; k < 144; ++k) P.role[k] = nsm > 0 ? role[k] : k;
  P.pad = 0;
  P.zero = 0;
  P.S = (Scratch*)scratch;
  if (nsm > 0) fused_kernel<true><<<nsm, NTHR, SM_TOTAL, cudaStreamPerThread>>>(P, mW, mWo);
  else fused_kernel<PLAIN><<<128, NTHR, SM_TOTAL, cudaStreamPerThread>>>(P, mW, mWo);
}
```

```cpp
#include <cuda_runtime.h>
#include <cuda_bf16.h>
#include <cuda.h>
#include <stdint.h>

#define DEV __device__ __forceinline__

#define NCOPY 4
#define NSUB 1
constexpr int NTHR = 512;
constexpr int SPIN_LIMIT = 1 << 22;

constexpr uint32_t SB = 1024;
constexpr uint32_t SM_XA   = SB;
constexpr uint32_t SM_S0   = SM_XA + 16384;
constexpr uint32_t SM_S1   = SM_S0 + 49152;
constexpr uint32_t SM_XB   = SM_S1 + 49152;
constexpr uint32_t SM_R    = SM_XB + 16384;
constexpr uint32_t SM_RES  = SM_R + 65536;
constexpr uint32_t SM_TAP  = SM_RES + 16384;
constexpr int TAP_SZ = 3584;
constexpr uint32_t SM_CS   = SM_TAP + 4 * TAP_SZ;
constexpr uint32_t SM_STAT = SM_CS + 800;
constexpr uint32_t SM_MISC = SM_STAT + 1280;
constexpr uint32_t SM_BAR  = SM_MISC + 512;
constexpr int SM_TOTAL = SM_BAR + 448 - SB;
constexpr int R_U = 512, R_A5 = 5120, R_A3 = 8704, R_B = 11776;
constexpr int T_E = 1536, T_O = T_E + 1602, T_C = 3714;
constexpr uint32_t B_W = SM_BAR, B_X = SM_BAR + 64, B_O = SM_BAR + 128, B_WO = SM_BAR + 256, B_RES = SM_BAR + 264;
constexpr uint32_t B_ST = SM_BAR + 272, B_R = SM_BAR + 288, B_E = SM_BAR + 304;
constexpr uint32_t B_F = SM_BAR + 320, B_G = SM_BAR + 352, B_K = SM_BAR + 376, B_ED = SM_BAR + 384, B_CS = SM_BAR + 400, B_FH = SM_BAR + 416;
constexpr uint32_t CNT = 0x141444CC;
constexpr int NB_WG = 1, NB_T = 5, NB_Q = 10, NB_H = 11, NB_P = 14, NB_RL = 15;

struct Scratch {
  uint32_t F[32 * 32];
  uint4    H[17 * 8 * 256];
  uint4    SR[2][8][512];
  uint4    ST[32 * 16];
  uint4    PS[128 * 64];
  uint4    CS[8 * 48];
  uint32_t C[10 * 32 * 32];
  uint4    XF[32 * 4096];
  uint4    O[32 * 8 * 512];
  uint4    XG[512 * 256];
};
__device__ __align__(1024) Scratch g_S;

struct Params {
  const uint16_t *logdt, *dskip, *Are, *Aim, *Bre, *Bim, *Cre, *Cim, *x0, *wqkv, *wo;
  uint16_t* out;
  Scratch* S;
  uint32_t zero, pad;
  uint8_t role[72];
};
#define EVENT(n) do {} while (0)
#define PROFD(slot, name, v) do {} while (0)
#define PROF(slot, name) do {} while (0)
#define PW(x)

DEV uint32_t s2u(const void* p) { return (uint32_t)__cvta_generic_to_shared(p); }
template <class T> DEV T opq(T x) { asm volatile("" : "+r"(x)); return x; }
DEV uint32_t pack2(float lo, float hi) { uint32_t d; asm("cvt.rn.bf16x2.f32 %0,%1,%2;" : "=r"(d) : "f"(hi), "f"(lo)); return d; }
DEV float bflo(uint32_t v) { return __uint_as_float(v << 16); }
DEV float bfhi(uint32_t v) { return __uint_as_float(v & 0xFFFF0000u); }
DEV float bfr(float x) { return bflo(pack2(x, 0.f)); }
DEV uint32_t hadd2(uint32_t a, uint32_t b) { uint32_t d; asm("add.rn.bf16x2 %0,%1,%2;" : "=r"(d) : "r"(a), "r"(b)); return d; }
DEV uint32_t hsub2(uint32_t a, uint32_t b) { uint32_t d; asm("sub.rn.bf16x2 %0,%1,%2;" : "=r"(d) : "r"(a), "r"(b)); return d; }
DEV uint32_t hmul2(uint32_t a, uint32_t b) { uint32_t d; asm("mul.rn.bf16x2 %0,%1,%2;" : "=r"(d) : "r"(a), "r"(b)); return d; }
DEV uint32_t hfma2(uint32_t a, uint32_t b, uint32_t c) { uint32_t d; asm("fma.rn.bf16x2 %0,%1,%2,%3;" : "=r"(d) : "r"(a), "r"(b), "r"(c)); return d; }
DEV uint32_t hmax2(uint32_t a, uint32_t b) { uint32_t d; asm("max.bf16x2 %0,%1,%2;" : "=r"(d) : "r"(a), "r"(b)); return d; }
DEV uint32_t prmt(uint32_t a, uint32_t b, uint32_t s) { uint32_t d; asm("prmt.b32 %0,%1,%2,%3;" : "=r"(d) : "r"(a), "r"(b), "r"(s)); return d; }
DEV uint32_t nz(uint32_t v) { uint32_t d; asm("max.u32 %0,%1,1;" : "=r"(d) : "r"(v)); return d; }
DEV uint32_t tagged(uint32_t v, uint32_t m, uint32_t tag) { uint32_t d; asm("lop3.b32 %0,%1,%2,%3,0xB8;" : "=r"(d) : "r"(v), "r"(m), "r"(tag)); return d; }
DEV uint32_t both(uint32_t a, uint32_t b, uint32_t x) { uint32_t d; asm("lop3.b32 %0,%1,%2,%3,0x42;" : "=r"(d) : "r"(a), "r"(b), "r"(x)); return d; }
DEV uint4 hadd8(const uint4& a, const uint4& b) { return make_uint4(hadd2(a.x, b.x), hadd2(a.y, b.y), hadd2(a.z, b.z), hadd2(a.w, b.w)); }
DEV uint32_t min4(const uint4& v) { return min(min(v.x, v.y), min(v.z, v.w)); }
DEV float rcp(float x) { float y; asm("rcp.approx.ftz.f32 %0,%1;" : "=f"(y) : "f"(x)); return y; }
DEV float sqrt_(float x) { float y; asm("sqrt.approx.ftz.f32 %0,%1;" : "=f"(y) : "f"(x)); return y; }
DEV float rsq(float x) { float y; asm("rsqrt.approx.ftz.f32 %0,%1;" : "=f"(y) : "f"(x)); return y; }
DEV float ex2(float x) { float y; asm("ex2.approx.ftz.f32 %0,%1;" : "=f"(y) : "f"(x)); return y; }

DEV uint4 ldr4(const void* p) { uint4 v; asm volatile("ld.relaxed.gpu.global.v4.u32 {%0,%1,%2,%3},[%4];" : "=r"(v.x), "=r"(v.y), "=r"(v.z), "=r"(v.w) : "l"(p) : "memory"); return v; }
DEV void ldr4_if(uint4& v, const void* p, bool c) {
  asm volatile("{.reg .pred q; setp.ne.u32 q,%5,0; @q ld.relaxed.gpu.global.v4.u32 {%0,%1,%2,%3},[%4];}"
    : "+r"(v.x), "+r"(v.y), "+r"(v.z), "+r"(v.w) : "l"(p), "r"((uint32_t)c) : "memory");
}
DEV uint2 ldr2(const void* p) { uint2 v; asm volatile("ld.relaxed.gpu.global.v2.u32 {%0,%1},[%2];" : "=r"(v.x), "=r"(v.y) : "l"(p) : "memory"); return v; }
DEV uint32_t ldr1(const void* p) { uint32_t v; asm volatile("ld.relaxed.gpu.global.u32 %0,[%1];" : "=r"(v) : "l"(p) : "memory"); return v; }
DEV void str4(void* p, uint32_t a, uint32_t b, uint32_t c, uint32_t d) { asm volatile("st.relaxed.gpu.global.v4.u32 [%0],{%1,%2,%3,%4};" :: "l"(p), "r"(a), "r"(b), "r"(c), "r"(d) : "memory"); }
DEV void str4_if(void* p, uint32_t a, uint32_t b, uint32_t c, uint32_t d, bool q) {
  asm volatile("{.reg .pred q; setp.ne.u32 q,%5,0; @q st.relaxed.gpu.global.v4.u32 [%0],{%1,%2,%3,%4};}" :: "l"(p), "r"(a), "r"(b), "r"(c), "r"(d), "r"((uint32_t)q) : "memory");
}
DEV void str2(void* p, uint32_t a, uint32_t b) { asm volatile("st.relaxed.gpu.global.v2.u32 [%0],{%1,%2};" :: "l"(p), "r"(a), "r"(b) : "memory"); }
DEV void str1(void* p, uint32_t a) { asm volatile("st.relaxed.gpu.global.u32 [%0],%1;" :: "l"(p), "r"(a) : "memory"); }
DEV void stw4(void* p, uint32_t a, uint32_t b, uint32_t c, uint32_t d) { asm volatile("st.global.v4.u32 [%0],{%1,%2,%3,%4};" :: "l"(p), "r"(a), "r"(b), "r"(c), "r"(d) : "memory"); }
DEV uint4 ldnc4(const void* p) { uint4 v; asm volatile("ld.global.nc.v4.u32 {%0,%1,%2,%3},[%4];" : "=r"(v.x), "=r"(v.y), "=r"(v.z), "=r"(v.w) : "l"(p)); return v; }
DEV uint4 ldw4(const void* p) { uint4 v; asm volatile("ld.global.v4.u32 {%0,%1,%2,%3},[%4];" : "=r"(v.x), "=r"(v.y), "=r"(v.z), "=r"(v.w) : "l"(p) : "memory"); return v; }
DEV void cp16(uint32_t d, const void* p) { asm volatile("cp.async.cg.shared.global [%0],[%1],16;" :: "r"(d), "l"(p) : "memory"); }
DEV uint32_t ld16_if(const void* p, bool c) { uint32_t v = 0; asm volatile("{.reg .pred q; setp.ne.u32 q,%2,0; @q ld.global.u16 %0,[%1];}" : "+r"(v) : "l"(p), "r"((uint32_t)c) : "memory"); return v; }
DEV uint32_t ldnc16(const void* p) { uint32_t v; asm volatile("ld.global.u16 %0,[%1];" : "=r"(v) : "l"(p) : "memory"); return v; }

DEV uint32_t lds1v(uint32_t a) { uint32_t v; asm volatile("ld.volatile.shared.u32 %0,[%1];" : "=r"(v) : "r"(a) : "memory"); return v; }
DEV uint4 lds4v(uint32_t a) { uint4 v; asm volatile("ld.volatile.shared.v4.u32 {%0,%1,%2,%3},[%4];" : "=r"(v.x), "=r"(v.y), "=r"(v.z), "=r"(v.w) : "r"(a) : "memory"); return v; }
DEV uint32_t lds1(uint32_t a) { uint32_t v; asm volatile("ld.shared.u32 %0,[%1];" : "=r"(v) : "r"(a)); return v; }
DEV uint2 lds2(uint32_t a) { uint2 v; asm volatile("ld.shared.v2.u32 {%0,%1},[%2];" : "=r"(v.x), "=r"(v.y) : "r"(a)); return v; }
DEV uint4 lds4(uint32_t a) { uint4 v; asm volatile("ld.shared.v4.u32 {%0,%1,%2,%3},[%4];" : "=r"(v.x), "=r"(v.y), "=r"(v.z), "=r"(v.w) : "r"(a)); return v; }
DEV uint32_t lds16(uint32_t a) { uint32_t v; asm volatile("ld.shared.u16 %0,[%1];" : "=r"(v) : "r"(a)); return v; }
DEV float lds1f(uint32_t a) { float v; asm volatile("ld.shared.f32 %0,[%1];" : "=f"(v) : "r"(a)); return v; }
DEV float2 lds2f(uint32_t a) { float2 v; asm volatile("ld.shared.v2.f32 {%0,%1},[%2];" : "=f"(v.x), "=f"(v.y) : "r"(a)); return v; }
DEV float4 lds4f(uint32_t a) { float4 v; asm volatile("ld.shared.v4.f32 {%0,%1,%2,%3},[%4];" : "=f"(v.x), "=f"(v.y), "=f"(v.z), "=f"(v.w) : "r"(a)); return v; }
DEV void sts1(uint32_t a, uint32_t v) { asm volatile("st.shared.u32 [%0],%1;" :: "r"(a), "r"(v) : "memory"); }
DEV void sts16(uint32_t a, uint32_t v) { asm volatile("{.reg .b16 h; cvt.u16.u32 h,%1; st.shared.u16 [%0],h;}" :: "r"(a), "r"(v) : "memory"); }
DEV void sts2f(uint32_t a, float x, float y) { asm volatile("st.shared.v2.f32 [%0],{%1,%2};" :: "r"(a), "f"(x), "f"(y) : "memory"); }
DEV void sts4f(uint32_t a, float x, float y, float z, float w) { asm volatile("st.shared.v4.f32 [%0],{%1,%2,%3,%4};" :: "r"(a), "f"(x), "f"(y), "f"(z), "f"(w) : "memory"); }
DEV void sts4(uint32_t a, uint32_t x, uint32_t y, uint32_t z, uint32_t w) { asm volatile("st.shared.v4.u32 [%0],{%1,%2,%3,%4};" :: "r"(a), "r"(x), "r"(y), "r"(z), "r"(w) : "memory"); }
DEV void sts4_if(uint32_t a, uint32_t x, uint32_t y, uint32_t z, uint32_t w, bool c) {
  asm volatile("{.reg .pred q; setp.ne.u32 q,%5,0; @q st.shared.v4.u32 [%0],{%1,%2,%3,%4};}" :: "r"(a), "r"(x), "r"(y), "r"(z), "r"(w), "r"((uint32_t)c) : "memory");
}
DEV void sts4z_if(uint32_t a, bool c) { asm volatile("{.reg .pred q; setp.ne.u32 q,%1,0; @q st.shared.v4.u32 [%0],{%2,%2,%2,%2};}" :: "r"(a), "r"((uint32_t)c), "r"(0) : "memory"); }

DEV void ldsm4t(uint32_t& r0, uint32_t& r1, uint32_t& r2, uint32_t& r3, uint32_t a) { asm volatile("ldmatrix.sync.aligned.m8n8.x4.trans.shared.b16 {%0,%1,%2,%3},[%4];" : "=r"(r0), "=r"(r1), "=r"(r2), "=r"(r3) : "r"(a) : "memory"); }
DEV void stsm4(uint32_t a, uint32_t r0, uint32_t r1, uint32_t r2, uint32_t r3) { asm volatile("stmatrix.sync.aligned.m8n8.x4.shared.b16 [%0],{%1,%2,%3,%4};" :: "r"(a), "r"(r0), "r"(r1), "r"(r2), "r"(r3) : "memory"); }
DEV void stsm2(uint32_t a, uint32_t r0, uint32_t r1) { asm volatile("stmatrix.sync.aligned.m8n8.x2.shared.b16 [%0],{%1,%2};" :: "r"(a), "r"(r0), "r"(r1) : "memory"); }
DEV void stsm4t(uint32_t a, uint32_t r0, uint32_t r1, uint32_t r2, uint32_t r3) { asm volatile("stmatrix.sync.aligned.m8n8.x4.trans.shared.b16 [%0],{%1,%2,%3,%4};" :: "r"(a), "r"(r0), "r"(r1), "r"(r2), "r"(r3) : "memory"); }
DEV uint32_t movm(uint32_t a) { uint32_t d; asm volatile("movmatrix.sync.aligned.m8n8.trans.b16 %0,%1;" : "=r"(d) : "r"(a)); return d; }
DEV void mma16(float (&d)[4], uint32_t a0, uint32_t a1, uint32_t a2, uint32_t a3, uint32_t b0, uint32_t b1) {
  asm volatile("mma.sync.aligned.m16n8k16.row.col.f32.bf16.bf16.f32 {%0,%1,%2,%3},{%4,%5,%6,%7},{%8,%9},{%0,%1,%2,%3};"
    : "+f"(d[0]), "+f"(d[1]), "+f"(d[2]), "+f"(d[3]) : "r"(a0), "r"(a1), "r"(a2), "r"(a3), "r"(b0), "r"(b1));
}
DEV void mma16z(float (&d)[4], uint32_t a0, uint32_t a1, uint32_t a2, uint32_t a3, uint32_t b0, uint32_t b1) {
  asm volatile("mma.sync.aligned.m16n8k16.row.col.f32.bf16.bf16.f32 {%0,%1,%2,%3},{%4,%5,%6,%7},{%8,%9},{%10,%10,%10,%10};"
    : "=f"(d[0]), "=f"(d[1]), "=f"(d[2]), "=f"(d[3]) : "r"(a0), "r"(a1), "r"(a2), "r"(a3), "r"(b0), "r"(b1), "f"(0.f));
}
DEV void mma8z(float (&d)[4], uint32_t a0, uint32_t a1, uint32_t b0) {
  asm volatile("mma.sync.aligned.m16n8k8.row.col.f32.bf16.bf16.f32 {%0,%1,%2,%3},{%4,%5},{%6},{%7,%7,%7,%7};"
    : "=f"(d[0]), "=f"(d[1]), "=f"(d[2]), "=f"(d[3]) : "r"(a0), "r"(a1), "r"(b0), "f"(0.f));
}
DEV void mma8(float (&d)[4], uint32_t a0, uint32_t a1, uint32_t b0) {
  asm volatile("mma.sync.aligned.m16n8k8.row.col.f32.bf16.bf16.f32 {%0,%1,%2,%3},{%4,%5},{%6},{%0,%1,%2,%3};"
    : "+f"(d[0]), "+f"(d[1]), "+f"(d[2]), "+f"(d[3]) : "r"(a0), "r"(a1), "r"(b0));
}

DEV void bar_sync(int id, int n) { asm volatile("bar.sync %0,%1;" :: "r"(id), "r"(n) : "memory"); }
DEV void bar_arrive(int id, int n) { asm volatile("bar.arrive %0,%1;" :: "r"(id), "r"(n) : "memory"); }
DEV void bar_sync_if(int id, int n, int c) { asm volatile("{.reg .pred q; setp.ne.s32 q,%2,0; @q bar.sync %0,%1;}" :: "r"(id), "r"(n), "r"(c) : "memory"); }
DEV void bar_arrive_if(int id, int n, int c) { asm volatile("{.reg .pred q; setp.ne.s32 q,%2,0; @q bar.arrive %0,%1;}" :: "r"(id), "r"(n), "r"(c) : "memory"); }
DEV bool bar_any(int id, int n, bool c) {
  uint32_t r; asm volatile("{.reg .pred p,q; setp.ne.u32 q,%3,0; bar.red.or.pred p,%1,%2,q; selp.u32 %0,1,0,p;}" : "=r"(r) : "r"(id), "r"(n), "r"((uint32_t)c) : "memory");
  return __any_sync(0xffffffffu, r);
}
DEV void fence_async_glob() { asm volatile("fence.proxy.async.global;" ::: "memory"); }
DEV void fence_async_smem() { asm volatile("fence.proxy.async.shared::cta;" ::: "memory"); }
DEV void fence_gpu() { asm volatile("fence.acq_rel.gpu;" ::: "memory"); }
DEV void mbar_wait(uint32_t b, uint32_t ph) {
  asm volatile("{\n.reg .pred p;\nW: mbarrier.try_wait.parity.shared::cta.b64 p,[%0],%1;\n@!p bra W;\n}" :: "r"(b), "r"(ph) : "memory");
}
DEV bool mbar_test(uint32_t b, uint32_t ph) {
  uint32_t r; asm volatile("{.reg .pred p; mbarrier.test_wait.parity.shared::cta.b64 p,[%1],%2; selp.u32 %0,1,0,p;}" : "=r"(r) : "r"(b), "r"(ph) : "memory");
  return __all_sync(0xffffffffu, r);
}
DEV uint32_t mbar_test2(uint32_t b, uint32_t ph) {
  uint32_t r; asm volatile("{.reg .pred p,q; mbarrier.test_wait.parity.shared::cta.b64 p,[%1],%2; mbarrier.test_wait.parity.shared::cta.b64 q,[%1+8],%2;\n"
                           "and.pred p,p,q; selp.u32 %0,1,0,p;}" : "=r"(r) : "r"(b), "r"(ph) : "memory");
  return r;
}
DEV void spin_guard(int it) { asm volatile("{.reg .pred p; setp.gt.s32 p,%0,%1; @p trap;}" :: "r"(it), "n"(SPIN_LIMIT)); }
DEV uint32_t here(uint32_t zero) {
  uint32_t d; asm volatile("mov.u32 %0,%%clock;" : "=r"(d) :: "memory"); return d & zero;
}
DEV int lane_here(uint32_t zero) {
  uint32_t d; asm volatile("mov.u32 %0,%%laneid;" : "=r"(d)); return d | here(zero);
}
DEV void delay(uint32_t n) {
  asm volatile("{\n.reg .pred p;\n.reg .u32 a,b;\nmov.u32 a,%%clock;\nW: mov.u32 b,%%clock;\nsub.u32 b,b,a;\nsetp.lt.u32 p,b,%0;\n@p bra.uni W;\n}" :: "r"(n) : "memory");
}
DEV void poll(const uint32_t* p, uint32_t n) {
  for (int it = 0; !__all_sync(0xffffffffu, ldr1(p) >= n); ++it) spin_guard(it);
}
DEV uint32_t* cnt_at(const Params& P, int n, int c, int lane) { return P.S->C + (32 * (NSUB * lane + c % NSUB) + n * 1024); }
DEV void cnt_add(uint32_t* p, uint32_t one, bool q) { asm volatile("{.reg .pred p; setp.ne.u32 p,%2,0; @p red.relaxed.gpu.global.add.u32 [%0],%1;}" :: "l"(p), "r"(one), "r"((uint32_t)q) : "memory"); }
DEV void cnt_wait(const Params& P, int n, int c, int lane) { poll(P.S->C + (32 * (NSUB * (c / (128 / NCOPY)) + lane % NSUB) + n * 1024), 128 / NSUB); }
DEV void mbar_init1(uint32_t b, int n) { asm volatile("{.reg .pred p; elect.sync _|p,0xffffffff; @p mbarrier.init.shared::cta.b64 [%0],%1;}" :: "r"(b), "r"(n) : "memory"); }
DEV void mbar_arrive1(uint32_t b) { asm volatile("{.reg .pred p; elect.sync _|p,0xffffffff; @p mbarrier.arrive.shared::cta.b64 _,[%0];}" :: "r"(b) : "memory"); }
DEV void mbar_arrive1_if(uint32_t b, int c) {
  asm volatile("{.reg .pred p,q; setp.ne.s32 q,%1,0; elect.sync _|p,0xffffffff; and.pred p,p,q; @p mbarrier.arrive.shared::cta.b64 _,[%0];}" :: "r"(b), "r"(c) : "memory");
}
DEV void mbar_expect1(uint32_t b, int bytes) { asm volatile("{.reg .pred p; elect.sync _|p,0xffffffff; @p mbarrier.arrive.expect_tx.shared::cta.b64 _,[%0],%1;}" :: "r"(b), "r"(bytes) : "memory"); }
DEV void flag_set1(uint32_t* q) { asm volatile("{.reg .pred p; elect.sync _|p,0xffffffff; @p st.relaxed.gpu.global.u32 [%0],1;}" :: "l"(q) : "memory"); }
DEV void tma3(uint32_t dst, const CUtensorMap* m, int c0, int c1, uint32_t bar) {
  asm volatile("{.reg .pred p; elect.sync _|p,0xffffffff;\n"
    "@p cp.async.bulk.tensor.3d.shared::cluster.global.mbarrier::complete_tx::bytes [%0],[%1,{%2,%3,%5}],[%4];}"
    :: "r"(dst), "l"(m), "r"(c0), "r"(c1), "r"(bar), "r"(0) : "memory");
}
DEV void tma5(uint32_t dst, const CUtensorMap* m, int c0, int c4, uint32_t bar) {
  asm volatile("{.reg .pred p; elect.sync _|p,0xffffffff;\n"
    "@p cp.async.bulk.tensor.5d.shared::cluster.global.mbarrier::complete_tx::bytes [%0],[%1,{%2,%5,%5,%5,%3}],[%4];}"
    :: "r"(dst), "l"(m), "r"(c0), "r"(c4), "r"(bar), "r"(0) : "memory");
}
DEV void bulk(uint32_t dst, const void* src, int bytes, uint32_t bar) {
  asm volatile("{.reg .pred p; elect.sync _|p,0xffffffff;\n@p cp.async.bulk.shared::cluster.global.mbarrier::complete_tx::bytes [%0],[%1],%2,[%3];}" :: "r"(dst), "l"(src), "r"(bytes), "r"(bar) : "memory");
}
DEV void bulk_store(void* dst, uint32_t src, int bytes) {
  asm volatile("{.reg .pred p; elect.sync _|p,0xffffffff;\n@p cp.async.bulk.global.shared::cta.bulk_group [%0],[%1],%2;}" :: "l"(dst), "r"(src), "r"(bytes) : "memory");
}
DEV void l2_prefetch(const void* src, int bytes) {
  asm volatile("{.reg .pred p; elect.sync _|p,0xffffffff;\n@p cp.async.bulk.prefetch.L2.global [%0],%1;}" :: "l"(src), "r"(bytes) : "memory");
}

DEV uint64_t mkdesc(uint32_t addr, uint32_t lbo, uint32_t sbo, uint32_t swz) {
  return (uint64_t)((addr >> 4) | ((lbo >> 4) << 16)) | ((uint64_t)((sbo >> 4) | (swz << 30)) << 32);
}
DEV void wg_fence() { asm volatile("wgmma.fence.sync.aligned;" ::: "memory"); }
DEV void wg_commit() { asm volatile("wgmma.commit_group.sync.aligned;" ::: "memory"); }
template <int N> DEV void wg_wait() { asm volatile("wgmma.wait_group.sync.aligned %0;" :: "n"(N) : "memory"); }
template <int N> DEV void zerov(float (&d)[N]) {
#pragma unroll
  for (int i = 0; i < N; ++i) asm volatile("mov.b32 %0,0;" : "=f"(d[i]));
}
template <int N> DEV void undef(float (&d)[N]) {
#pragma unroll
  for (int i = 0; i < N; ++i) asm volatile("" : "=f"(d[i]));
}
#define R4(d, o) "+f"(d[o]), "+f"(d[o + 1]), "+f"(d[o + 2]), "+f"(d[o + 3])
#define R8(d, o) R4(d, o), R4(d, o + 4)
#define R16(d, o) R8(d, o), R8(d, o + 8)
#define R32(d, o) R16(d, o), R16(d, o + 16)
#define L0 "%0,%1,%2,%3,%4,%5,%6,%7,%8,%9,"
#define L10(a) "%" #a "0,%" #a "1,%" #a "2,%" #a "3,%" #a "4,%" #a "5,%" #a "6,%" #a "7,%" #a "8,%" #a "9,"
#define WG_HEAD(pr, n) "{.reg .pred p; setp.ne.s32 p,%" #pr ",0;\nwgmma.mma_async.sync.aligned.m64n" #n "k16.f32.bf16.bf16 {"
DEV void wg_rs64k(float (&d)[32], const uint32_t (&a)[4], uint64_t db, int acc) {
  asm volatile(WG_HEAD(37, 64) L0 L10(1) L10(2) "%30,%31},{%32,%33,%34,%35},%36,p,1,1,0;}"
    : R32(d, 0) : "r"(a[0]), "r"(a[1]), "r"(a[2]), "r"(a[3]), "l"(db), "r"(acc));
}
DEV void wg_rs48t(float (&d)[24], const uint32_t (&a)[4], uint64_t db, int acc) {
  asm volatile(WG_HEAD(29, 48) L0 L10(1) "%20,%21,%22,%23},{%24,%25,%26,%27},%28,p,1,1,1;}"
    : R16(d, 0), R8(d, 16) : "r"(a[0]), "r"(a[1]), "r"(a[2]), "r"(a[3]), "l"(db), "r"(acc));
}
DEV void wg_rs32t(float (&d)[16], const uint32_t (&a)[4], uint64_t db, int acc) {
  asm volatile(WG_HEAD(21, 32) L0 "%10,%11,%12,%13,%14,%15},{%16,%17,%18,%19},%20,p,1,1,1;}"
    : R16(d, 0) : "r"(a[0]), "r"(a[1]), "r"(a[2]), "r"(a[3]), "l"(db), "r"(acc));
}
DEV void wg_ss8(float (&d)[4], uint64_t da, uint64_t db) {
  asm volatile("wgmma.mma_async.sync.aligned.m64n8k16.f32.bf16.bf16 {%0,%1,%2,%3},%4,%5,1,1,1,1,0;" : R4(d, 0) : "l"(da), "l"(db));
}
DEV void wg_ss48(float (&d)[24], uint64_t da, uint64_t db, int acc) {
  asm volatile(WG_HEAD(26, 48) L0 L10(1) "%20,%21,%22,%23},%24,%25,p,1,1,1,1;}" : R16(d, 0), R8(d, 16) : "l"(da), "l"(db), "r"(acc));
}
DEV void wg_ss64(float (&d)[32], uint64_t da, uint64_t db, int acc) {
  asm volatile(WG_HEAD(34, 64) L0 L10(1) L10(2) "%30,%31},%32,%33,p,1,1,0,1;}" : R32(d, 0) : "l"(da), "l"(db), "r"(acc));
}
DEV void wg_ss192(float (&d)[96], uint64_t da, uint64_t db, int acc) {
  asm volatile(WG_HEAD(98, 192) L0 L10(1) L10(2) L10(3) L10(4) L10(5) L10(6) L10(7) L10(8) "%90,%91,%92,%93,%94,%95},%96,%97,p,1,1,1,1;}"
    : R32(d, 0), R32(d, 32), R32(d, 64) : "l"(da), "l"(db), "r"(acc));
}

DEV void wg_rs192t(float (&d)[96], const uint32_t (&a)[4], uint64_t db) {
  asm volatile("wgmma.mma_async.sync.aligned.m64n192k16.f32.bf16.bf16 {" L0 L10(1) L10(2) L10(3) L10(4) L10(5) L10(6) L10(7) L10(8) "%90,%91,%92,%93,%94,%95},{%96,%97,%98,%99},%100,1,1,1,1;"
    : R32(d, 0), R32(d, 32), R32(d, 64) : "r"(a[0]), "r"(a[1]), "r"(a[2]), "r"(a[3]), "l"(db));
}

DEV float ln_sd(float s, float q, float& m) {
  m = s * (1.f / 512.f);
  return bfr(sqrt_(bfr(bfr(fmaxf(q * (1.f / 512.f) - m * m, 0.f)) + 1e-5f)));
}
DEV float4 gram(const uint32_t (&w)[8][2], int g, uint32_t zero) {
  float s[4], q[4][4];
  const uint32_t o0 = 0x3F803F80u | zero, o1 = 0x3F803F80u ^ zero;
#pragma unroll
  for (int j = 0; j < 8; ++j) {
#pragma unroll
    for (int h = 0; h < 2; ++h) { if (j < 2) mma8z(q[2 * j + h], w[j][0], w[j][1], w[j][h]); else mma8(q[2 * (j & 1) + h], w[j][0], w[j][1], w[j][h]); }
    if (j == 1) mma16z(s, w[0][0], w[0][1], w[1][0], w[1][1], o0, o1);
    else if (j & 1) mma16(s, w[j - 1][0], w[j - 1][1], w[j][0], w[j][1], o0, o1);
  }
  const bool od = g & 1;
  return make_float4(s[0], od ? q[0][1] + q[2][1] : q[0][0] + q[2][0], s[2], od ? q[1][3] + q[3][3] : q[1][2] + q[3][2]);
}
DEV void keep(uint32_t v, uint32_t zero) {
  asm volatile("{.reg .pred p; setp.ne.u32 p,%1,0; @p st.shared.u32 [%0],%0;}" :: "r"(v), "r"(zero) : "memory");
}
DEV void keep(const void* v, uint32_t zero) { asm volatile("{.reg .pred p; setp.ne.u32 p,%1,0; @p st.global.u32 [%0],%1;}" :: "l"(v), "r"(zero) : "memory"); }
struct XgAddr { uint32_t a, b; uint4* dst; };
template <bool FRAG> DEV XgAddr xg_addr(uint4* dst, uint32_t stg, int wp, int lane, uint32_t zero) {
  const int t = lane & 3, r = 4 * wp + (lane >> 3);
  XgAddr x = {stg + t * (FRAG ? 256 : 1024) + ((wp ^ t) * 32) + (lane >> 2) * 4,
              stg + r * 128 + (((lane & 7) ^ (2 * (((r >> 1) ^ (r >> 3)) & 3))) * 16), dst + (r * 256 + (lane & 7))};
  keep(x.a, zero); keep(x.b, zero); keep(x.dst, zero);
  return x;
}
template <bool FRAG> DEV void xg_put(const XgAddr& x, const uint32_t (&w)[8][2]) {
#pragma unroll
  for (int n = 0; n < 8; ++n) {
    const uint32_t b = (x.a ^ ((n & 3) * 32)) + (FRAG ? n * 1024 : (n >> 2) * 4096 + (n & 3) * 256);
    sts1(b, prmt(w[n][0], w[n][1], 0x5410)); sts1(b + 128, prmt(w[n][0], w[n][1], 0x7632));
  }
}
DEV void xg_store(const XgAddr& x, uint32_t tag) {
  const uint32_t m = (~x.b >> 4) & 1;
#pragma unroll
  for (int k = 0; k < 4; ++k) {
    const uint4 v = lds4((x.b ^ ((k & 1) * 64)) + k * 2048);
    str4(x.dst + k * 4096, tagged(v.x, m, tag), v.y, v.z, v.w);
  }
}
template <int N, int M> DEV void fold(float (&v)[M], int lane, int bit) {
  const bool b = lane & bit;
#pragma unroll
  for (int k = 0; k < N; ++k) { const float sn = b ? v[k] : v[k + N], kp = b ? v[k + N] : v[k]; v[k] = kp + __shfl_xor_sync(0xffffffffu, sn, bit); }
}
DEV int piece(int n, int cg) { return n ? n - (n <= cg) : cg; }
DEV uint32_t kvslot(int pos) { return (pos & 2 ? SM_XA : SM_S1) + 16384 + (pos & 1) * 4096; }
DEV uint32_t xstage(int q, int e) { return ((q + 1) & 2) ? SM_R + ((q & 2) + e) * 16384 : e ? SM_XB : SM_XA; }
DEV void cmul(float& orr, float& oi, float ar, float ai, float br, float bi) {
  float r = ar * br - ai * bi, i = ar * bi + ai * br; orr = r; oi = i;
}
DEV void cexp_(float al, float bt, float s, float& er, float& ei) {
  float mag = ex2(al * s), ph = bt * s;
  ph -= rintf(ph);
  float ang = ph * 6.283185307179586f;
  er = mag * __cosf(ang); ei = mag * __sinf(ang);
}

#define KS 2048
DEV void put8(uint32_t a, const float (&r)[8], const float (&i)[8]) {
  sts4(a, pack2(r[0], r[1]), pack2(r[2], r[3]), pack2(r[4], r[5]), pack2(r[6], r[7]));
  sts4(a + 1024, pack2(i[0], i[1]), pack2(i[2], i[3]), pack2(i[4], i[5]), pack2(i[6], i[7]));
}
DEV void tables(const uint32_t (&pv)[8], int k4, int w, int lane) {
  PW(4 * k4 + w)
  [[maybe_unused]] const int layer = 0;
  const float dt = bfr(__expf(bflo(pv[6])));
  const float al = dt * bflo(pv[0]) * 1.4426950408889634f, bt = dt * bflo(pv[1]) * 0.15915494309189535f;
  float qr[8], qi[8], yr[8], yi[8];
  cmul(qr[0], qi[0], bflo(pv[4]), bflo(pv[5]), dt * bflo(pv[2]), dt * bflo(pv[3]));
  PROFD(2, a_par, __float_as_uint(qr[0] + al + bt));
  float e1r, e1i, eMr, eMi, eLr, eLi;
  cexp_(al, bt, 1.f, e1r, e1i); cexp_(al, -bt, 8.f, yr[1], yi[1]); cexp_(al, -bt, 64.f, eMr, eMi); cexp_(al, bt, 256.f, eLr, eLi);
  const uint32_t ad = SB + k4 * 32768 + (w & 1) * 512 + lane * 16, am = ad + (w >> 1) * KS, an = ad + (8 + 3 * (w >> 1)) * KS;
  yr[0] = 1.f; yi[0] = 0.f;
#pragma unroll
  for (int k = 1; k < 8; ++k) {
    cmul(qr[k], qi[k], qr[k - 1], qi[k - 1], e1r, e1i);
    if (k > 1) cmul(yr[k], yi[k], yr[k - 1], yi[k - 1], yr[1], yi[1]);
  }
  put8(an, qr, qi);
#pragma unroll
  for (int j = 0; j < 4; ++j) {
    put8(am + j * 2 * KS, yr, yi);
#pragma unroll
    for (int k = 0; k < 8; ++k) {
      if (j == 0 && k == 0) { yr[0] = eMr; yi[0] = eMi; } else if (j < 3) cmul(yr[k], yi[k], yr[k], yi[k], eMr, eMi);
    }
    if (j == 0) {
#pragma unroll
      for (int k = 0; k < 8; ++k) { const int o = k < 4 ? 2 * k : k < 6 ? 2 * k - 8 : k - 2; cmul(qr[k], qi[k], qr[o], qi[o], eLr, eLi); }
      put8(an + KS, qr, qi);
    } else if (j == 1) {
#pragma unroll
      for (int k = 0; k < 5; ++k) cmul(qr[k], qi[k], qr[k ? k - 1 : 6], qi[k ? k - 1 : 6], eLr, eLi);
      put8(an + 2 * KS, qr, qi);
    }
  }
  PROF(3, a_tab);
}

DEV void sts16_if(uint32_t a, uint32_t v, bool c) { asm volatile("{.reg .pred q; .reg .b16 h; setp.ne.u32 q,%2,0; cvt.u16.u32 h,%1; @q st.shared.u16 [%0],h;}" :: "r"(a), "r"(v), "r"((uint32_t)c) : "memory"); }
DEV void sts1_if(uint32_t a, uint32_t v, bool c) { asm volatile("{.reg .pred q; setp.ne.u32 q,%2,0; @q st.shared.u32 [%0],%1;}" :: "r"(a), "r"(v), "r"((uint32_t)c) : "memory"); }
DEV void taps(uint32_t dskip, int k4, int w, int lane) {
  PW(4 * k4 + w)
  [[maybe_unused]] const int layer = 0;
  fence_async_smem();
  bar_sync(k4 > 1 ? NB_WG + k4 : NB_Q, k4 > 1 ? 128 : 416);
  float d[24];
  undef(d);
  const uint64_t da = mkdesc(SB + k4 * 32768, 1024, KS, 0);
  wg_fence();
#pragma unroll
  for (int j = 0; j < 8; ++j) wg_ss48(d, da + j * 8, da + KS / 2 + j * 8, j);
  wg_commit();
  const int b = 8 * w + (lane >> 2), t = lane & 3, id = 32 * w + lane;
  constexpr int DO = T_O - T_E;
  const uint32_t te = SM_TAP + k4 * TAP_SZ + T_E, a0 = te - 16 * b - 4 * t;
  const uint32_t a1 = a0 - 512 - 4 * t, a2 = te - 2 * (511 + b) - 64 * t, a3 = te + (T_C - T_E) - 2 * (127 + b) - 128 * t;
  wg_wait<0>();
  PROF(4, a_mma);
  {
    const uint32_t v = pack2(d[1] + d[15], d[0] + d[14] + (id ? 0.f : bflo(dskip)));
    sts1(a0 + DO - 2, v); sts16(a0 - 2, v); sts16(a0, v >> 16);
  }
  {
    const uint32_t v = pack2(d[5] + d[19], d[4] + d[18]), u = prmt(v, v, 0x3232);
    const bool lo = t < 2, k512 = id == 2;
    sts1_if(k512 ? te - 2 * 512 : a1, u, (lo && id) || k512);
    sts1_if(k512 ? te - 2 * 514 : a1 - 4, k512 ? u : v, lo || k512);
    sts1_if(k512 ? te + DO - 2 * 513 : a1 + DO - 2, u, lo || k512);
    sts16(lo ? a1 + DO - 4 : a2 + DO - 194, v);
    sts16(lo ? (id ? a1 + DO + 2 : a1) : k512 ? te + DO - 2 * 511 : a2 + DO, u);
    sts16_if(a2 - 194, v, !lo);
    sts16_if(k512 ? te + DO - 2 * 514 : a2, u, !lo);
  }
  {
    const uint32_t v = pack2(d[8] + d[22], d[9] + d[23]);
    sts16_if(id ? a3 : te - 2 * 639, v, t < 2 || id == 2);
    sts16_if(a3 - 64, v >> 16, t < 2);
    sts16_if(te + DO - 2 * 639, v, id == 0);
  }
  bar_sync(NB_WG + k4, 128);
  mbar_arrive1_if(B_K, w == 0);
}

DEV uint32_t cpy(uint32_t v, uint32_t id) {
  uint32_t d; asm volatile("prmt.b32 %0,%1,%1,%2;" : "=r"(d) : "r"(v), "r"(id)); return d;
}
DEV uint32_t uoff(int s) { return (s ^ ((s >> 3) & 3)) * 16; }
template <bool FULL> DEV void boxes(const uint32_t (&u)[10], uint32_t a, uint32_t a9, uint32_t a7, uint32_t (&pv)[4]) {
  uint32_t v[8], p[8], x[4], y[4];
#pragma unroll
  for (int j = 0; j < 8; ++j) { v[j] = prmt(u[j], u[j + 1], 0x5432); p[j] = hadd2(u[j], v[j]); }
#pragma unroll
  for (int j = 0; j < 4; ++j) { x[j] = hadd2(hadd2(p[j + 1], p[j + 2]), u[j + 3]); y[j] = hadd2(v[j + 3], p[j + 4]); }
  sts4(a + R_A5, x[0], x[1], x[2], x[3]);
  sts4(a + R_A3, y[0], y[1], y[2], y[3]);
  if (FULL) {
#pragma unroll
    for (int j = 0; j < 4; ++j) { x[j] = hadd2(x[j], hadd2(v[j], v[j + 3])); y[j] = hadd2(x[j], hadd2(u[j], u[j + 4])); pv[j] = p[j + 4]; }
    sts4(a7, x[0], x[1], x[2], x[3]);
    sts4(a9, y[0], y[1], y[2], y[3]);
  }
}
DEV uint32_t shfl_up(uint32_t v, int d) { uint32_t r; asm volatile("shfl.sync.up.b32 %0,%1,%2,0,0xffffffff;" : "=r"(r) : "r"(v), "r"(d) : "memory"); return r; }
DEV void halo(uint32_t (&u)[10], uint32_t a, uint32_t b, int lane) {
  asm volatile("{.reg .pred p,q; setp.eq.s32 p,%8,0; setp.lt.s32 q,%8,2;\n@p ld.shared.v4.u32 {%2,%3,%4,%5},[%6];\n@q ld.shared.v2.u32 {%0,%1},[%7];}"
    : "+r"(u[0]), "+r"(u[1]), "+r"(u[2]), "+r"(u[3]), "+r"(u[4]), "+r"(u[5]) : "r"(a), "r"(b), "r"(lane));
}
#define W1 4
#define ROT 2
#define G1 -1
#define G2 1
#define G3 8
#define TPS 0x7134
#define GMASK ((G1 >= 0 ? 2 : 0) | (G2 >= 0 ? 4 : 0) | (G3 >= 0 ? 8 : 0))
#define GATE1(g, n, p) if (g >= 0 && (g & 3) == p) mbar_arrive1_if(B_G + 8 * n, k4 == (g >> 2));
#define GATE(p) GATE1(G1, 0, p) GATE1(G2, 1, p) GATE1(G3, 2, p)
#define TMASK(p) (((TPS & 15) == p) | ((((TPS >> 4) & 15) == p) << 1) | ((((TPS >> 8) & 15) == p) << 2) | ((((TPS >> 12) & 15) == p) << 3))
#define TURN(p) if (TMASK(p) == 15) bar_arrive(NB_T + 1 + k4, 256); else if (TMASK(p)) { if ((TMASK(p) >> k4) & 1) bar_arrive(NB_T + 1 + k4, 256); }
DEV void w_load(const CUtensorMap* mW, int cg, int h) {
  mbar_expect1(B_W + 8 * h, 24576);
  tma3(SM_S0 + (h & 3) * 24576, mW, 64 * cg, 64 * h, B_W + 8 * h);
}

DEV void conv(const Params& P, const CUtensorMap* mW, int c, int k4, int w, int layer) {
  const uint32_t zero = P.zero;
  PW(4 * k4 + w)
  int lane = lane_here(zero);
  const int g = lane >> 2, t = lane & 3, v = w ^ (ROT * (k4 & 1)), tid = 32 * v + lane;
  const uint32_t reg = SM_R + k4 * 16384, tp = SM_TAP + k4 * TAP_SZ;
  const uint32_t g0 = tp + ((g & 1) ? T_O : T_E) + 2 * (2 * t - g);
  uint32_t F[18][4], U[20], qc[4][4];
#define LO(q, a) q[0] = lds1(a); q[2] = lds1(a + 16);
#define HI(q, a) q[1] = lds1(a - 128); q[3] = lds1(a - 112);
  {
    const uint32_t ga = g0 - 32 * (w & 1) - 576 * (w >> 1), g2 = tp + T_C - 258 - 32 * w + 4 * (t - g);
    F[0][2] = lds1(ga + 48);
#pragma unroll
    for (int j = 0; j < 8; ++j) { F[j][0] = lds1(ga + 32 - 32 * j); F[j][1] = lds1(ga + 16 - 32 * j); }
#pragma unroll
    for (int j = 0; j < 20; ++j) U[j] = lds1(ga - 224 - 16 * j);
#pragma unroll
    for (int j = 0; j < 4; ++j) { LO(qc[j], g2 + 32 * j) HI(qc[j], g2 + 32 * j) }
  }
  if (layer) { mbar_wait(B_ED, 0); mbar_wait(B_ED + 8, 0); }
  sts4z_if(reg + lane * 16 + (w ? w * 3584 + 1024 : 0), w < 3);
  PROF(5, a_pre);
  if (k4 == 3 && w == 3) {
    mbar_wait(B_E, layer);
    mbar_wait(B_K, 0);
#pragma unroll
    for (int h = 0; h < 4; ++h) w_load(mW, c & 7, h);
  }
  const uint32_t bo = reg + R_B + tid * 16 + (v >> 1) * 1056, be = tid == 127 ? reg + R_B + 1024 : bo + (tid == 63 ? 2112 : 1056);
  const uint32_t a9 = (lane & 1) ? be : bo, a7 = (lane & 1) ? bo : be, ua = reg + R_U + uoff(tid);
  const uint32_t h1 = reg + R_U + v * 512 - 64, h2 = h1 + 24 - 16 * lane;
  keep(a9 & a7 & ua & h2, zero);
  mbar_wait(k4 && ((GMASK >> k4) & 1) ? B_G - 8 + 8 * k4 : B_E, layer);
  PROF(6, a_x);
  uint4 x[2];
  uint32_t pv[4];
  {
    uint4 s[4];
    uint32_t u[2][10];
#pragma unroll
    for (int z = 0; z < 2; ++z) { x[z] = lds4(reg + R_B + tid * 16 + z * 2048); s[2 * z] = lds4(SM_RES + tid * 16 + z * 2048); s[2 * z + 1] = lds4(SM_RES + tid * 16 + z * 2048 + 4096); }
    for (int it = 0;; ++it) {
      const uint32_t m = min(min(min((both(x[0].x, x[1].x, layer) | lane) & 1, min(s[0].x, s[0].z)), min(s[1].x, s[1].z)), min(min(s[2].x, s[2].z), min(s[3].x, s[3].z)));
      if (__builtin_expect(__all_sync(0xffffffffu, m != 0u), 1)) break;
      EVENT(16 + layer * 4 + k4);
      const int o = tid | here(zero);
#pragma unroll
      for (int z = 0; z < 2; ++z) x[z] = ldr4(&P.S->XG[(128 * k4 + c) * 256 + o] + z * 128);
#pragma unroll
      for (int z = 0; z < 4; ++z) {
        s[z] = ldr4(&P.S->SR[layer][c >> 4][o] + ((z >> 1) * 128 + (z & 1) * 256));
        sts4(SM_RES + tid * 16 + (z >> 1) * 2048 + (z & 1) * 4096, s[z].x, s[z].y, s[z].z, s[z].w);
      }
      spin_guard(it);
    }
#pragma unroll
    for (int z = 0; z < 2; ++z) {
      u[z][6] = hmul2(hsub2(x[z].x, s[2 * z].y), s[2 * z].x); u[z][7] = hmul2(hsub2(x[z].y, s[2 * z].w), s[2 * z].z);
      u[z][8] = hmul2(hsub2(x[z].z, s[2 * z + 1].y), s[2 * z + 1].x); u[z][9] = hmul2(hsub2(x[z].w, s[2 * z + 1].w), s[2 * z + 1].z);
      sts4(ua + z * 2048, u[z][6], u[z][7], u[z][8], u[z][9]);
    }
    u[1][0] = 0; u[1][1] = s[3].x; u[1][2] = s[2].x; u[1][3] = s[2].y; u[1][4] = s[2].z; u[1][5] = s[2].w;
    if (v < 2) {
#pragma unroll
      for (int j = 1; j < 6; ++j) u[1][j] = shfl_up(u[1][j < 2 ? 8 + j : 4 + j], j < 2 ? 2 : 1);
    }
#pragma unroll
    for (int j = 0; j < 6; ++j) u[0][j] = shfl_up(u[0][j < 2 ? 8 + j : 4 + j], j < 2 ? 2 : 1);
    bar_sync(NB_WG + k4, 128);
    GATE(0)
    PROF(7, a_u);
    halo(u[0], h1, h2, lane);
    halo(u[1], h1 + 2048, h2 + 2048, lane + 16 * (v & 2));
    sts4z_if(reg + R_B + 1040, tid == 0);
    boxes<true>(u[0], reg + tid * 16, a9, a7, pv);
    if (v < 2) boxes<false>(u[1], reg + tid * 16 + 2048, 0, 0, pv);
  }
  GATE(1)
  fence_async_smem();
  if (k4 == 3 && w == 0) {
    const uint32_t src = SM_RES + 8192;
#pragma unroll
    for (int z = 0; z < 4; ++z) sts4(src + lane * 16 + z * 512, 0, 0, 0, 0);
    fence_async_smem();
    __syncwarp();
#pragma unroll
    for (int z = 0; z < 2; ++z) {
      bulk_store(&P.S->H[(c + 8) * 256] + z * 128, src, 2048);
      bulk_store(P.S->F + ((c >> 3) * 64 + 4 * (c & 7)) + z * 32, src, 16);
    }
    bulk_store(&P.S->PS[c * 64], src, 1024);
    bulk_store(&P.S->ST[c * 4], src, 64);
    if (c < 8 && layer) bulk_store(&P.S->CS[c * 48], src, 768);
    if (c < 5) bulk_store(P.S->C + (c + 5 - 5 * layer) * 1024, src, 128 * NCOPY * NSUB);
    asm volatile("cp.async.bulk.commit_group;" ::: "memory");
  }
  const uint32_t id = opq(0x3210u);
#pragma unroll
  for (int j = 0; j < 8; ++j) { F[j][3] = cpy(F[j][0], id); if (j) F[j][2] = cpy(F[j - 1][1], id); }
  PROF(8, a_box);
  bar_sync(NB_T + k4, k4 ? 256 : 128);
  PROF(9, a_turn);
  float acc[32], f1[24], f3[16];
  uint32_t qa[4][4], qb[4][4], fp[4];
  const uint64_t db = mkdesc(reg + R_U, 16, 512, 2) + 2;
#define STEP(mm, n) wg_fence(); mm; wg_commit(); wg_wait<n>();
#define D(j, n) STEP(wg_rs64k(acc, F[j], db - 2 * j, j), n)
#define C(j, n) STEP(wg_rs32t(f3, qc[j], mkdesc(reg + R_B, 128, 1040, 0) + 16 * j, j), n)
#define NIL(q, y) { const uint32_t z = y & zero; q[2][1] = cpy(z, 0); q[2][3] = cpy(z, 1); q[3][1] = cpy(z, 2); q[3][3] = cpy(z, 3); }
#define X(j) F[j][0] = cpy(U[2 * j - 16], ix); F[j][1] = cpy(U[2 * j - 15], ix); F[j][3] = cpy(F[j][0], ix); F[j][2] = cpy(F[j - 1][1], ix);
  const uint32_t g1 = g0 - 2 * 576 - 16 * w;
  const uint64_t d1 = mkdesc(reg + R_A5, 128, 512, 0);
  constexpr int O3 = (R_A3 - R_A5) / 16;
  uint32_t ix = id;
  undef(acc);
  D(0, 4) TURN(0) D(1, 4) D(2, 4) D(3, 4) D(4, 4) D(5, 2)
  undef(f3);
  C(0, 3) C(1, 3) TURN(1) C(2, 3) X(8) C(3, W1) X(9) LO(qa[0], g1)
  D(6, W1) HI(qa[0], g1) X(10) D(7, W1) LO(qa[1], g1 + 32) X(11) D(8, W1) HI(qa[1], g1 + 32) D(9, 4) LO(qa[2], g1 - 64)
  fp[0] = pack2(f3[0], f3[1]); fp[1] = pack2(f3[4], f3[5]); fp[2] = pack2(f3[8] + f3[2], f3[9] + f3[3]); fp[3] = pack2(f3[12] + f3[6], f3[13] + f3[7]);
  ix |= fp[0] & fp[1] & fp[2] & fp[3] & zero;
  X(12) D(10, 4) TURN(2) LO(qa[3], g1 - 32) X(13) X(14) D(11, 4) LO(qb[0], g1 - 192) X(15) D(12, 4) HI(qb[0], g1 - 192) X(16)
  D(13, 4) LO(qb[1], g1 - 160) X(17) D(14, 4) TURN(3) HI(qb[1], g1 - 160) NIL(qa, qa[1][0])
  D(15, 4) LO(qb[2], g1 - 256) D(16, 3) LO(qb[3], g1 - 224) NIL(qb, qa[1][1]) D(17, 2) TURN(4)
  PROF(10, a_den);
  undef(f1);
  wg_fence();
#pragma unroll
  for (int j = 0; j < 4; ++j) wg_rs48t(f1, qa[j], d1 + 16 * (j & 1) - 32 * (j >> 1), j);
  wg_commit();
  wg_wait<1>();
  TURN(5)
  wg_fence();
#pragma unroll
  for (int j = 0; j < 4; ++j) wg_rs48t(f1, qb[j], d1 + O3 + 16 * (j & 1) - 32 * (j >> 1), 1);
  wg_commit();
  TURN(6)
  lane = lane_here(zero);
  bar_sync(NB_WG + k4, 128);
  {
    const int p = (lane + 9 * (w >> 1)) & 31;
    const uint32_t ya = reg + ((w >> 1) ? R_B : R_U) + p * 64 + (((2 * (w & 1)) ^ ((p >> 1) & 3)) * 16), up = p < lane ? 2048 : 0;
#pragma unroll
    for (int z = 0; z < 4; ++z) {
      const float* a = acc + 16 * (z >> 1) + 2 * (z & 1);
      stsm4t((ya + (up ^ ((z >> 1) * 2048))) ^ ((z & 1) * 16), pack2(a[0], a[1]), pack2(a[4], a[5]), pack2(a[8], a[9]), pack2(a[12], a[13]));
    }
  }
  asm volatile("cp.async.bulk.wait_group 0;" ::: "memory");
  const uint32_t fa = reg + R_A5 + (lane >> 3) * 512 + w * 128 + (lane & 7) * 16;
  const uint32_t fc = reg + R_A3 + uoff(64 * (lane >> 4) + 16 * w + 2 * (lane & 7) + 1 - ((lane >> 3) & 1));
  uint32_t k1024 = lds16(tp + T_E - 2 * 639 + (fa & fc & zero));
  wg_wait<0>();
  GATE(2)
  PROF(11, a_far);
  bar_sync(NB_WG + k4, 128);
  stsm4(fc, fp[0], fp[1], fp[2], fp[3]);
  stsm4(fa, pack2(f1[0], f1[1]), pack2(f1[4], f1[5]), pack2(f1[8] + f1[2], f1[9] + f1[3]), pack2(f1[12] + f1[6], f1[13] + f1[7]));
  stsm2(fa + 2048, pack2(f1[16] + f1[10], f1[17] + f1[11]), pack2(f1[20] + f1[14], f1[21] + f1[15]));
  {
    const int o = 32 * v + lane;
    const uint32_t a = reg + uoff(o), b = reg + R_A5 + o * 16;
    uint4 y[2] = {hadd8(lds4(a + R_U), lds4(o >= 36 ? a + R_B : reg)), hadd8(lds4(a + R_U + 2048), lds4(a + R_B + 2048))};
    bar_sync(NB_WG + k4, 128);
    TURN(7)
    PROF(12, a_sts);
    const uint4 f = lds4(v >= 2 ? b - 1024 : reg), f2 = lds4(b + 1024);
    uint4 h = lds4(a + R_A3);
    const int e0 = (o >> 3) * 8192 + (128 * k4 + c) * 16 + (((o & 4) + ((o >> 1) & 1)) ^ (c & 7)) * 2 + (o & 1);
    const uint32_t me = (e0 & 3) == ((c >> 1) & 3), m0 = me & ~c, m1 = me & c, tag = 1 - layer;
    uint32_t* cp = cnt_at(P, 1 + 5 * layer + k4, c, lane);
    keep(cp, zero);
    k1024 = prmt(k1024, k1024, 0x1010);
    h = make_uint4(hfma2(pv[0], k1024, h.x), hfma2(pv[1], k1024, h.y), hfma2(pv[2], k1024, h.z), hfma2(pv[3], k1024, h.w));
    y[0] = hadd8(y[0], f); y[1] = hadd8(y[1], hadd8(f2, h));
    cnt_add(cp, 1 | (y[0].x & y[1].x & zero), (o ^ 96) < NCOPY);
#pragma unroll
    for (int z = 0; z < 2; ++z) {
      const uint4 r = hadd8(x[z], y[z]);
      str2((uint2*)P.S->XF + e0 + z * 131072, tagged(prmt(r.x, r.y, 0x5410), m0, tag), tagged(prmt(r.z, r.w, 0x5410), m1, tag));
      str2((uint2*)P.S->XF + (e0 ^ 4) + z * 131072, tagged(prmt(r.x, r.y, 0x7632), m0, tag), tagged(prmt(r.z, r.w, 0x7632), m1, tag));
    }
  }
  TURN(9)
  GATE(3)
  PROF(13, a_out);
}

#define FH 1
#define QPIN 1
#define XORD 1
DEV void x_load(const Params& P, int c, int q, int layer) {
#pragma unroll
  for (int z = 0; z < 2; ++z) {
    const int e = z ^ (XORD && q == 3 && !(c & 4));
    mbar_expect1(B_X + 16 * q + 8 * e, 16384);
    bulk(xstage(q, e), P.S->XF + ((2 * (c >> 3) + 1 - e) * 4096 + q * 1024), 16384, B_X + 16 * q + 8 * e);
  }
}

DEV void means(uint32_t (&m)[4], int row, int lane, int layer, uint32_t zero) {
  mbar_wait(B_CS, 0);
  mbar_wait(B_ST, layer);
  const uint32_t a = SM_MISC + row * 4 + (lane & 28), k = (lane & 3) ? 0u : ~0u;
  m[0] = lds1(a) & k; m[1] = lds1(a + 32) & k; m[2] = m[0] & zero; m[3] = m[1] & zero;
}

DEV void attn_phase(const Params& P, int c, int e, int w, int lane, int layer) {
  PW(4 * e + w)
  const int cg = c & 7, J = 2 * (c >> 3) + 1 - e;
  float acc[96];
  zerov(acc);
  uint32_t m[4] = {0, 0, 0, 0};
#pragma unroll 1
  for (int q = 0;; ++q) {
    const uint64_t da = mkdesc(xstage(q, e), 16, 1024, 1), db = mkdesc(SM_S0 + (q & 1) * 49152, 8192, 1024, 1);
    const uint32_t wr = mbar_test2(B_W + 16 * q, layer), xa = xstage(q, e) + w * 4096 + lane * 132;
    mbar_wait(B_X + 16 * q + 8 * e, layer);
    for (int it = 0;; ++it) {
      const uint32_t ok = both(lds1(xa), lds1(xa ^ 32), layer) & both(lds1(xa ^ 64), lds1(xa ^ 96), layer);
      if (__all_sync(0xffffffffu, ok & 1)) break;
      EVENT(8 * layer + 2 * q + e);
#pragma unroll 1
      for (int j = 0; j < 8; ++j) cp16(xstage(q, e) + w * 4096 + j * 512 + lane * 16, P.S->XF + (J * 4096 + q * 1024 + w * 256 + j * 32 + lane));
      asm volatile("cp.async.wait_all;" ::: "memory");
      fence_async_smem();
      __syncwarp();
      spin_guard(it);
    }
    bool all = __all_sync(0xffffffffu, wr);
    if (q == 0 && e && w == 0) {
      bar_sync(NB_H, 256);
      cnt_wait(P, 2 + 5 * layer, c, lane);
      x_load(P, c, 1, layer);
      PROF(27, m_xi);
    }
    if (q == 3 && e) means(m, 16 * w, lane, layer, P.zero);
    if (!all) { mbar_wait(B_W + 16 * q, layer); all = mbar_test(B_W + 16 * q + 8, layer); }
    bar_sync(e ? NB_Q : q ? NB_T : NB_T + 4, 256);
    PROF(14 + q, m_q);
    wg_fence();
#pragma unroll
    for (int k = 0; k < 8; ++k) {
      if (k == 4) { wg_commit(); if (!all) mbar_wait(B_W + 16 * q + 8, layer); wg_fence(); }
      wg_ss192(acc, da + k * 128, db + (k >> 2) * 1536 + (k & 3) * 128, 1);
    }
    wg_commit();
    if (q == 3) break;
    bar_arrive(e ? NB_T : NB_Q, 256);
    if (FH) { wg_wait<1>(); mbar_arrive1_if(B_FH + 8 * q, e && q < 2); }
    wg_wait<0>();
    mbar_arrive1(B_F + 8 * q);
  }
  const int pos = 2 - 2 * e + (w >> 1);
  uint4* h = P.S->H + ((c + 8) * 256 + (w & 1) * 128 + lane);
  const uint32_t kw = kvslot(pos + 1) + (w & 1) * 2048 + lane * 16;
  {
    if (!e) means(m, 64 + 16 * w, lane, layer, P.zero);
    PROF(28, m_sub);
    wg_fence();
    wg_rs192t(acc, m, mkdesc(SM_CS, 0, 32, 0));
    wg_commit();
    bar_arrive_if(NB_Q, 256, !e);
    keep(h, kw & P.zero);
    mbar_wait(B_F + 16, layer);
    wg_wait<0>();
    mbar_arrive1(B_F + 24);
  }
  PROF(18, m_qkv);
  uint32_t Q[4][4], K[4][3][2], V[4][3][2];
  uint32_t pin = P.zero;
#pragma unroll
  for (int z = 0; z < 4; ++z) {
    V[z][1][0] = pack2(acc[64 + 8 * z], acc[65 + 8 * z]); V[z][1][1] = pack2(acc[68 + 8 * z], acc[69 + 8 * z]);
    K[z][1][0] = pack2(acc[32 + 8 * z], acc[33 + 8 * z]); K[z][1][1] = pack2(acc[36 + 8 * z], acc[37 + 8 * z]);
    pin &= V[z][1][0] & V[z][1][1];
    K[z][2][0] = nz(pack2(acc[34 + 8 * z], acc[35 + 8 * z])); K[z][2][1] = pack2(acc[38 + 8 * z], acc[39 + 8 * z]);
    V[z][2][0] = pack2(acc[66 + 8 * z], acc[67 + 8 * z]); V[z][2][1] = pack2(acc[70 + 8 * z], acc[71 + 8 * z]);
    str4_if(h + z * 32, K[z][2][0], K[z][2][1], V[z][2][0], V[z][2][1], pos == 3);
  }
#pragma unroll
  for (int z = 0; z < 8; ++z) V[z >> 1][2][z & 1] = movm(z < 7 ? V[z >> 1][2][z & 1] : V[3][2][1] | pin);
  if (pos == 0) mbar_wait(B_F + 24, layer);
#pragma unroll
  for (int z = 0; z < 4; ++z) sts4_if(kw + z * 512, K[z][2][0], K[z][2][1], V[z][2][0], V[z][2][1], pos < 3);
  bar_arrive(NB_H + pos + 1, 128);
  PROF(19, m_kv);
  lane |= here(P.zero);
  int g = lane >> 2, t = lane & 3;
  const uint32_t ra = SM_STAT + 256 + (32 - 32 * e + 8 * w) * 16, ob = e ? SM_S1 : SM_XA;
  const float r0 = lds1f(ra + (g >> 1) * 16 + (g & 1) * 4), r1 = lds1f(ra + 64 + (g >> 1) * 16 + (g & 1) * 4);
  const uint4 k1 = lds4(ra + 16 * t), k2 = lds4(ra + 64 + 16 * t);
#pragma unroll
  for (int z = 0; z < 8; ++z) {
    V[z >> 1][1][z & 1] = movm(V[z >> 1][1][z & 1]);
    Q[z >> 1][2 * (z & 1)] = pack2(acc[4 * z], acc[4 * z + 1]);
    Q[z >> 1][2 * (z & 1) + 1] = pack2(acc[4 * z + 2], acc[4 * z + 3]);
    pin &= Q[z >> 1][2 * (z & 1)] & Q[z >> 1][2 * (z & 1) + 1];
  }
  {
    const bool p0 = 2 * t > g, p1 = 2 * t + 1 > g, first = c < 8 && pos == 0;
    const uint32_t M = (p0 ? 0xFFFFu : 0u) | (p1 ? 0xFFFF0000u : 0u);
    const float sc0 = r0 * (0.25f * 1.4426950408889634f), sc1 = r1 * (0.25f * 1.4426950408889634f);
    const float sk2 = __uint_as_float(p0 ? k1.x : k2.x) * sc1, sk3 = __uint_as_float(p1 ? k1.y : k2.y) * sc1;
    const int oo = (2 * (w & 2) + (w & 1)) * 64 + (lane ^ (g >> 1));
    uint4* O = P.S->O + (J * 4096 + cg * 512 + oo);
    keep(oo, pin & M & __float_as_uint(sk2) & __float_as_uint(sk3) & __float_as_uint(sc0));
    mbar_wait(B_F + 24, layer);
    float L[4][4];
#pragma unroll
    for (int z = 0; z < 4; ++z) {
      float S[4];
      mma16z(L[z], Q[z][0], Q[z][1], Q[z][2], Q[z][3], K[z][1][0], K[z][1][1]);
      mma16z(S, Q[z][0], Q[z][1], Q[z][2], Q[z][3], K[z][2][0], K[z][2][1]);
      L[z][2] = (p0 ? L[z][2] : S[2]) * sk2; L[z][3] = (p1 ? L[z][3] : S[3]) * sk3;
      if (QPIN) pin &= __float_as_uint(L[z][2]) & __float_as_uint(L[z][3]);
    }
    bar_sync(NB_H + pos + pin, pos ? 128 : 160);
    const uint4 k0 = lds4(ra - 192 + 16 * t);
#pragma unroll
    for (int z = 0; z < 4; ++z) {
      const uint4 hv = lds4(kvslot(pos) + (w & 1) * 2048 + lane * 16 + z * 512);
      K[z][0][0] = hv.x; K[z][0][1] = hv.y; V[z][0][0] = hv.z; V[z][0][1] = hv.w;
    }
    PROF(20, m_halo);
    const float sk0 = __uint_as_float(p0 ? k0.x : k1.x) * sc0, sk1 = __uint_as_float(p1 ? k0.y : k1.y) * sc0;
    const uint32_t rm[4] = {k0.z & M, k1.z & ~M, k1.z & M, k2.z & ~M}, s0 = k0.w | P.zero, s1 = k1.w | P.zero;
    uint4 ov[4];
#pragma unroll
    for (int h2 = 0; h2 < 2; ++h2) {
      uint32_t A[2], B[2], mx[2];
#pragma unroll
      for (int z = 0; z < 2; ++z) {
        const int h = 2 * h2 + z;
        float S[4];
        mma16z(S, Q[h][0], Q[h][1], Q[h][2], Q[h][3], K[h][0][0], K[h][0][1]);
        if (first) { S[0] = __uint_as_float(0xFF800000u); S[1] = S[0]; }
        A[z] = pack2((p0 ? S[0] : L[h][0]) * sk0, L[h][2]);
        B[z] = pack2((p1 ? S[1] : L[h][1]) * sk1, L[h][3]);
      }
#pragma unroll
      for (int z = 0; z < 2; ++z) mx[z] = hmax2(A[z], B[z]);
#pragma unroll
      for (int z = 0; z < 2; ++z) mx[z] = hmax2(mx[z], __shfl_xor_sync(0xffffffffu, mx[z], 1));
#pragma unroll
      for (int z = 0; z < 2; ++z) mx[z] = hmax2(mx[z], __shfl_xor_sync(0xffffffffu, mx[z], 2));
      float Oa[2][3][4];
#pragma unroll
      for (int z = 0; z < 2; ++z) {
        const int h = 2 * h2 + z;
        const uint32_t a = hsub2(A[z], mx[z]), b = hsub2(B[z], mx[z]);
        const uint32_t w0 = pack2(ex2(bflo(a)), ex2(bflo(b))), w1 = pack2(ex2(bfhi(a)), ex2(bfhi(b)));
        const uint32_t u0 = hmul2(w0, rm[0]), u1 = hmul2(w0, rm[1]), u2 = hmul2(w1, rm[2]), u3 = hmul2(w1, rm[3]);
        const uint32_t z0 = w0 & P.zero, z1 = w1 & P.zero;
        mma16z(Oa[z][2], u0, z0, u1, u2, s0, s1);
#pragma unroll
        for (int d = 0; d < 2; ++d) mma16z(Oa[z][d], u0, z0, u1, u2, V[h][0][d], V[h][1][d]);
        mma8(Oa[z][2], z1, u3, k2.w);
#pragma unroll
        for (int d = 0; d < 2; ++d) mma8(Oa[z][d], z1, u3, V[h][2][d]);
      }
#pragma unroll
      for (int r = 0; r < 4; r += 2) {
        const float i0 = rcp(Oa[0][2][r]), i1 = rcp(Oa[1][2][r]);
        const uint32_t o0 = pack2(Oa[0][0][r] * i0, Oa[0][0][r + 1] * i0), o1 = pack2(Oa[0][1][r] * i0, Oa[0][1][r + 1] * i0);
        const uint32_t o2 = pack2(Oa[1][0][r] * i1, Oa[1][0][r + 1] * i1), o3 = pack2(Oa[1][1][r] * i1, Oa[1][1][r + 1] * i1);
        str4(O + h2 * 32 + r * 64, o0, o1, o2, o3);
        ov[h2 + r] = make_uint4(o0, o1, o2, o3);
      }
    }
    bar_arrive(NB_T + 1 + e, 160);
#pragma unroll
    for (int z = 0; z < 4; ++z) sts4(ob + oo * 16 + (z & 1) * 512 + (z & 2) * 1024, ov[z].x, ov[z].y, ov[z].z, ov[z].w);
  }
  fence_async_smem();
  PROF(21, m_att);
  lane = lane_here(P.zero); g = lane >> 2; t = lane & 3;
  uint32_t res[8][2];
  mbar_wait(B_RES, layer);
  mbar_wait(B_WO, layer);
  {
    const uint32_t a = SM_RES + e * 8192 + (lane >> 4) * 1024 + (lane & 7) * 128 + (((2 * (w & 2) + ((lane >> 2) & 2) + (w & 1)) ^ (lane & 7)) * 16);
#pragma unroll
    for (int j = 0; j < 8; j += 2) ldsm4t(res[j][0], res[j][1], res[j + 1][0], res[j + 1][1], a + j * 1024);
  }
  PROF(26, m_res);
  XgAddr xa = xg_addr<true>(P.S->XG + (64 * cg * 256 + 8 * J), ob, w, lane, P.zero);
  uint4* ps = &P.S->PS[((4 * J + w) * 8 + cg) * 8 + g];
  keep(ps, P.zero);
  if (layer) {
    xa.a = ob + w * 2048 + (lane & 15) * 128 + (((lane >> 4) ^ (lane & 7)) * 16);
    xa.b = ob + w * 2048 + (lane >> 3) * 128 + (((lane & 7) ^ (lane >> 3)) * 16);
    xa.dst = (uint4*)P.out + ((64 * J + 16 * w + 2 * (lane >> 3)) * 64 + 8 * cg + (lane & 7));
  }
  uint32_t y[8][2];
#pragma unroll 1
  for (int it = 0;; ++it) {
    float ac[32];
#pragma unroll
    for (int j = 0; j < 16; ++j) {
      asm volatile("shl.b32 %0,%1,16;" : "=f"(ac[2 * j]) : "r"(res[j >> 1][j & 1]));
      asm volatile("and.b32 %0,%1,0xFFFF0000;" : "=f"(ac[2 * j + 1]) : "r"(res[j >> 1][j & 1]));
    }
    const uint64_t da = mkdesc(ob, 16, 1024, 2), db = mkdesc(SM_R, 16, 1024, 1);
    wg_fence();
    bar_sync_if(NB_T, 256, it == 0);
#pragma unroll 1
    for (int n = 0; n < 8; ++n) {
      mbar_wait(B_O + 64 * e + 8 * n, layer);
      if (n == 1) PROF(22, m_o1);
      if (n == 7) PROF(23, m_o7);
      wg_fence();
#pragma unroll
      for (int k = 0; k < 4; ++k) wg_ss64(ac, da + n * 512 + (k >> 1) * 32 + (k & 1) * 2, db + n * 512 + k * 128, 1);
      wg_commit();
    }
    wg_wait<0>();
    const bool bad = ac[0] != ac[0] || ac[2] != ac[2];
#pragma unroll
    for (int j = 0; j < 8; ++j) {
      y[j][0] = pack2(ac[4 * j], ac[4 * j + 1]); y[j][1] = pack2(ac[4 * j + 2], ac[4 * j + 3]);
    }
    if (!bar_any(NB_WG + e, 128, bad) || it == 16) break;
    EVENT(24 + 2 * layer + e);
#pragma unroll 1
    for (int n = 0; n < 8; ++n) {
      if (w == 0) { mbar_expect1(B_R + 8 * e, 8192); bulk(ob + n * 8192, P.S->O + (J * 4096 + piece(n, cg) * 512), 8192, B_R + 8 * e); }
      mbar_wait(B_R + 8 * e, n & 1);
      bar_sync(NB_WG + e, 128);
    }
  }
  PROF(24, m_wo);
  if (layer == 0) {
    const float4 s = gram(y, g, P.zero);
    xg_put<true>(xa, y);
    str4_if(ps, nz(__float_as_uint(s.x)), __float_as_uint(s.y), __float_as_uint(s.z), __float_as_uint(s.w), t == (g >> 1));
    mbar_arrive1(B_ED + 8 * e);
    bar_sync(NB_WG + e, 128);
    xg_store(xa, 0);
    bar_arrive(NB_T + 3, 288);
  } else {
#pragma unroll
    for (int j = 0; j < 8; j += 2) stsm4(xa.a ^ (j * 16), y[j][0], y[j][1], y[j + 1][0], y[j + 1][1]);
    __syncwarp();
#pragma unroll
    for (int k = 0; k < 4; ++k) {
      const uint4 v = lds4((xa.b ^ ((k & 1) * 64)) + k * 512);
      stw4(xa.dst + ((k & 1) * 8 + (k >> 1)) * 64, v.x, v.y, v.z, v.w);
    }
  }
  PROF(25, m_epi);
}

#define HDELAY 200
#define ODELAY 200
#define FDELAY 300
#define PZB B_X + 48
#define H5 1
#define SRDELAY 350

DEV void o_load(const Params& P, int c, int e, int lane, int layer) {
  PW(8 + e)
  const int J = 2 * (c >> 3) + 1 - e;
#pragma unroll
  for (int n = 0; n < 8; ++n) mbar_expect1(B_O + 64 * e + 8 * n, n ? 8192 : 0);
  const uint4* src = P.S->O + J * 4096;
  const uint32_t* fp = P.S->F + (J * 32 + (lane & 28));
  keep(fp, P.zero);
  bar_sync(NB_T + 1 + e, 160);
  flag_set1(P.S->F + (J * 32 + 4 * (c & 7)));
  delay(ODELAY);
  PROF(26, a_go);
  poll(fp, 1);
  PROF(25, h_seen);
  bar_sync_if(NB_Q, 64, e);
  uint32_t dst = e ? SM_S1 : SM_XA, bar = B_O + 64 * e;
#pragma unroll 1
  for (int n = c & 7; n > (c & 7) - 7; --n) {
    dst += 8192; bar += 8;
    bulk(dst, src + (n > 0 ? 0 : 512), 8192, bar);
    src += 512;
  }
  bar_arrive_if(NB_Q, 64, !e);
  PROF(28, a_o);
}

DEV void stats(const Params& P, int c, int w, int lane, int layer) {
  PW(12 + w)
  lane = opq(lane);
  const int r = 2 * (lane >> 3), k = (2 * (c & 3) + ((lane >> 2) & 1)) ^ r, e = 1 - ((c >> 2) & 1);
  const uint32_t o = (32 * w + r) * 128 + k * 16 + (lane & 3) * 4;
  const uint32_t no0 = (lane & 7) != r, no1 = ((lane & 7) ^ 4) != r + 1;
  uint32_t* st = (uint32_t*)P.S->ST + (16 * c + 2 * (lane & 7) + (lane >> 4));
  keep(st, P.zero);
  float v[4] = {0.f, 0.f, 0.f, 0.f};
#pragma unroll 1
  for (int q = 0; q < 4; ++q) {
    mbar_wait(B_X + 16 * q + 8 * e, layer);
    PROF(19 + q, s_l);
    uint32_t x[8];
    for (int it = 0;; ++it) {
#pragma unroll
      for (int z = 0; z < 8; ++z) x[z] = lds1v(xstage(q, e) + (o ^ ((z & 1) * 144)) + (z >> 1) * 1024);
      const uint32_t ok = (both(x[0], x[2], layer) & both(x[4], x[6], layer) | no0) & (both(x[1], x[3], layer) & both(x[5], x[7], layer) | no1);
      if (__all_sync(0xffffffffu, ok & 1)) break;
      spin_guard(it);
    }
    mbar_arrive1(B_F + 8 * q);
#pragma unroll
    for (int z = 0; z < 8; ++z) {
      const float lo = bflo(x[z]), hi = bfhi(x[z]);
      v[0] += lo; v[1] += lo * lo; v[2] += hi; v[3] += hi * hi;
    }
  }
  PROFD(14, s_part, __float_as_uint(v[0]));
  fold<2>(v, lane, 16); fold<1>(v, lane, 8);
  PROFD(16, s_fold, __float_as_uint(v[0]));
  if (w) {
    sts1(SM_MISC - 128 + w * 128 + lane * 4, __float_as_uint(v[0]));
    bar_arrive(NB_P, 128);
  } else {
    mbar_wait(B_ST + 8, layer);
    bar_sync(NB_P, 128);
    v[0] += lds1f(SM_MISC + lane * 4) + lds1f(SM_MISC + 128 + lane * 4) + lds1f(SM_MISC + 256 + lane * 4);
    float m;
    const float sd = ln_sd(v[0], __shfl_xor_sync(0xffffffffu, v[0], 8), m);
    if (!(lane & 8)) str1(st, pack2(m, sd));
    PROF(17, s_pub);
    uint4 s;
    for (int it = 0;; ++it) {
      s = ldr4(P.S->ST + ((c >> 3) * 32 + lane));
      if (__all_sync(0xffffffffu, min4(s) != 0u)) break;
      spin_guard(it);
    }
    PROF(18, s_seen);
    const float r0 = rcp(bfhi(s.x)), r1 = rcp(bfhi(s.y)), r2 = rcp(bfhi(s.z)), r3 = rcp(bfhi(s.w));
    const uint32_t sg = 0x80008000u;
    sts4(SM_MISC + lane * 16, prmt(s.x, s.x, 0x1010) ^ sg, prmt(s.y, s.y, 0x1010) ^ sg, prmt(s.z, s.z, 0x1010) ^ sg, prmt(s.w, s.w, 0x1010) ^ sg);
    sts4(SM_STAT + 256 + lane * 32, __float_as_uint(r0), __float_as_uint(r1), pack2(r0, r1), prmt(s.x, s.y, 0x7632));
    sts4(SM_STAT + 272 + lane * 32, __float_as_uint(r2), __float_as_uint(r3), pack2(r2, r3), prmt(s.z, s.w, 0x7632));
    __syncwarp();
    mbar_arrive1(B_ST);
  }
  PROF(15, s_stat);
  if (w == 1) {
    mbar_wait(B_ST, layer);
    if (c >= 8) {
      uint2 s;
      for (int it = 0;; ++it) {
        s = ldr2((const uint2*)P.S->ST + ((c >> 3) * 64 - 12 + (lane & 11)));
        if (__all_sync(0xffffffffu, min(s.x, s.y) != 0u)) break;
        spin_guard(it);
      }
      const float r0 = rcp(bfhi(s.x)), r1 = rcp(bfhi(s.y));
      sts4(SM_STAT + 64 + (lane & 11) * 16, __float_as_uint(r0), __float_as_uint(r1), pack2(r0, r1), prmt(s.x, s.y, 0x7632));
    }
    bar_arrive(NB_H, 160);
  }
  if (w >= 2) {
    const uint4* h = P.S->H + (c * 256 + (w & 1) * 128 + lane);
    uint4 hv[4];
#pragma unroll
    for (int z = 0; z < 4; ++z) hv[z] = make_uint4(0, 0, 0, 0);
    bar_sync(NB_RL, 128);
    PROFD(26, s_hb, lds1v(SM_MISC));
    delay(HDELAY);
    for (int it = 0; c >= 8; ++it) {
#pragma unroll
      for (int z = 0; z < 4; ++z) hv[z] = ldr4(h + z * 32);
      if (__all_sync(0xffffffffu, min(min(hv[0].x, hv[1].x), min(hv[2].x, hv[3].x)) != 0u)) break;
      spin_guard(it);
    }
    mbar_wait(B_F + 24, layer);
#pragma unroll
    for (int z = 0; z < 4; ++z) sts4(kvslot(0) + (w & 1) * 2048 + lane * 16 + z * 512, hv[z].x, hv[z].y, movm(hv[z].z), movm(hv[z].w));
    bar_arrive(NB_H, 160);
    PROF(25, s_halo);
  }
}

DEV void finalize(const Params& P, int c, int lane, int layer) {
  PW(12)
  uint2* so = (uint2*)P.S->SR[layer] + ((lane >> 3) * 1024 + (lane & 2) * 256 + 4 * c + ((lane >> 1) & 2) + (lane & 1));
  const uint4* ps = &P.S->PS[c * 64 + lane];
  keep(so, P.zero); keep(ps, P.zero);
  uint4 a, b;
  if (layer == 0) {
    bar_sync(NB_P, 256);
    a = lds4(SM_RES + 8192 + lane * 16); b = lds4(SM_RES + 8704 + lane * 16);
  } else {
    mbar_wait(B_ED + 8 - 2 * (c & 4), 0);
    delay(FDELAY);
    for (int it = 0;; ++it) {
      a = ldr4(ps); b = ldr4(ps + 32);
      if (__all_sync(0xffffffffu, min(a.x, b.x) != 0u)) break;
      spin_guard(it);
    }
  }
  float z[4] = {__uint_as_float(a.x) + __uint_as_float(b.x), __uint_as_float(a.y) + __uint_as_float(b.y),
                __uint_as_float(a.z) + __uint_as_float(b.z), __uint_as_float(a.w) + __uint_as_float(b.w)};
#pragma unroll
  for (int o = 8; o < 32; o <<= 1)
#pragma unroll
    for (int k = 0; k < 4; ++k) z[k] += __shfl_xor_sync(0xffffffffu, z[k], o);
  const float m0 = z[0] * (1.f / 512.f), m1 = z[2] * (1.f / 512.f);
  const float r0 = rsq(fmaxf(z[1] * (1.f / 512.f) - m0 * m0, 0.f) + 1e-5f), r1 = rsq(fmaxf(z[3] * (1.f / 512.f) - m1 * m1, 0.f) + 1e-5f);
  const uint32_t wr = nz(pack2(r0, r1)), wm = pack2(m0, m1);
  str2(so, wr, wm); str2(so + 4096, wr, wm);
  PROF(23, s_sr);
}

DEV void announce(const Params& P, int c, int lane, int layer) {
  PW(13)
  uint32_t* cp = cnt_at(P, 5 * layer, c, lane);
  keep(cp, P.zero);
  bar_sync(NB_T + 3, layer ? 288 : 256);
  cnt_add(cp, 1, lane < NCOPY);
  if (!layer) { bar_sync(NB_Q, 416); fence_async_smem(); }
  PROF(24, s_own);
}

DEV void fetch(const Params& P, int c, int lane, int layer) {
  PW(13)
  mbar_expect1(B_E, 24576);
  cnt_wait(P, 5 * layer, c, lane);
#pragma unroll
  for (int k = 0; k < 4; ++k) bulk(SM_R + k * 16384 + R_B, P.S->XG + (128 * k + c) * 256, 4096, B_E);
  if (layer) delay(SRDELAY);
  bulk(SM_RES, P.S->SR[layer][c >> 4], 8192, B_E);
  if (!layer) { l2_prefetch(P.wqkv + c * 6144, 12288); l2_prefetch(P.wo + c * 2048, 4096); }
  PROF(25, s_all);
}

DEV float2 cs_rows(const Params& P, int row, int col, int lane) {
  float cs[8];
#pragma unroll
  for (int k = 0; k < 8; ++k) cs[k] = 0.f;
  uint4 v[8];
#pragma unroll
  for (int k = 0; k < 8; ++k) v[k] = ldnc4(P.wqkv + ((row + (lane >> 3)) * 1536 + col + 8 * (lane & 7)) + 4 * k * 1536);
#pragma unroll
  for (int k = 0; k < 8; ++k) {
    cs[0] += bflo(v[k].x); cs[1] += bfhi(v[k].x); cs[2] += bflo(v[k].y); cs[3] += bfhi(v[k].y);
    cs[4] += bflo(v[k].z); cs[5] += bfhi(v[k].z); cs[6] += bflo(v[k].w); cs[7] += bfhi(v[k].w);
  }
  fold<4>(cs, lane, 16); fold<2>(cs, lane, 8);
  return make_float2(cs[0], cs[1]);
}
DEV void cs_put(const Params& P, int b, int lane, float x, float y) {
  const uint32_t hi = pack2(x, y);
  uint32_t* p = (uint32_t*)P.S->CS + ((b & 7) * 192 + (b >> 3) * 64 + (lane & 7) * 8 + (lane >> 3));
  str1(p, nz(hi)); str1(p + 4, nz(pack2(x - bflo(hi), y - bfhi(hi))));
}
DEV void cs_spare(const Params& P, const CUtensorMap* mW, int j, int n, int warp, int lane) {
  mbar_init1(B_W + 8 * warp, warp < 8 ? 1 : 12);
  sts2f(SM_TAP + lane * 8, __uint_as_float(0x3F803F80u), __uint_as_float(0x3F803F80u));
  fence_async_smem();
  __syncthreads();
#pragma unroll 1
  for (int cg = j, ph = 0; cg < 8; cg += n, ph ^= 1) {
    if (warp == 12) {
#pragma unroll 1
      for (int h = 0; h < 8; ++h) {
        mbar_wait(B_W + 64 + 8 * h, ph ^ 1);
        mbar_expect1(B_W + 8 * h, 24576);
        tma3(SB + h * 24576, mW, 64 * cg, 64 * h, B_W + 8 * h);
      }
    } else if (warp < 12) {
      float d[4];
      zerov(d);
#pragma unroll 1
      for (int h = 0; h < 8; ++h) {
        mbar_wait(B_W + 8 * h, ph);
        wg_fence();
#pragma unroll
        for (int k = 0; k < 4; ++k) wg_ss8(d, mkdesc(SB + h * 24576 + (warp >> 2) * 8192, 16, 1024, 1) + k * 128, mkdesc(SM_TAP, 128, 128, 0));
        wg_commit();
        wg_wait<0>();
        mbar_arrive1(B_W + 64 + 8 * h);
      }
      const float x = (lane & 2) ? d[2] : d[0], y = __shfl_xor_sync(0xffffffffu, x, 4);
      const uint32_t hi = pack2(x, y), lo = pack2(x - bflo(hi), y - bfhi(hi));
      if (!(lane & 4)) str1((uint32_t*)P.S->CS + (cg * 192 + warp * 16 + (lane & 3) * 4 + (lane >> 3)), nz((lane & 1) ? lo : hi));
      __syncwarp();
    }
  }
}
DEV void cs_alone(const Params& P, int b, int lane) {
  float x = 0.f, y = 0.f;
#pragma unroll 1
  for (int k = 0; k < 16; ++k) { const float2 u = cs_rows(P, 32 * k, 64 * b, lane); x += u.x; y += u.y; }
  cs_put(P, b, lane, x, y);
}
DEV void cs_get(const Params& P, int cg, int lane) {
  const uint4* p = (const uint4*)P.S->CS + (cg * 48 + min(lane, 23) * 2);
  uint4 a, b;
  for (int it = 0;; ++it) {
    a = ldr4(p); b = ldr4(p + 1);
    if (__all_sync(0xffffffffu, min(min4(a), min4(b)) != 0u)) break;
    spin_guard(it);
  }
  sts4(SM_CS + min(lane, 23) * 32, a.x, a.y, a.z, a.w); sts4(SM_CS + min(lane, 23) * 32 + 16, b.x, b.y, b.z, b.w);
  fence_async_smem();
  __syncwarp();
  mbar_arrive1(B_CS);
}

DEV void x0_get(uint32_t (&x)[8][2], uint32_t a) {
  asm volatile("cp.async.wait_group 0;" ::: "memory");
#pragma unroll
  for (int z = 0; z < 4; ++z) {
    const uint4 v = lds4(a + z * 512);
    x[2 * (z & 2)][z & 1] = v.x; x[2 * (z & 2) + 1][z & 1] = v.y; x[2 * (z & 2) + 2][z & 1] = v.z; x[2 * (z & 2) + 3][z & 1] = v.w;
  }
}

DEV void par_load(const Params& P, int ch, int m, uint32_t (&pv)[8], bool c) {
  const int mo = ch * 128 + m;
  pv[0] = ld16_if(P.Are + mo, c); pv[1] = ld16_if(P.Aim + mo, c); pv[2] = ld16_if(P.Bre + mo, c); pv[3] = ld16_if(P.Bim + mo, c);
  pv[4] = ld16_if(P.Cre + mo, c); pv[5] = ld16_if(P.Cim + mo, c); pv[6] = ld16_if(P.logdt + ch, c); pv[7] = ld16_if(P.dskip + ch, c);
}

template <bool BY_SM> __global__ void __launch_bounds__(NTHR, 1)
fused_kernel(const __grid_constant__ Params P, const __grid_constant__ CUtensorMap mapW,
             const __grid_constant__ CUtensorMap mapWo) {
  extern __shared__ __align__(1024) uint8_t smem_raw[];
  uint32_t smid; asm("mov.u32 %0,%%smid;" : "=r"(smid));
  if (!BY_SM) smid = blockIdx.x;
  const int role = 2 * P.role[(smid >> 1) + (threadIdx.x >> 10)] + (smid & 1);
  uint32_t pv[8];
  par_load(P, (threadIdx.x & 384) + (role & 127), threadIdx.x & 127, pv, threadIdx.x < 384 && role < 128);
  const int warp0 = __shfl_sync(0xffffffffu, threadIdx.x >> 5, 0), lane0 = threadIdx.x & 31, c = __shfl_sync(0xffffffffu, role, 0);
  if (c >= 128) {
    if (threadIdx.x < NCOPY * NSUB)
#pragma unroll 1
      for (int it = 0; it < 256 && ldr1(P.S->C + 32 * threadIdx.x) < 128 / NSUB; ++it) __nanosleep(200);
    __syncwarp();
    cs_spare(P, &mapW, c - 128, gridDim.x - 128, warp0, lane0);
    return;
  }
  const int cg = c & 7;
  PW(warp0)
  uint32_t dskip;
  {
    [[maybe_unused]] const int layer = 0;
    const int lane = lane0, g = lane >> 2, t = lane & 3, warp = warp0, k4 = warp >> 2, w = warp & 3;
    __syncthreads();
    const uint16_t* r = P.x0 + ((k4 < 2 ? 8192 * c + 64 * warp : (128 * (c >> 3) + 16 * (warp - 8)) * 512 + 64 * cg) + 1024 * g + 8 * t);
    const uint32_t xa = SM_R + k4 * 16384 + w * 2048 + lane * 16;
#pragma unroll
    for (int z = 0; z < 4; ++z) cp16(xa + z * 512, r + (z & 1) * 512 + (z & 2) * 16);
    asm volatile("cp.async.commit_group;" ::: "memory");
    sts4(SM_TAP + k4 * TAP_SZ + (32 * w + lane) * 16, 0, 0, 0, 0);
    sts4z_if(SM_TAP + k4 * TAP_SZ + 2048 + (32 * w + lane) * 16, w < 3);
    const XgAddr xd = xg_addr<false>(P.S->XG + (64 * cg * 256 + 16 * (c >> 3) + 8 * (k4 & 1)), SM_R + k4 * 16384 + 8192, w, lane, P.zero);
    uint32_t x[8][2];
    if (k4 == 3) {
      if (threadIdx.x == 448) {
        asm volatile("prefetch.tensormap [%0];" :: "l"(&mapW) : "memory");
        asm volatile("prefetch.tensormap [%0];" :: "l"(&mapWo) : "memory");
      }
      __syncwarp();
      par_load(P, 128 * k4 + c, 32 * w + lane, pv, true);
      if (s2u(smem_raw) != SB) __trap();
      sts4(SM_STAT - 32 + min(lane, 17) * 16, 0x3F800000u, 0x3F800000u, 0x3F803F80u, 0x3F803F80u);
      x0_get(x, xa);
      PROF(27, a_ld);
      xg_put<false>(xd, x);
      bar_sync(NB_WG + 3, 128);
      xg_store(xd, 1);
      bar_arrive(NB_T + 3, 256);
#pragma unroll
      for (int n = 0; n < 14; ++n) mbar_init1(SM_BAR + (n < 10 ? w * 80 : 240 + w * 32) + n * 8, n < 10 ? 1 : (CNT >> (8 * w + 2 * (n - 10 & 2))) & 15);
      bar_sync(NB_Q, 416);
    }
    tables(pv, k4, w, lane);
    if (k4 < 3) {
      x0_get(x, xa);
      if (k4 < 2) {
        const float4 s = gram(x, g, P.zero);
        if (t == (g >> 1)) sts4f(SM_RES + 8192 + (warp * 8 + g) * 16, s.x, s.y, s.z, s.w);
        __syncwarp();
        bar_arrive_if(NB_P, 256, warp != 7);
      } else {
        xg_put<false>(xd, x);
        bar_sync(NB_WG + 2, 128);
        xg_store(xd, 1);
        bar_arrive_if(NB_T + 3, 256, w);
      }
    }
    dskip = pv[7];
    PROF(1, a_x0);
  }
#pragma unroll 1
  for (int layer = 0; layer < 2; ++layer) {
    int lane = lane_here(P.zero);
    const int warp = warp0 | (layer & P.zero), k4 = warp >> 2, w = warp & 3;
    if (warp == (layer ? 12 : 7)) finalize(P, c, lane, layer);
    if (warp == (layer ? 13 : 8)) { announce(P, c, lane, layer); fetch(P, c, lane, layer); }
    if (layer == 0) {
      taps(dskip, k4, w, lane);
    }
    conv(P, &mapW, c, k4, w, layer);
    lane = lane_here(P.zero);
    if (k4 < 2) {
      bar_arrive_if(NB_H, 256, warp != 4);
      if (warp == 0) {
        mbar_wait(B_K, 0);
        cnt_wait(P, 1 + 5 * layer, c, lane);
        x_load(P, c, 0, layer);
        PROF(27, m_xi);
      }
      attn_phase(P, c, k4, w, lane, layer);
    } else {
      bar_arrive_if(NB_RL, 256, warp >= 10);
      if (k4 == 3) {
        stats(P, c, w, lane, layer);
      } else if (w < 2) {
        bar_sync_if(NB_RL, 256, w);
        cnt_wait(P, 3 + 5 * layer + w, c, lane);
        bar_sync_if(NB_RL, 256, !w);
        if (w) mbar_wait(B_F, layer);
        x_load(P, c, 2 + w, layer);
        if (H5 && w) w_load(&mapW, cg, 5);
        PROF(14, h_xi);
        if (w == 1) str4(&P.S->SR[layer][lane >> 2][4 * c + (lane & 3)], 0, 0, 0, 0);
      } else if (w == 2) {
        mbar_expect1(B_WO, 65536);
        mbar_expect1(B_RES, 16384);
#pragma unroll 1
        for (int q = 0; q < 4; ++q) {
          if (FH && q < 2) { mbar_wait(B_FH + 8 * q, layer); w_load(&mapW, cg, 4 + 2 * q); }
          mbar_wait(B_F + 8 * q, layer);
          if (!FH && q < 2) w_load(&mapW, cg, 4 + 2 * q);
          if (q == 1 || (q == 0 && !H5)) w_load(&mapW, cg, 5 + 2 * q);
          if (q == 2) {
            mbar_wait(B_ST, layer);
#pragma unroll 1
            for (int n = 0; n < 8; ++n) tma5(SM_R + n * 8192, &mapWo, 64 * cg, 2 * piece(n, cg), B_WO);
          }
          if (q == 3) {
#pragma unroll
            for (int e = 0; e < 2; ++e) bulk(SM_RES + e * 8192, P.S->XF + ((2 * (c >> 3) + 1 - e) * 4096 + cg * 512), 8192, B_RES);
          }
          PROF(15 + q, h_w);
        }
      }
      if (warp == 11) {
        if (!BY_SM && c < 24 && layer == 0) cs_alone(P, c, lane);
#pragma unroll
        for (int z = 0; z < 8; ++z) sts4(SM_RES + 10240 + lane * 16 + z * 512, ~0u, ~0u, ~0u, ~0u);
        fence_async_smem();
        mbar_wait(PZB, layer);
#pragma unroll
        for (int z = 0; z < 4; ++z) bulk_store(&P.S->O[((c >> 3) * 16 + cg) * 512] + ((z >> 1) * 4096 + (z & 1) * 256), SM_RES + 10240, 4096);
        asm volatile("cp.async.bulk.commit_group;\ncp.async.bulk.wait_group 0;" ::: "memory");
        mbar_arrive1(B_ST + 8);
        PROF(18, h_pz);
      }
      if (warp == 8 && layer == 0) { cs_get(P, cg, lane); PROF(20, h_cs); }
      if (warp < 10) o_load(P, c, w, lane, layer);
    }
    asm volatile("mov.b32 %0,0;" : "=r"(dskip));
  }
}

typedef CUresult (*EncodeFn)(CUtensorMap*, CUtensorMapDataType, cuuint32_t, void*, const cuuint64_t*, const cuuint64_t*,
                             const cuuint32_t*, const cuuint32_t*, CUtensorMapInterleave, CUtensorMapSwizzle,
                             CUtensorMapL2promotion, CUtensorMapFloatOOBfill);

#define PLAIN false
static int place_roles(uint8_t* role) {
  int dev = 0, nsm = 0;
  cudaGetDevice(&dev);
  cudaDeviceGetAttribute(&nsm, cudaDevAttrMultiProcessorCount, dev);
  if (nsm <= 128 || nsm > 144 || (nsm & 1)) return 0;
  cudaFuncSetAttribute(fused_kernel<true>, cudaFuncAttributeNonPortableClusterSizeAllowed, 1);
  int occ[9] = {0};
  for (int k = 2; k <= 8; ++k) {
    cudaLaunchConfig_t cfg = {};
    cudaLaunchAttribute at[1];
    at[0].id = cudaLaunchAttributeClusterDimension;
    at[0].val.clusterDim.x = 2 * k; at[0].val.clusterDim.y = 1; at[0].val.clusterDim.z = 1;
    cfg.gridDim = dim3(2 * k); cfg.blockDim = dim3(NTHR); cfg.dynamicSmemBytes = SM_TOTAL; cfg.attrs = at; cfg.numAttrs = 1;
    if (cudaOccupancyMaxActiveClusters(&occ[k], fused_kernel<true>, &cfg) != cudaSuccess) { cudaGetLastError(); occ[k] = 0; }
  }
  int n[10];
  n[7] = occ[8]; n[6] = occ[7]; n[5] = occ[6] - 0; n[4] = occ[5];
  n[3] = occ[4] - n[7]; n[1] = occ[2] - n[3] - n[5] - n[7]; n[0] = n[2] = n[1];
  n[8] = occ[3] - n[2] - n[5];
  const int ntpc = nsm / 2;
  int sum = 0;
  bool ok = n[0] > 0 && n[0] <= 8;
  for (int r = 0; r < 9; ++r) { ok = ok && n[r] >= 0 && (r == 0 || n[r] <= n[r - 1]); sum += n[r]; }
  if (!ok || sum > ntpc) { for (int r = 0; r < 9; ++r) n[r] = r < 8 ? 8 : 0; sum = 64; }
  int tp[8][9], cnt[8] = {0}, pool[72], np = 0, id = 0;
  for (int r = 0; r < 9; ++r)
    for (int g = n[0] - n[r]; g < n[0]; ++g) tp[g][cnt[g]++] = id++;
  for (; id < ntpc; ++id) pool[np++] = id;
  int order[72], no = 0;
  for (int g = 0; g < n[0]; ++g) {
    const int full = cnt[g] / 4 * 4;
    for (int k = 0; k < cnt[g]; ++k) { if (k < full) order[no++] = tp[g][k]; else pool[np++] = tp[g][k]; }
  }
  for (int k = 0; k < np; ++k) order[no++] = pool[k];
  for (int k = 0; k < ntpc; ++k) role[order[k]] = k;
  return nsm;
}

extern "C" void kernel_launch(void* const* d_in, const int* in_sizes, int n_in, void* d_out, int out_size) {
  (void)in_sizes; (void)n_in; (void)out_size;
  static EncodeFn enc = nullptr;
  static uint8_t role[72];
  static int nsm = 0;
  static void* scratch = nullptr;
  if (!enc) {
    void* fn = nullptr;
    cudaDriverEntryPointQueryResult qr;
    cudaGetDriverEntryPoint("cuTensorMapEncodeTiled", &fn, cudaEnableDefault, &qr);
    enc = (EncodeFn)fn;
    cudaFuncSetAttribute(fused_kernel<true>, cudaFuncAttributeMaxDynamicSharedMemorySize, SM_TOTAL);
    cudaFuncSetAttribute(fused_kernel<PLAIN>, cudaFuncAttributeMaxDynamicSharedMemorySize, SM_TOTAL);
    nsm = place_roles(role);
    cudaGetSymbolAddress(&scratch, g_S);
  }
  CUtensorMap mW, mWo;
  {
    cuuint64_t dim[3] = {512, 512, 3}, str[2] = {3072, 1024};
    cuuint32_t box[3] = {64, 64, 3}, es[3] = {1, 1, 1};
    enc(&mW, CU_TENSOR_MAP_DATA_TYPE_BFLOAT16, 3, d_in[10], dim, str, box, es, CU_TENSOR_MAP_INTERLEAVE_NONE,
        CU_TENSOR_MAP_SWIZZLE_128B, CU_TENSOR_MAP_L2_PROMOTION_NONE, CU_TENSOR_MAP_FLOAT_OOB_FILL_NONE);
  }
  {
    cuuint64_t dim[5] = {512, 2, 4, 4, 16}, str[4] = {1024, 8192, 2048, 32768};
    cuuint32_t box[5] = {64, 2, 4, 4, 2}, es[5] = {1, 1, 1, 1, 1};
    enc(&mWo, CU_TENSOR_MAP_DATA_TYPE_BFLOAT16, 5, d_in[11], dim, str, box, es, CU_TENSOR_MAP_INTERLEAVE_NONE,
        CU_TENSOR_MAP_SWIZZLE_128B, CU_TENSOR_MAP_L2_PROMOTION_NONE, CU_TENSOR_MAP_FLOAT_OOB_FILL_NONE);
  }
  Params P;
  P.x0 = (const uint16_t*)d_in[0]; P.Are = (const uint16_t*)d_in[1]; P.Aim = (const uint16_t*)d_in[2];
  P.Bre = (const uint16_t*)d_in[3]; P.Bim = (const uint16_t*)d_in[4]; P.Cre = (const uint16_t*)d_in[5];
  P.Cim = (const uint16_t*)d_in[6]; P.logdt = (const uint16_t*)d_in[7]; P.dskip = (const uint16_t*)d_in[8];
  P.wqkv = (const uint16_t*)d_in[10]; P.wo = (const uint16_t*)d_in[11]; P.out = (uint16_t*)d_out;
  for (int k = 0; k < 72; ++k) P.role[k] = nsm > 0 ? role[k] : k;
  P.pad = 0;
  P.zero = 0;
  P.S = (Scratch*)scratch;
  if (nsm > 0) fused_kernel<true><<<nsm, NTHR, SM_TOTAL, cudaStreamPerThread>>>(P, mW, mWo);
  else fused_kernel<PLAIN><<<128, NTHR, SM_TOTAL, cudaStreamPerThread>>>(P, mW, mWo);
}
```
